```python
import torch

def _softmax(x, axis=-1):
    return torch.softmax(x, dim=axis)
def _gelu(x):
    return torch.nn.functional.gelu(x, approximate="tanh")
def _silu(x):
    return torch.nn.functional.silu(x)
def _sigmoid(x):
    return torch.sigmoid(x)
def _layernorm(x, axis=-1, eps=1e-5):
    m = x.mean(dim=axis, keepdim=True)
    v = x.var(dim=axis, keepdim=True, unbiased=False)
    return (x - m) / torch.sqrt(v + eps)
def _scatter_add(tgt, idx, src, axis=0):
    return tgt.clone().index_add_(axis, idx, src)
def _segment_sum(src, seg, n):
    out = torch.zeros((n,) + src.shape[1:], dtype=src.dtype)
    return out.index_add_(0, seg, src)
def _pad(x, pw):
    flat = tuple(v for pair in reversed(pw) for v in pair)
    return torch.nn.functional.pad(x, flat)

kernel_name = 'standalone__deep_cross_xdeepfm__recsys'

def setup_inputs():

    _w = (lambda a: (lambda t: t.to(torch.bfloat16) if t.is_floating_point() else t)(torch.as_tensor(a)))
    B, F, D, L = 4096, 26, 16, 6
    V = min(1000, 100000)
    Din = F * D
    return {
        "idx": _w((lambda lo, hi, *s: torch.randint(lo, hi, s))(0, V, B, F).to(torch.int64)),
        "table": _w((lambda *s: torch.randn(*s, dtype=torch.bfloat16) * 0.8)(V, D)),
        "ws_cin": _w((lambda *s: torch.randn(*s, dtype=torch.bfloat16) * 0.4)(L, F, F, F) * (1.0 / F)),
        "w_cin_out": _w((lambda *s: torch.randn(*s, dtype=torch.bfloat16) * 0.4)(L * F) * ((L * F) ** -0.5)),
        "w_dnn1": _w((lambda *s: torch.randn(*s, dtype=torch.bfloat16) * 0.8)(Din, Din) * (Din ** -0.5)),
        "b_dnn1": _w((lambda *s: torch.randn(*s, dtype=torch.bfloat16) * 3.2)(Din) * 0.1),
        "w_dnn2": _w((lambda *s: torch.randn(*s, dtype=torch.bfloat16) * 0.4)(Din) * (Din ** -0.5)),
        "b_out": _w((lambda *s: torch.randn(*s, dtype=torch.bfloat16) * 0.4)(1)),
    }

def reference(idx, table, ws_cin, w_cin_out, w_dnn1, b_dnn1, w_dnn2, b_out):
    x0 = table[idx]
    B = x0.shape[0]
    L = ws_cin.shape[0]
    xk = x0
    pooled = []
    for l in range(L):
        xk = torch.einsum('bid,bjd,hij->bhd', xk, x0, ws_cin[l])
        pooled.append(xk.sum(axis=-1))
    p_plus = torch.stack(pooled, axis=1).reshape(B, -1)
    logit_cin = p_plus @ w_cin_out
    h = x0.reshape(B, -1)
    h = _gelu(h @ w_dnn1 + b_dnn1)
    logit_dnn = h @ w_dnn2
    return logit_cin + logit_dnn + b_out
```

```cpp
#include <cuda_runtime.h>
#include <cuda_bf16.h>
#include <cuda.h>
#include <stdint.h>

typedef __nv_bfloat16 bf16;

constexpr int NF = 26;
constexpr int DIN = 416;
constexpr int NCTA = 128;

constexpr int G0_KS = 24, G0_N = 56, G0_SLAB = G0_N * 32;
constexpr int L_KS = 43, L_SLAB = 1024;
constexpr int G0_BYTES = G0_KS * G0_SLAB;
constexpr int L_BYTES = L_KS * L_SLAB;
constexpr int IMG_BYTES = G0_BYTES + 3 * L_BYTES;

constexpr int W1_STAGES = 13, W1_SLOTS = 8, W1_STAGE_BYTES = 16384;
constexpr int OFF_LA = 81920;
constexpr int OFF_LB = 0;
constexpr int OFF_LC0 = 44032;
constexpr int OFF_LC1 = 125952;
constexpr int LC_SPLIT = 37;
constexpr int OFF_G0 = 132096;
constexpr int OFF_X0 = 175104;
constexpr int X0_FS = 2064;
constexpr int X0_BYTES = NF * X0_FS;
constexpr int OFF_MISC = OFF_X0 + X0_BYTES;
constexpr int OFF_BAR = OFF_MISC;
constexpr int OFF_BW = OFF_BAR + 192;
constexpr int OFF_DPART = OFF_BW + 1664;
constexpr int OFF_DSUM = OFF_DPART + 512;
constexpr int OFF_WTAB = OFF_DSUM + 256;
constexpr int OFF_LOFF = OFF_WTAB + 256;
constexpr int SMEM_BYTES = OFF_LOFF + 512;
static_assert(SMEM_BYTES <= 232448, "smem");

constexpr int BAR_W1FULL = 0, BAR_W1EMPTY = 8, BAR_IMG = 16  , BAR_X0 = 20, BAR_DNN = 21;

__device__ __align__(1024) unsigned char g_img[IMG_BYTES];
__device__ unsigned long long g_part[NCTA * 64];
__device__ unsigned g_epoch;

__device__ __forceinline__ uint32_t smem_u32(const void* p) { return (uint32_t)__cvta_generic_to_shared(p); }
__device__ __forceinline__ void mbar_init(uint32_t bar, uint32_t cnt) {
  asm volatile("mbarrier.init.shared::cta.b64 [%0], %1;" ::"r"(bar), "r"(cnt) : "memory");
}
__device__ __forceinline__ void mbar_expect_tx(uint32_t bar, uint32_t bytes) {
  asm volatile("mbarrier.arrive.expect_tx.shared::cta.b64 _, [%0], %1;" ::"r"(bar), "r"(bytes) : "memory");
}
__device__ __forceinline__ void mbar_arrive(uint32_t bar) {
  asm volatile("mbarrier.arrive.shared::cta.b64 _, [%0];" ::"r"(bar) : "memory");
}
__device__ __forceinline__ bool mbar_try(uint32_t bar, uint32_t parity) {
  uint32_t ok;
  asm volatile("{\n.reg .pred p;\nmbarrier.try_wait.parity.shared::cta.b64 p, [%1], %2;\nselp.u32 %0, 1, 0, p;\n}\n"
               : "=r"(ok) : "r"(bar), "r"(parity) : "memory");
  return ok != 0;
}
__device__ __forceinline__ void mbar_wait(uint32_t bar, uint32_t parity) {
  for (uint32_t it = 0; it < (1u << 26); it++)
    if (mbar_try(bar, parity)) return;
  __trap();
}
__device__ __forceinline__ void bulk_g2s(uint32_t dst, const void* src, uint32_t bytes, uint32_t bar) {
  asm volatile("cp.async.bulk.shared::cluster.global.mbarrier::complete_tx::bytes [%0], [%1], %2, [%3];"
               ::"r"(dst), "l"(src), "r"(bytes), "r"(bar) : "memory");
}
__device__ __forceinline__ void tma_2d(uint32_t dst, const CUtensorMap* tm, int x, int y, uint32_t bar) {
  asm volatile("cp.async.bulk.tensor.2d.shared::cluster.global.mbarrier::complete_tx::bytes [%0], [%1, {%3, %4}], [%2];"
               ::"r"(dst), "l"(tm), "r"(bar), "r"(x), "r"(y) : "memory");
}
__device__ __forceinline__ void cp_async16(uint32_t dst, const void* src) {
  asm volatile("cp.async.cg.shared.global [%0], [%1], 16;" ::"r"(dst), "l"(src) : "memory");
}
__device__ __forceinline__ void fence_proxy_async() { asm volatile("fence.proxy.async.shared::cta;" ::: "memory"); }
__device__ __forceinline__ void named_bar(int id, int n) { asm volatile("bar.sync %0, %1;" ::"r"(id), "r"(n) : "memory"); }

__device__ __forceinline__ void wg_fence() { asm volatile("wgmma.fence.sync.aligned;" ::: "memory"); }
__device__ __forceinline__ void wg_commit() { asm volatile("wgmma.commit_group.sync.aligned;" ::: "memory"); }
template <int N> __device__ __forceinline__ void wg_wait() { asm volatile("wgmma.wait_group.sync.aligned %0;" ::"n"(N) : "memory"); }
template <int N> __device__ __forceinline__ void reg_fence(float (&d)[N]) {
#pragma unroll
  for (int i = 0; i < N; i++) asm volatile("" : "+f"(d[i])::"memory");
}
__device__ __forceinline__ uint64_t make_desc(uint32_t saddr, uint32_t lbo, uint32_t sbo, uint32_t swz) {
  return (uint64_t)((saddr & 0x3FFFF) >> 4) | ((uint64_t)(lbo >> 4) << 16) | ((uint64_t)(sbo >> 4) << 32) | ((uint64_t)swz << 62);
}

#define ACC4(d, o) "+f"(d[o]), "+f"(d[o + 1]), "+f"(d[o + 2]), "+f"(d[o + 3])
#define ACC8(d, o) ACC4(d, o), ACC4(d, o + 4)

__device__ __forceinline__ void wgmma_rs_n32(float (&d)[16], uint32_t a0, uint32_t a1, uint32_t a2, uint32_t a3, uint64_t db, int sc) {
  asm volatile("{\n.reg .pred p;\nsetp.ne.b32 p, %21, 0;\n"
               "wgmma.mma_async.sync.aligned.m64n32k16.f32.bf16.bf16 "
               "{%0,%1,%2,%3,%4,%5,%6,%7,%8,%9,%10,%11,%12,%13,%14,%15}, {%16,%17,%18,%19}, %20, p, 1, 1, 0;\n}\n"
               : ACC8(d, 0), ACC8(d, 8)
               : "r"(a0), "r"(a1), "r"(a2), "r"(a3), "l"(db), "r"(sc));
}
__device__ __forceinline__ void wgmma_rs_n56(float (&d)[28], uint32_t a0, uint32_t a1, uint32_t a2, uint32_t a3, uint64_t db, int sc) {
  asm volatile("{\n.reg .pred p;\nsetp.ne.b32 p, %33, 0;\n"
               "wgmma.mma_async.sync.aligned.m64n56k16.f32.bf16.bf16 "
               "{%0,%1,%2,%3,%4,%5,%6,%7,%8,%9,%10,%11,%12,%13,%14,%15,%16,%17,%18,%19,%20,%21,%22,%23,%24,%25,%26,%27}, "
               "{%28,%29,%30,%31}, %32, p, 1, 1, 0;\n}\n"
               : ACC8(d, 0), ACC8(d, 8), ACC8(d, 16), ACC4(d, 24)
               : "r"(a0), "r"(a1), "r"(a2), "r"(a3), "l"(db), "r"(sc));
}
__device__ __forceinline__ void wgmma_ss_n128(float (&d)[64], uint64_t da, uint64_t db, int sc) {
  asm volatile("{\n.reg .pred p;\nsetp.ne.b32 p, %66, 0;\n"
               "wgmma.mma_async.sync.aligned.m64n128k16.f32.bf16.bf16 "
               "{%0,%1,%2,%3,%4,%5,%6,%7,%8,%9,%10,%11,%12,%13,%14,%15,%16,%17,%18,%19,%20,%21,%22,%23,%24,%25,%26,%27,%28,%29,%30,%31,"
               "%32,%33,%34,%35,%36,%37,%38,%39,%40,%41,%42,%43,%44,%45,%46,%47,%48,%49,%50,%51,%52,%53,%54,%55,%56,%57,%58,%59,%60,%61,%62,%63}, "
               "%64, %65, p, 1, 1, 0, 1;\n}\n"
               : ACC8(d, 0), ACC8(d, 8), ACC8(d, 16), ACC8(d, 24), ACC8(d, 32), ACC8(d, 40), ACC8(d, 48), ACC8(d, 56)
               : "l"(da), "l"(db), "r"(sc));
}
__device__ __forceinline__ void wgmma_ss_n80(float (&d)[40], uint64_t da, uint64_t db, int sc) {
  asm volatile("{\n.reg .pred p;\nsetp.ne.b32 p, %42, 0;\n"
               "wgmma.mma_async.sync.aligned.m64n80k16.f32.bf16.bf16 "
               "{%0,%1,%2,%3,%4,%5,%6,%7,%8,%9,%10,%11,%12,%13,%14,%15,%16,%17,%18,%19,%20,%21,%22,%23,%24,%25,%26,%27,%28,%29,%30,%31,"
               "%32,%33,%34,%35,%36,%37,%38,%39}, "
               "%40, %41, p, 1, 1, 0, 1;\n}\n"
               : ACC8(d, 0), ACC8(d, 8), ACC8(d, 16), ACC8(d, 24), ACC8(d, 32)
               : "l"(da), "l"(db), "r"(sc));
}

__device__ __forceinline__ uint32_t mul_lo(uint32_t v, uint32_t r) {
  __nv_bfloat162 a = *reinterpret_cast<__nv_bfloat162*>(&v), b = *reinterpret_cast<__nv_bfloat162*>(&r);
  __nv_bfloat162 c = __hmul2(__low2bfloat162(a), b);
  return *reinterpret_cast<uint32_t*>(&c);
}
__device__ __forceinline__ uint32_t mul_hi(uint32_t v, uint32_t r) {
  __nv_bfloat162 a = *reinterpret_cast<__nv_bfloat162*>(&v), b = *reinterpret_cast<__nv_bfloat162*>(&r);
  __nv_bfloat162 c = __hmul2(__high2bfloat162(a), b);
  return *reinterpret_cast<uint32_t*>(&c);
}
__device__ __forceinline__ uint32_t mul_ew(uint32_t v, uint32_t r) {
  __nv_bfloat162 a = *reinterpret_cast<__nv_bfloat162*>(&v), b = *reinterpret_cast<__nv_bfloat162*>(&r);
  __nv_bfloat162 c = __hmul2(a, b);
  return *reinterpret_cast<uint32_t*>(&c);
}
__device__ __forceinline__ uint32_t pack_bf16(float lo, float hi) {
  uint32_t r;
  asm("cvt.rn.bf16x2.f32 %0, %1, %2;" : "=r"(r) : "f"(hi), "f"(lo));
  return r;
}
__device__ __forceinline__ float bf2f(bf16 v) { return __bfloat162float(v); }
__device__ __forceinline__ float bflo(uint32_t w) { return __uint_as_float(w << 16); }
__device__ __forceinline__ float bfhi(uint32_t w) { return __uint_as_float(w & 0xffff0000u); }

__host__ __device__ __forceinline__ int Fq(int q, int t, int e) {
  if (t == 12) return 24 + e;
  int u = (t + 3 * q) % 12;
  int sw = (q >= 2 && u >= 6) ? 1 : 0;
  return 2 * u + (e ^ sw);
}
constexpr int M_ONE = 26, M_NONE = 27;
__device__ __forceinline__ void g0_mono(int s, int q, int e, int& f1, int& f2) {
  f1 = M_NONE; f2 = M_NONE;
  if (s < 30) { int d = s / 6 + 1, a = (s % 6) >> 1, hi = s & 1; f1 = Fq(q, a, hi); f2 = Fq(q, a + d, e); }
  else if (s < 33) { int a = s - 30; f1 = Fq(q, a, e); f2 = Fq(q, a + 6, e); }
  else if (s < 35) { int a = s - 33; f1 = f2 = Fq(q, a, e); }
  else if (s == 35) { f1 = Fq(q, e, 0); f2 = Fq(q, e, 1); }
  else if (s == 36) { f1 = Fq(q, 2, 0); f2 = Fq(q, 2, e); }
  else if (s == 37) { if (e == 1) f1 = f2 = Fq(q, 2, 1); }
  else if (s < 44) { int a = (s - 38) >> 1, hi = (s - 38) & 1; f1 = 24 + hi; f2 = Fq(q, a, e); }
  else if (s < 47) { f1 = Fq(q, s - 44, e); f2 = M_ONE; }
  else {
    if (q == 0) { f1 = 24; f2 = 24 + e; }
    else if (q == 1) { if (e == 1) f1 = f2 = 25; }
    else if (q == 2) { f1 = 24 + e; f2 = M_ONE; }
    else { if (e == 0) { f1 = M_ONE; f2 = M_ONE; } }
  }
}

struct QScratch { float A4[NF * NF]; float Wf[NF * 28]; float M[NF * 28]; };

template <int NT, typename SyncF>
__device__ __forceinline__ void setup_role(int cta, int t, const bf16* __restrict__ ws, const bf16* __restrict__ wout,
                                           QScratch* qs, SyncF sync) {
  const uint32_t* ws32 = reinterpret_cast<const uint32_t*>(ws);
  uint32_t* img32 = reinterpret_cast<uint32_t*>(g_img);
  if (cta < NF) {
    const int io = cta;
    for (int p = t; p < NF * 13; p += NT) {
      int h = p / 13, tp = p % 13;
      uint32_t w = __ldg(ws32 + ((4 * NF + h) * NF + io) * 13 + tp);
      qs->A4[h * NF + 2 * tp] = bflo(w);
      qs->A4[h * NF + 2 * tp + 1] = bfhi(w);
    }
    for (int p = t; p < NF * 13; p += NT) {
      uint32_t w[NF];
#pragma unroll
      for (int hp = 0; hp < NF; hp++) w[hp] = __ldg(ws32 + (5 * NF + hp) * 338 + p);
      float s0 = 0.f, s1 = 0.f;
#pragma unroll
      for (int hp = 0; hp < NF; hp++) {
        float c = bf2f(__ldg(wout + 5 * NF + hp));
        s0 = fmaf(c, bflo(w[hp]), s0);
        s1 = fmaf(c, bfhi(w[hp]), s1);
      }
      int h = p / 13, tp = p % 13;
      qs->Wf[h * 28 + 2 * tp] = s0;
      qs->Wf[h * 28 + 2 * tp + 1] = s1;
    }
    if (t < NF) { qs->Wf[t * 28 + 26] = bf2f(__ldg(wout + 4 * NF + t)); qs->Wf[t * 28 + 27] = 0.f; }
    sync();
    if (t < 13 * 14) {
      int ab = t % 13, bb = t / 13;
      float m00 = 0, m01 = 0, m10 = 0, m11 = 0;
#pragma unroll
      for (int h = 0; h < NF; h++) {
        float2 a = *reinterpret_cast<const float2*>(&qs->A4[h * NF + 2 * ab]);
        float2 b = *reinterpret_cast<const float2*>(&qs->Wf[h * 28 + 2 * bb]);
        m00 = fmaf(a.x, b.x, m00); m01 = fmaf(a.x, b.y, m01);
        m10 = fmaf(a.y, b.x, m10); m11 = fmaf(a.y, b.y, m11);
      }
      qs->M[(2 * ab) * 28 + 2 * bb] = m00; qs->M[(2 * ab) * 28 + 2 * bb + 1] = m01;
      qs->M[(2 * ab + 1) * 28 + 2 * bb] = m10; qs->M[(2 * ab + 1) * 28 + 2 * bb + 1] = m11;
    }
    sync();
    if (t < 192) {
      int ks = t >> 3, half = (t >> 2) & 1, q = t & 3;
      int s = 2 * ks + half;
      float v[2];
#pragma unroll
      for (int e = 0; e < 2; e++) {
        int f1, f2;
        g0_mono(s, q, e, f1, f2);
        float x;
        if (f1 == M_NONE) x = 0.f;
        else if (f1 == M_ONE) x = bf2f(__ldg(wout + 3 * NF + io));
        else if (f2 == M_ONE) x = qs->M[f1 * 28 + 26];
        else if (f1 == f2) x = qs->M[f1 * 28 + f1];
        else x = qs->M[f1 * 28 + f2] + qs->M[f2 * 28 + f1];
        v[e] = x;
      }
      uint32_t w = pack_bf16(v[0], v[1]);
      int base = ks * (G0_SLAB / 4) + half * 32 + q;
      if (io < 24) {
        int n = 24 + io;
        img32[base + (n >> 3) * 64 + (n & 7) * 4] = w;
      } else {
        int n0 = 48 + 4 * (io - 24) + 1;
        img32[base + 6 * 64 + (n0 & 7) * 4] = w;
        img32[base + 6 * 64 + ((n0 + 2) & 7) * 4] = w;
      }
    }
  } else {
    constexpr int LW = L_BYTES / 4;
    constexpr int X1W = G0_KS * 224;
    for (int w = (cta - NF) * NT + t; w < 3 * LW + X1W; w += (NCTA - NF) * NT) {
      if (w < 3 * LW) {
        int li = w / LW, r = w % LW;
        int ks = r >> 8, ng = (r >> 6) & 3, half = (r >> 5) & 1, n8 = (r >> 2) & 7, q = r & 3;
        int n = ng * 8 + n8;
        int s = 2 * ks + half;
        int o = (n < 24) ? n : ((n & 1) ? -1 : 24 + ((n - 24) >> 2));
        uint32_t val = 0;
        if (o >= 0) {
          if (s < 85) {
            int in, tt;
            bool zero = false;
            if (s < 78) { int a = s / 13; tt = s % 13; in = 8 * (a >> 1) + 2 * q + (a & 1); }
            else { int k = s - 78; tt = (k < 3) ? k : (k < 6 ? k + 3 : 12); in = 24 + (q >> 1); zero = (tt == 12) && (q & 1); }
            if (!zero) {
              int f0 = Fq(q, tt, 0);
              int l = (li == 0) ? 3 : (li == 1 ? 1 : 2);
              int hh = (li == 0) ? in : o, ii = (li == 0) ? o : in;
              uint32_t x = __ldg(ws32 + ((l * NF + hh) * NF + ii) * 13 + (f0 >> 1));
              val = (f0 & 1) ? ((x >> 16) | (x << 16)) : x;
            }
          } else if (li == 0 && q == 0) {
            val = (uint32_t)__bfloat16_as_ushort(wout[2 * NF + o]);
          }
        }
        img32[G0_BYTES / 4 + w] = val;
      } else {
        int r = w - 3 * LW;
        int ks = r / 224, rr = r % 224;
        int ci = rr >> 3, half = (rr >> 2) & 1, q = rr & 3;
        int n = (ci < 24) ? ci : 48 + 2 * (ci - 24);
        int h = (ci < 24) ? ci : 24 + ((ci - 24) >> 1);
        int s = 2 * ks + half;
        float v[2];
#pragma unroll
        for (int e = 0; e < 2; e++) {
          int f1, f2;
          g0_mono(s, q, e, f1, f2);
          float x = 0.f;
          if (f1 < NF && f2 < NF) {
            const bf16* wh = ws + h * NF * NF;
            x = bf2f(__ldg(wh + f1 * NF + f2));
            if (f1 != f2) x += bf2f(__ldg(wh + f2 * NF + f1));
          }
          v[e] = x;
        }
        img32[ks * (G0_SLAB / 4) + (n >> 3) * 64 + half * 32 + (n & 7) * 4 + q] = pack_bf16(v[0], v[1]);
      }
    }
  }
}

__global__ void __launch_bounds__(256) setup_kernel(const bf16* __restrict__ ws, const bf16* __restrict__ wout) {
  __shared__ QScratch qs;
  setup_role<256>(blockIdx.x, threadIdx.x, ws, wout, &qs, [] { __syncthreads(); });
  if (blockIdx.x == 0 && threadIdx.x == 0) g_epoch = g_epoch + 1;
}

template <int S>
__device__ __forceinline__ uint32_t l_prod(const uint32_t (&vp)[4], const uint32_t (&X)[13]) {
  if constexpr (S < 78) {
    constexpr int a = S / 13, t = S % 13;
    return (a & 1) ? mul_hi(vp[a >> 1], X[t]) : mul_lo(vp[a >> 1], X[t]);
  } else if constexpr (S < 85) {
    constexpr int k = S - 78;
    constexpr int t = (k < 3) ? k : (k < 6 ? k + 3 : 12);
    return mul_lo(vp[3], X[t]);
  } else {
    return 0x00003F80u;
  }
}
template <int S>
__device__ __forceinline__ uint32_t g0_prod(const uint32_t (&X)[13], uint32_t selU, uint32_t selV) {
  if constexpr (S < 30) {
    constexpr int d = S / 6 + 1, a = (S % 6) >> 1;
    return (S & 1) ? mul_hi(X[a], X[a + d]) : mul_lo(X[a], X[a + d]);
  } else if constexpr (S < 33) {
    return mul_ew(X[S - 30], X[S - 24]);
  } else if constexpr (S < 35) {
    return mul_ew(X[S - 33], X[S - 33]);
  } else if constexpr (S == 35) {
    return mul_ew(__byte_perm(X[0], X[1], 0x5410), __byte_perm(X[0], X[1], 0x7632));
  } else if constexpr (S == 36) {
    return mul_lo(X[2], X[2]);
  } else if constexpr (S == 37) {
    return mul_hi(X[2], X[2]);
  } else if constexpr (S < 44) {
    constexpr int a = (S - 38) >> 1;
    return ((S - 38) & 1) ? mul_hi(X[12], X[a]) : mul_lo(X[12], X[a]);
  } else if constexpr (S < 47) {
    return X[S - 44];
  } else {
    return mul_ew(__byte_perm(X[12], 0x3F803F80u, selU), __byte_perm(X[12], 0x3F803F80u, selV));
  }
}

constexpr int NBK = 4;

template <int KS, int KE>
__device__ __forceinline__ void l_fill(uint32_t (*A)[4], const uint32_t (&vp)[2][4], const uint32_t (&X)[2][13]) {
  A[0][0] = l_prod<2 * KS>(vp[0], X[0]);
  A[0][1] = l_prod<2 * KS>(vp[1], X[1]);
  A[0][2] = l_prod<2 * KS + 1>(vp[0], X[0]);
  A[0][3] = l_prod<2 * KS + 1>(vp[1], X[1]);
  if constexpr (KS + 1 < KE) l_fill<KS + 1, KE>(A + 1, vp, X);
}
template <int B0, bool SPLIT>
__device__ __forceinline__ void layer_rec(float (&d)[16], const uint32_t (&vp)[2][4], const uint32_t (&X)[2][13],
                                          uint64_t desc, uint64_t desc2) {
  constexpr int KS = B0 * NBK;
  constexpr int KE = (KS + NBK < L_KS) ? KS + NBK : L_KS;
  uint32_t A[NBK][4];
  l_fill<KS, KE>(A, vp, X);
  wg_fence();
#pragma unroll
  for (int k = 0; k < KE - KS; k++) {
    const int ks = KS + k;
    uint64_t db = (SPLIT && ks >= LC_SPLIT) ? desc2 + (uint64_t)(((ks - LC_SPLIT) * L_SLAB) >> 4) : desc + (uint64_t)((ks * L_SLAB) >> 4);
    wgmma_rs_n32(d, A[k][0], A[k][1], A[k][2], A[k][3], db, ks > 0);
  }
  wg_commit();
  if constexpr (KE < L_KS) {
    wg_wait<1>();
    layer_rec<B0 + 1, SPLIT>(d, vp, X, desc, desc2);
  }
}
template <int KS, int KE>
__device__ __forceinline__ void g0_fill(uint32_t (*A)[4], const uint32_t (&X)[2][13], uint32_t selU, uint32_t selV) {
  A[0][0] = g0_prod<2 * KS>(X[0], selU, selV);
  A[0][1] = g0_prod<2 * KS>(X[1], selU, selV);
  A[0][2] = g0_prod<2 * KS + 1>(X[0], selU, selV);
  A[0][3] = g0_prod<2 * KS + 1>(X[1], selU, selV);
  if constexpr (KS + 1 < KE) g0_fill<KS + 1, KE>(A + 1, X, selU, selV);
}
template <int B0>
__device__ __forceinline__ void g0_rec(float (&d)[28], const uint32_t (&X)[2][13], uint32_t selU, uint32_t selV, uint64_t desc) {
  constexpr int KS = B0 * NBK;
  constexpr int KE = (KS + NBK < G0_KS) ? KS + NBK : G0_KS;
  uint32_t A[NBK][4];
  g0_fill<KS, KE>(A, X, selU, selV);
  wg_fence();
#pragma unroll
  for (int k = 0; k < KE - KS; k++)
    wgmma_rs_n56(d, A[k][0], A[k][1], A[k][2], A[k][3], desc + (uint64_t)(((KS + k) * G0_SLAB) >> 4), (KS + k) > 0);
  wg_commit();
  if constexpr (KE < G0_KS) {
    wg_wait<1>();
    g0_rec<B0 + 1>(d, X, selU, selV, desc);
  }
}

__device__ __forceinline__ void ldsm_x4_t(uint32_t addr, uint32_t& r0, uint32_t& r1, uint32_t& r2, uint32_t& r3) {
  asm volatile("ldmatrix.sync.aligned.m8n8.x4.trans.shared.b16 {%0,%1,%2,%3}, [%4];"
               : "=r"(r0), "=r"(r1), "=r"(r2), "=r"(r3) : "r"(addr) : "memory");
}
__device__ __forceinline__ void ldsm_x2_t(uint32_t addr, uint32_t& r0, uint32_t& r1) {
  asm volatile("ldmatrix.sync.aligned.m8n8.x2.trans.shared.b16 {%0,%1}, [%2];" : "=r"(r0), "=r"(r1) : "r"(addr) : "memory");
}
__device__ __forceinline__ float tanh_fast(float x) { float y; asm("tanh.approx.f32 %0, %1;" : "=f"(y) : "f"(x)); return y; }

template <int NC>
__device__ __forceinline__ void dnn_epilogue(float (&d)[NC * 4], const float4* __restrict__ bw, float& r0, float& r1) {
  const float k0 = 0.7978845608028654f, k01 = 0.7978845608028654f * 0.044715f;
  float s0 = 0.f, s1 = 0.f;
#pragma unroll
  for (int c = 0; c < NC; c++) {
    float4 p = bw[c * 4];
#pragma unroll
    for (int e = 0; e < 4; e++) {
      float b = (e & 1) ? p.z : p.x, w = (e & 1) ? p.w : p.y;
      float x = d[c * 4 + e] + b;
      float u = x * fmaf(x * x, k01, k0);
      float th = tanh_fast(u);
      float z = x * w;
      if (e < 2) { s0 += z; s0 = fmaf(z, th, s0); } else { s1 += z; s1 = fmaf(z, th, s1); }
    }
  }
  r0 = s0; r1 = s1;
}

__global__ void __launch_bounds__(512, 1)
main_kernel(const __grid_constant__ CUtensorMap tm0, const __grid_constant__ CUtensorMap tm1,
            const int* __restrict__ idx, const bf16* __restrict__ table, const bf16* __restrict__ b1,
            const bf16* __restrict__ w2, const bf16* __restrict__ wout, const bf16* __restrict__ bout,
            bf16* __restrict__ out) {
  extern __shared__ __align__(1024) unsigned char smem[];
  const uint32_t sb = smem_u32(smem);
  const int tid = threadIdx.x, warp = tid >> 5, lane = tid & 31;
  const int cta = blockIdx.x, nh = cta & 1, mt = cta >> 1;
  const uint32_t bar0 = sb + OFF_BAR;
  auto BAR = [&](int i) { return bar0 + 8 * i; };

  const bool is_prod = (tid == 384);
  const CUtensorMap* tm = nh ? &tm1 : &tm0;
  if (is_prod) {
    if (sb & 1023) __trap();
    for (int i = 0; i < W1_SLOTS; i++) { mbar_init(BAR(BAR_W1FULL + i), 1); mbar_init(BAR(BAR_W1EMPTY + i), 2); }
    for (int i = 0; i < 4; i++) mbar_init(BAR(BAR_IMG + i), 1);
    mbar_init(BAR(BAR_X0), 256);
    mbar_init(BAR(BAR_DNN), 64);
    asm volatile("fence.mbarrier_init.release.cluster;" ::: "memory");
    fence_proxy_async();
    for (int st = 0; st < W1_SLOTS; st++) {
      mbar_expect_tx(BAR(BAR_W1FULL + st), W1_STAGE_BYTES);
#pragma unroll
      for (int a = 0; a < 4; a++) tma_2d(sb + st * W1_STAGE_BYTES + a * 4096, tm, a * 64, st * 32, BAR(BAR_W1FULL + st));
    }
    mbar_expect_tx(BAR(BAR_IMG + 0), G0_BYTES);
    bulk_g2s(sb + OFF_G0, g_img, G0_BYTES, BAR(BAR_IMG + 0));
  }
  if (warp >= 8) {
    int t = tid - 256;
    if (t < 208) {
      int n = nh * 208 + t;
      float2 v = make_float2(bf2f(b1[n]), 0.5f * bf2f(w2[n]));
      reinterpret_cast<float2*>(smem + OFF_BW)[t] = v;
    }
    if (t < 64) {
      int l = t >> 5, q = (t >> 3) & 3, a = t & 7;
      float v = 0.f;
      if (a < 6) v = bf2f(wout[l * NF + 8 * (a >> 1) + 2 * q + (a & 1)]);
      else if (a == 6 && !(q & 1)) v = bf2f(wout[l * NF + 24 + (q >> 1)]);
      reinterpret_cast<float*>(smem + OFF_WTAB)[t] = v;
    }
    {
      int ln = t >> 3, k = t & 7;
      int m = ln >> 3, r = ln & 7;
      int tt = (k < 6) ? 2 * k + (m >> 1) : 12;
      int hh = m & 1;
      int off = Fq(r >> 1, tt, r & 1) * X0_FS + hh * 1024;
      reinterpret_cast<uint16_t*>(smem + OFF_LOFF)[t] = (uint16_t)off;
    }
  }
  int myidx[7];
  if (warp < 8) {
#pragma unroll
    for (int k = 0; k < 7; k++) {
      int p = tid + 256 * k;
      myidx[k] = (p < 64 * NF) ? __ldg(idx + mt * 64 * NF + p) : 0;
    }
  }
  __syncthreads();

  const unsigned epoch = *((volatile unsigned*)&g_epoch);
  if (is_prod) {
    for (int st = W1_SLOTS; st < W1_STAGES; st++) {
      int slot = st - W1_SLOTS;
      mbar_wait(BAR(BAR_W1EMPTY + slot), 0);
      mbar_expect_tx(BAR(BAR_W1FULL + slot), W1_STAGE_BYTES);
#pragma unroll
      for (int a = 0; a < 4; a++) tma_2d(sb + slot * W1_STAGE_BYTES + a * 4096, tm, a * 64, st * 32, BAR(BAR_W1FULL + slot));
    }
    mbar_wait(BAR(BAR_W1EMPTY + 5), 0); mbar_wait(BAR(BAR_W1EMPTY + 6), 0); mbar_wait(BAR(BAR_W1EMPTY + 7), 0);
    mbar_expect_tx(BAR(BAR_IMG + 1), L_BYTES);
    bulk_g2s(sb + OFF_LA, g_img + G0_BYTES, L_BYTES, BAR(BAR_IMG + 1));
    mbar_wait(BAR(BAR_W1EMPTY + 0), 1); mbar_wait(BAR(BAR_W1EMPTY + 1), 1); mbar_wait(BAR(BAR_W1EMPTY + 2), 1);
    mbar_expect_tx(BAR(BAR_IMG + 2), L_BYTES);
    bulk_g2s(sb + OFF_LB, g_img + G0_BYTES + L_BYTES, L_BYTES, BAR(BAR_IMG + 2));
    mbar_wait(BAR(BAR_W1EMPTY + 3), 1); mbar_wait(BAR(BAR_W1EMPTY + 4), 1);
    mbar_expect_tx(BAR(BAR_IMG + 3), L_BYTES);
    bulk_g2s(sb + OFF_LC0, g_img + G0_BYTES + 2 * L_BYTES, LC_SPLIT * L_SLAB, BAR(BAR_IMG + 3));
    bulk_g2s(sb + OFF_LC1, g_img + G0_BYTES + 2 * L_BYTES + LC_SPLIT * L_SLAB, (L_KS - LC_SPLIT) * L_SLAB, BAR(BAR_IMG + 3));
  }
  __syncwarp();

  const int wg = warp >> 2, w4 = warp & 3, g = lane >> 2, q = lane & 3;

  if (wg < 2) {
#pragma unroll
    for (int k = 0; k < 7; k++) {
      int p = tid + 256 * k;
      if (p < 64 * NF) {
        int s = p / NF, f = p - s * NF;
        const unsigned char* src = reinterpret_cast<const unsigned char*>(table) + (size_t)myidx[k] * 32;
        uint32_t dst = sb + OFF_X0 + f * X0_FS + s * 16;
        cp_async16(dst, src);
        cp_async16(dst + 1024, src + 16);
      }
    }
    asm volatile("cp.async.wait_all;" ::: "memory");
    fence_proxy_async();
    mbar_arrive(BAR(BAR_X0));
    mbar_wait(BAR(BAR_X0), 0);
    const uint64_t da0 = make_desc(sb + OFF_X0, 1024, 128, 0);
    const uint64_t db0 = make_desc(sb + (wg == 0 ? 0 : 8192), 4096, 1024, 1);
    float r0, r1;
    if (wg == 0) {
      float acc[64];
#pragma unroll 1
      for (int st = 0; st < W1_STAGES; st++) {
        int slot = st & 7;
        mbar_wait(BAR(BAR_W1FULL + slot), (st >> 3) & 1);
        wg_fence();
        uint64_t db = db0 + (uint64_t)((slot * W1_STAGE_BYTES) >> 4);
        uint64_t da = da0 + (uint64_t)((st * 2 * X0_FS) >> 4);
        wgmma_ss_n128(acc, da, db, st > 0);
        wgmma_ss_n128(acc, da + (X0_FS >> 4), db + (2048 >> 4), 1);
        wg_commit();
        wg_wait<1>();
        if (st > 0 && (tid & 127) == 0) mbar_arrive(BAR(BAR_W1EMPTY + ((st - 1) & 7)));
      }
      wg_wait<0>();
      reg_fence(acc);
      if ((tid & 127) == 0) mbar_arrive(BAR(BAR_W1EMPTY + ((W1_STAGES - 1) & 7)));
      dnn_epilogue<16>(acc, reinterpret_cast<const float4*>(smem + OFF_BW) + q, r0, r1);
    } else {
      float acc[40];
#pragma unroll 1
      for (int st = 0; st < W1_STAGES; st++) {
        int slot = st & 7;
        mbar_wait(BAR(BAR_W1FULL + slot), (st >> 3) & 1);
        wg_fence();
        uint64_t db = db0 + (uint64_t)((slot * W1_STAGE_BYTES) >> 4);
        uint64_t da = da0 + (uint64_t)((st * 2 * X0_FS) >> 4);
        wgmma_ss_n80(acc, da, db, st > 0);
        wgmma_ss_n80(acc, da + (X0_FS >> 4), db + (2048 >> 4), 1);
        wg_commit();
        wg_wait<1>();
        if (st > 0 && (tid & 127) == 0) mbar_arrive(BAR(BAR_W1EMPTY + ((st - 1) & 7)));
      }
      wg_wait<0>();
      reg_fence(acc);
      if ((tid & 127) == 0) mbar_arrive(BAR(BAR_W1EMPTY + ((W1_STAGES - 1) & 7)));
      dnn_epilogue<10>(acc, reinterpret_cast<const float4*>(smem + OFF_BW) + 64 + q, r0, r1);
    }
    r0 += __shfl_xor_sync(0xffffffffu, r0, 1); r0 += __shfl_xor_sync(0xffffffffu, r0, 2);
    r1 += __shfl_xor_sync(0xffffffffu, r1, 1); r1 += __shfl_xor_sync(0xffffffffu, r1, 2);
    float* dpart = reinterpret_cast<float*>(smem + OFF_DPART);
    if (q == 0) { dpart[wg * 64 + w4 * 16 + g] = r0; dpart[wg * 64 + w4 * 16 + g + 8] = r1; }
    named_bar(1, 256);
    if (tid < 64) {
      float v = dpart[tid] + dpart[64 + tid];
      reinterpret_cast<float*>(smem + OFF_DSUM)[tid] = v;
      unsigned long long pk = ((unsigned long long)epoch << 32) | (unsigned long long)__float_as_uint(v);
      asm volatile("st.relaxed.gpu.global.u64 [%0], %1;" ::"l"(&g_part[cta * 64 + tid]), "l"(pk) : "memory");
      mbar_arrive(BAR(BAR_DNN));
    }
  } else {
    mbar_wait(BAR(BAR_X0), 0);
  }

  const uint64_t dG0 = make_desc(sb + OFF_G0, 128, 256, 0);
  const uint64_t dLA = make_desc(sb + OFF_LA, 128, 256, 0);
  const uint64_t dLB = make_desc(sb + OFF_LB, 128, 256, 0);
  const uint64_t dLC0 = make_desc(sb + OFF_LC0, 128, 256, 0);
  const uint64_t dLC1 = make_desc(sb + OFF_LC1, 128, 256, 0);
  const uint32_t selU = (q == 0) ? 0x1010u : (q == 1) ? 0x3232u : (q == 2) ? 0x3210u : 0x7654u;
  const uint32_t selV = (q < 2) ? 0x3210u : 0x7654u;
  const float bo = bf2f(bout[0]);

#pragma unroll 1
  for (int it = 0; it < 2; it++) {
    const int sl = nh * 32 + (wg + 4 * it) * 4 + w4;
    uint32_t X[2][13];
    {
      uint4 o = *reinterpret_cast<const uint4*>(smem + OFF_LOFF + lane * 16);
      uint32_t base = sb + OFF_X0 + sl * 16;
      ldsm_x4_t(base + (o.x & 0xffff), X[0][0], X[1][0], X[0][1], X[1][1]);
      ldsm_x4_t(base + (o.x >> 16), X[0][2], X[1][2], X[0][3], X[1][3]);
      ldsm_x4_t(base + (o.y & 0xffff), X[0][4], X[1][4], X[0][5], X[1][5]);
      ldsm_x4_t(base + (o.y >> 16), X[0][6], X[1][6], X[0][7], X[1][7]);
      ldsm_x4_t(base + (o.z & 0xffff), X[0][8], X[1][8], X[0][9], X[1][9]);
      ldsm_x4_t(base + (o.z >> 16), X[0][10], X[1][10], X[0][11], X[1][11]);
      ldsm_x2_t(base + (o.w & 0xffff), X[0][12], X[1][12]);
    }
    float S = 0.f;
    uint32_t vx[2][4], vg[2][4];
    {
      float a0[28];
      mbar_wait(BAR(BAR_IMG + 0), 0);
      g0_rec<0>(a0, X, selU, selV, dG0);
      wg_wait<0>();
      reg_fence(a0);
      const float4* wt = reinterpret_cast<const float4*>(smem + OFF_WTAB) + q * 2;
      float4 wa = wt[0], wb = wt[1];
#pragma unroll
      for (int r = 0; r < 2; r++) {
        S = fmaf(wa.x, a0[0 + 2 * r], S); S = fmaf(wa.y, a0[1 + 2 * r], S);
        S = fmaf(wa.z, a0[4 + 2 * r], S); S = fmaf(wa.w, a0[5 + 2 * r], S);
        S = fmaf(wb.x, a0[8 + 2 * r], S); S = fmaf(wb.y, a0[9 + 2 * r], S);
        S = fmaf(wb.z, a0[24 + 2 * r], S);
#pragma unroll
        for (int c = 0; c < 3; c++) {
          vx[r][c] = pack_bf16(a0[4 * c + 2 * r], a0[4 * c + 2 * r + 1]);
          vg[r][c] = pack_bf16(a0[12 + 4 * c + 2 * r], a0[12 + 4 * c + 2 * r + 1]);
        }
        vx[r][3] = pack_bf16(a0[24 + 2 * r], 0.f);
        vg[r][3] = pack_bf16(a0[24 + 2 * r + 1], 0.f);
      }
    }
    float g3[16], xa[16];
    mbar_wait(BAR(BAR_IMG + 1), 0);
    layer_rec<0, false>(g3, vg, X, dLA, dLA);
    mbar_wait(BAR(BAR_IMG + 2), 0);
    wg_wait<1>();
    layer_rec<0, false>(xa, vx, X, dLB, dLB);
    wg_wait<0>();
    reg_fence(g3);
    reg_fence(xa);
    {
      const float4* wt = reinterpret_cast<const float4*>(smem + OFF_WTAB) + 8 + q * 2;
      float4 wa = wt[0], wb = wt[1];
#pragma unroll
      for (int r = 0; r < 2; r++) {
        S = fmaf(wa.x, xa[0 + 2 * r], S); S = fmaf(wa.y, xa[1 + 2 * r], S);
        S = fmaf(wa.z, xa[4 + 2 * r], S); S = fmaf(wa.w, xa[5 + 2 * r], S);
        S = fmaf(wb.x, xa[8 + 2 * r], S); S = fmaf(wb.y, xa[9 + 2 * r], S);
        S = fmaf(wb.z, xa[12 + 2 * r], S);
#pragma unroll
        for (int c = 0; c < 3; c++) vx[r][c] = pack_bf16(xa[4 * c + 2 * r], xa[4 * c + 2 * r + 1]);
        vx[r][3] = pack_bf16(xa[12 + 2 * r], 0.f);
      }
    }
    mbar_wait(BAR(BAR_IMG + 3), 0);
    const unsigned long long* pp = &g_part[(cta ^ 1) * 64 + sl];
    unsigned long long pk;
    asm volatile("ld.relaxed.gpu.global.u64 %0, [%1];" : "=l"(pk) : "l"(pp) : "memory");
    layer_rec<0, true>(xa, vx, X, dLC0, dLC1);
    wg_wait<0>();
    reg_fence(xa);
    {
      float Se = 0.f;
#pragma unroll
      for (int r = 0; r < 2; r++) {
#pragma unroll
        for (int c = 0; c < 3; c++) {
          S = fmaf(g3[4 * c + 2 * r], xa[4 * c + 2 * r], S);
          S = fmaf(g3[4 * c + 2 * r + 1], xa[4 * c + 2 * r + 1], S);
        }
        Se = fmaf(g3[12 + 2 * r], xa[12 + 2 * r], Se);
      }
      if (!(q & 1)) S += Se;
    }
#pragma unroll
    for (int o = 16; o > 0; o >>= 1) S += __shfl_xor_sync(0xffffffffu, S, o);
    mbar_wait(BAR(BAR_DNN), 0);
    if (lane == 0) {
      uint32_t spin = 0;
      while ((unsigned)(pk >> 32) != epoch) {
        asm volatile("ld.relaxed.gpu.global.u64 %0, [%1];" : "=l"(pk) : "l"(pp) : "memory");
        if (++spin > (1u << 24)) __trap();
      }
      float own = reinterpret_cast<const float*>(smem + OFF_DSUM)[sl];
      float peer = __uint_as_float((unsigned)pk);
      float d0 = nh ? peer : own, d1 = nh ? own : peer;
      out[mt * 64 + sl] = __float2bfloat16(S + (d0 + d1) + bo);
    }
    __syncwarp();
  }
}

typedef CUresult (*EncodeFn)(CUtensorMap*, CUtensorMapDataType, cuuint32_t, void*, const cuuint64_t*, const cuuint64_t*,
                             const cuuint32_t*, const cuuint32_t*, CUtensorMapInterleave, CUtensorMapSwizzle,
                             CUtensorMapL2promotion, CUtensorMapFloatOOBfill);

extern "C" void kernel_launch(void* const* d_in, const int* in_sizes, int n_in, void* d_out, int out_size) {
  const int* idx = (const int*)d_in[0];
  const bf16* table = (const bf16*)d_in[1];
  const bf16* ws = (const bf16*)d_in[2];
  const bf16* wout = (const bf16*)d_in[3];
  const bf16* w1 = (const bf16*)d_in[4];
  const bf16* b1 = (const bf16*)d_in[5];
  const bf16* w2 = (const bf16*)d_in[6];
  const bf16* bo = (const bf16*)d_in[7];
  bf16* out = (bf16*)d_out;

  static EncodeFn enc = nullptr;
  if (!enc) {
    void* fn = nullptr;
    cudaDriverEntryPointQueryResult qr;
    cudaGetDriverEntryPoint("cuTensorMapEncodeTiled", &fn, cudaEnableDefault, &qr);
    enc = (EncodeFn)fn;
    cudaFuncSetAttribute(main_kernel, cudaFuncAttributeMaxDynamicSharedMemorySize, SMEM_BYTES);
  }
  CUtensorMap tm[2];
  for (int h = 0; h < 2; h++) {
    cuuint64_t dims[2] = {208, (cuuint64_t)DIN};
    cuuint64_t strides[1] = {(cuuint64_t)DIN * 2};
    cuuint32_t box[2] = {64, 32};
    cuuint32_t es[2] = {1, 1};
    enc(&tm[h], CU_TENSOR_MAP_DATA_TYPE_BFLOAT16, 2, (void*)(w1 + h * 208), dims, strides, box, es,
        CU_TENSOR_MAP_INTERLEAVE_NONE, CU_TENSOR_MAP_SWIZZLE_128B, CU_TENSOR_MAP_L2_PROMOTION_L2_128B,
        CU_TENSOR_MAP_FLOAT_OOB_FILL_NONE);
  }
  cudaStream_t st = cudaStreamPerThread;
  setup_kernel<<<NCTA, 256, 0, st>>>(ws, wout);
  main_kernel<<<NCTA, 512, SMEM_BYTES, st>>>(tm[0], tm[1], idx, table, b1, w2, wout, bo, out);
}
```

```cpp
#include <cuda_runtime.h>
#include <cuda_bf16.h>
#include <cuda.h>
#include <stdint.h>

typedef __nv_bfloat16 bf16;

constexpr int NF = 26;
constexpr int NCTA = 128;

constexpr int G0_KS = 24, G0_N = 56, G0_SLAB = G0_N * 32;
constexpr int L_KS = 43, L_SLAB = 1024;
constexpr int G0_BYTES = G0_KS * G0_SLAB;
constexpr int L_BYTES = L_KS * L_SLAB;
constexpr int IMG_BYTES = G0_BYTES + 3 * L_BYTES;

constexpr int W1_STAGES = 7;
constexpr int W1_STAGE_BYTES = 16384;
constexpr int OFF_LB = 0;
constexpr int OFF_LA = 44032;
constexpr int OFF_LC = 88064;
__host__ __device__ constexpr int w1_off(int st) { return st < 2 ? st * W1_STAGE_BYTES : OFF_LA + (st - 2) * W1_STAGE_BYTES; }
constexpr int OFF_G0 = 132096;
constexpr int OFF_IDX = 132096 + 16384;
constexpr int OFF_TAB = OFF_G0 + G0_BYTES;
constexpr int OFF_XOFF = OFF_TAB + 32000;
constexpr int OFF_BAR = OFF_XOFF + 6656;
constexpr int OFF_BW = OFF_BAR + 256;
constexpr int OFF_W2 = OFF_BW + 256;
constexpr int OFF_WTAB = OFF_W2 + 1792;
constexpr int OFF_EPOCH = OFF_WTAB + 256;
constexpr int OFF_STAB = (OFF_EPOCH + 16 + 127) / 128 * 128;
constexpr int OFF_LOFF = OFF_STAB + 3072 + 704;
constexpr int SMEM_BYTES = OFF_STAB + 4288;
static_assert(SMEM_BYTES <= 229376, "smem");
constexpr int LAUNCH_SMEM = SMEM_BYTES;

constexpr int BAR_W1FULL = 0  , BAR_W1FREE = 10  , BAR_W1DONE = 11  ,
              BAR_IMG = 14  , BAR_X0 = 18, BAR_SETUP = 19, BAR_EPOCH = 20, BAR_TABS = 21,
              BAR_Q = 22, BAR_STAB = 23, BAR_G0B = 24, NBAR = 25;

struct TmaMaps { CUtensorMap m[4]; };
struct Params {
  const int* idx; const bf16* table; const bf16* ws; const bf16* wout; const bf16* b1; const bf16* w2; const bf16* bout;
  bf16* out;
  unsigned char* img; unsigned long long* part; unsigned* ctr; const void* tabs;
  uint64_t dk, dmn;
  uint2 role[NCTA];
};

__device__ __align__(1024) unsigned char g_img[IMG_BYTES];
__device__ unsigned long long g_part[NCTA * 128];
__device__ unsigned g_ctr;

#define GT(i) do {} while (0)
#define TL(i) do {} while (0)
#define TLP(i) do {} while (0)
#define TLA(i) do {} while (0)
#define TLW(w, i) do {} while (0)
#define TL_INIT() do {} while (0)
#define TL_START() 0
#define TL_PUT0(c) do {} while (0)
#define TL_DUMP() do {} while (0)
__device__ __forceinline__ uint32_t smem_u32(const void* p) { return (uint32_t)__cvta_generic_to_shared(p); }
__device__ __forceinline__ bool elect_one() {
  uint32_t pred;
  asm volatile("{\n.reg .pred p;\nelect.sync _|p, 0xffffffff;\nselp.u32 %0, 1, 0, p;\n}\n" : "=r"(pred));
  return pred != 0;
}
__device__ __forceinline__ void mbar_init(uint32_t bar, uint32_t cnt) {
  asm volatile("mbarrier.init.shared::cta.b64 [%0], %1;" ::"r"(bar), "r"(cnt) : "memory");
}
__device__ __forceinline__ void mbar_expect_tx(uint32_t bar, uint32_t bytes) {
  asm volatile("mbarrier.arrive.expect_tx.shared::cta.b64 _, [%0], %1;" ::"r"(bar), "r"(bytes) : "memory");
}
__device__ __forceinline__ void mbar_arrive(uint32_t bar) {
  asm volatile("mbarrier.arrive.shared::cta.b64 _, [%0];" ::"r"(bar) : "memory");
}
__device__ __forceinline__ bool mbar_try(uint32_t bar, uint32_t parity) {
  uint32_t ok;
  asm volatile("{\n.reg .pred p;\nmbarrier.try_wait.parity.shared::cta.b64 p, [%1], %2;\nselp.u32 %0, 1, 0, p;\n}\n"
               : "=r"(ok) : "r"(bar), "r"(parity) : "memory");
  return ok != 0;
}
__device__ __forceinline__ void mbar_wait(uint32_t bar, uint32_t parity) {
#pragma unroll 1
  for (uint32_t it = 0; it < (1u << 26); it++)
    if (mbar_try(bar, parity)) return;
  __trap();
}
__device__ __forceinline__ void bulk_g2s(uint32_t dst, const void* src, uint32_t bytes, uint32_t bar) {
  asm volatile("cp.async.bulk.shared::cluster.global.mbarrier::complete_tx::bytes [%0], [%1], %2, [%3];"
               ::"r"(dst), "l"(src), "r"(bytes), "r"(bar) : "memory");
}
__device__ __forceinline__ void tma_2d(uint32_t dst, const CUtensorMap* tm, int x, int y, uint32_t bar) {
  asm volatile("cp.async.bulk.tensor.2d.shared::cluster.global.mbarrier::complete_tx::bytes [%0], [%1, {%3, %4}], [%2];"
               ::"r"(dst), "l"(tm), "r"(bar), "r"(x), "r"(y) : "memory");
}
__device__ __forceinline__ void cp_async16(uint32_t dst, const void* src) {
  asm volatile("cp.async.cg.shared.global [%0], [%1], 16;" ::"r"(dst), "l"(src) : "memory");
}
__device__ __forceinline__ void fence_proxy_async() { asm volatile("fence.proxy.async.shared::cta;" ::: "memory"); }
__device__ __forceinline__ void fence_proxy_async_all() { asm volatile("fence.proxy.async;" ::: "memory"); }
template <int ID, int N> __device__ __forceinline__ void named_bar_t() { asm volatile("bar.sync %0, %1;" ::"n"(ID), "n"(N) : "memory"); }
#define named_bar(id, n) named_bar_t<id, n>()

__device__ __forceinline__ void wg_fence() { asm volatile("wgmma.fence.sync.aligned;" ::: "memory"); }
__device__ __forceinline__ void wg_commit() { asm volatile("wgmma.commit_group.sync.aligned;" ::: "memory"); }
template <int N> __device__ __forceinline__ void wg_wait() { asm volatile("wgmma.wait_group.sync.aligned %0;" ::"n"(N) : "memory"); }
template <int N> __device__ __forceinline__ void reg_fence(float (&d)[N]) {
#pragma unroll
  for (int i = 0; i < N; i++) asm volatile("" : "+f"(d[i])::"memory");
}
constexpr uint32_t SMEM_BASE = 1024;
__host__ __device__ constexpr uint64_t make_desc(uint32_t off, uint32_t lbo, uint32_t sbo, uint32_t swz) {
  return (uint64_t)(((SMEM_BASE + off) & 0x3FFFF) >> 4) | ((uint64_t)(lbo >> 4) << 16) | ((uint64_t)(sbo >> 4) << 32) | ((uint64_t)swz << 62);
}

#define ACC4(d, o) "+f"(d[o]), "+f"(d[o + 1]), "+f"(d[o + 2]), "+f"(d[o + 3])
#define ACC8(d, o) ACC4(d, o), ACC4(d, o + 4)

__device__ __forceinline__ void wgmma_rs_n32(float (&d)[16], uint32_t a0, uint32_t a1, uint32_t a2, uint32_t a3, uint64_t db, int sc) {
  asm volatile("{\n.reg .pred p;\nsetp.ne.b32 p, %21, 0;\n"
               "wgmma.mma_async.sync.aligned.m64n32k16.f32.bf16.bf16 "
               "{%0,%1,%2,%3,%4,%5,%6,%7,%8,%9,%10,%11,%12,%13,%14,%15}, {%16,%17,%18,%19}, %20, p, 1, 1, 0;\n}\n"
               : ACC8(d, 0), ACC8(d, 8)
               : "r"(a0), "r"(a1), "r"(a2), "r"(a3), "l"(db), "r"(sc));
}
__device__ __forceinline__ void wgmma_rs_n56(float (&d)[28], uint32_t a0, uint32_t a1, uint32_t a2, uint32_t a3, uint64_t db, int sc) {
  asm volatile("{\n.reg .pred p;\nsetp.ne.b32 p, %33, 0;\n"
               "wgmma.mma_async.sync.aligned.m64n56k16.f32.bf16.bf16 "
               "{%0,%1,%2,%3,%4,%5,%6,%7,%8,%9,%10,%11,%12,%13,%14,%15,%16,%17,%18,%19,%20,%21,%22,%23,%24,%25,%26,%27}, "
               "{%28,%29,%30,%31}, %32, p, 1, 1, 0;\n}\n"
               : ACC8(d, 0), ACC8(d, 8), ACC8(d, 16), ACC4(d, 24)
               : "r"(a0), "r"(a1), "r"(a2), "r"(a3), "l"(db), "r"(sc));
}
__device__ __forceinline__ void wgmma_rs_n112_tb(float (&d)[56], uint32_t a0, uint32_t a1, uint32_t a2, uint32_t a3, uint64_t db, int sc) {
  asm volatile("{\n.reg .pred p;\nsetp.ne.b32 p, %61, 0;\n"
               "wgmma.mma_async.sync.aligned.m64n112k16.f32.bf16.bf16 "
               "{%0,%1,%2,%3,%4,%5,%6,%7,%8,%9,%10,%11,%12,%13,%14,%15,%16,%17,%18,%19,%20,%21,%22,%23,%24,%25,%26,%27,%28,%29,%30,%31,%32,%33,%34,%35,%36,%37,%38,%39,%40,%41,%42,%43,%44,%45,%46,%47,%48,%49,%50,%51,%52,%53,%54,%55}, "
               "{%56,%57,%58,%59}, %60, p, 1, 1, 1;\n}\n"
               : ACC8(d, 0), ACC8(d, 8), ACC8(d, 16), ACC8(d, 24), ACC8(d, 32), ACC8(d, 40), ACC8(d, 48)
               : "r"(a0), "r"(a1), "r"(a2), "r"(a3), "l"(db), "r"(sc));
}

__device__ __forceinline__ void wgmma_rs_n8(float (&d)[4], uint32_t a0, uint32_t a1, uint32_t a2, uint32_t a3, uint64_t db, int sc) {
  asm volatile("{\n.reg .pred p;\nsetp.ne.b32 p, %9, 0;\n"
               "wgmma.mma_async.sync.aligned.m64n8k16.f32.bf16.bf16 {%0,%1,%2,%3}, {%4,%5,%6,%7}, %8, p, 1, 1, 0;\n}\n"
               : ACC4(d, 0)
               : "r"(a0), "r"(a1), "r"(a2), "r"(a3), "l"(db), "r"(sc));
}
__device__ __forceinline__ uint32_t mul_lo(uint32_t v, uint32_t r) {
  __nv_bfloat162 a = *reinterpret_cast<__nv_bfloat162*>(&v), b = *reinterpret_cast<__nv_bfloat162*>(&r);
  __nv_bfloat162 c = __hmul2(__low2bfloat162(a), b);
  return *reinterpret_cast<uint32_t*>(&c);
}
__device__ __forceinline__ uint32_t mul_hi(uint32_t v, uint32_t r) {
  __nv_bfloat162 a = *reinterpret_cast<__nv_bfloat162*>(&v), b = *reinterpret_cast<__nv_bfloat162*>(&r);
  __nv_bfloat162 c = __hmul2(__high2bfloat162(a), b);
  return *reinterpret_cast<uint32_t*>(&c);
}
__device__ __forceinline__ uint32_t mul_ew(uint32_t v, uint32_t r) {
  __nv_bfloat162 a = *reinterpret_cast<__nv_bfloat162*>(&v), b = *reinterpret_cast<__nv_bfloat162*>(&r);
  __nv_bfloat162 c = __hmul2(a, b);
  return *reinterpret_cast<uint32_t*>(&c);
}
__device__ __forceinline__ uint32_t pack_bf16(float lo, float hi) {
  uint32_t r;
  asm("cvt.rn.bf16x2.f32 %0, %1, %2;" : "=r"(r) : "f"(hi), "f"(lo));
  return r;
}
__device__ __forceinline__ float bf2f(bf16 v) { return __bfloat162float(v); }
__device__ __forceinline__ float bflo(uint32_t w) { return __uint_as_float(w << 16); }
__device__ __forceinline__ float bfhi(uint32_t w) { return __uint_as_float(w & 0xffff0000u); }

__device__ __forceinline__ void st_img(uint32_t* p, uint32_t v) {
  asm volatile("st.relaxed.gpu.global.u32 [%0], %1;" ::"l"(p), "r"(v) : "memory");
}
__device__ __forceinline__ uint32_t ld_back(const uint32_t* p) {
  uint32_t v;
  asm volatile("ld.relaxed.gpu.global.u32 %0, [%1];" : "=r"(v) : "l"(p) : "memory");
  return v;
}
__host__ __device__ constexpr int Fq(int q, int t, int e) {
  if (t == 12) return 24 + e;
  const int u = (t + 3 * q) % 12;
  const int sw = (q >= 2 && u >= 6) ? 1 : 0;
  return 2 * u + (e ^ sw);
}
constexpr int M_ONE = 26, M_NONE = 27;
struct Mono { int f1, f2; };
__host__ __device__ constexpr Mono g0_mono(int s, int q, int e) {
  if (s < 30) { const int d = s / 6 + 1, a = (s % 6) >> 1; return {Fq(q, a, s & 1), Fq(q, a + d, e)}; }
  if (s < 33) return {Fq(q, s - 30, e), Fq(q, s - 24, e)};
  if (s < 35) return {Fq(q, s - 33, e), Fq(q, s - 33, e)};
  if (s == 35) return {Fq(q, e, 0), Fq(q, e, 1)};
  if (s == 36) return {Fq(q, 2, 0), Fq(q, 2, e)};
  if (s == 37) return e ? Mono{Fq(q, 2, 1), Fq(q, 2, 1)} : Mono{M_NONE, M_NONE};
  if (s < 44) return {24 + ((s - 38) & 1), Fq(q, (s - 38) >> 1, e)};
  if (s < 47) return {Fq(q, s - 44, e), M_ONE};
  if (q == 0) return {24, 24 + e};
  if (q == 1) return e ? Mono{25, 25} : Mono{M_NONE, M_NONE};
  if (q == 2) return {24 + e, M_ONE};
  return e ? Mono{M_NONE, M_NONE} : Mono{M_ONE, M_ONE};
}
constexpr int QM_RS = 40;
constexpr int O_ZERO = 31 * QM_RS + 39, O_CONST = 30 * QM_RS + 39;
struct StaticTabs {
  uint32_t otab[48 * 8];
  uint32_t x1tab[48 * 8];
  uint16_t ltab[88 * 4];
  uint16_t loff[32 * 8];
};
constexpr StaticTabs make_tabs() {
  StaticTabs T{};
  for (int s = 0; s < 48; s++)
    for (int q = 0; q < 4; q++)
      for (int e = 0; e < 2; e++) {
        const Mono m = g0_mono(s, q, e);
        const bool none = m.f1 == M_NONE, cs = m.f1 == M_ONE, lin = m.f2 == M_ONE;
        const uint32_t o1 = none ? O_ZERO : cs ? O_CONST : m.f1 * QM_RS + (lin ? 26 : m.f2);
        const uint32_t dg = (!none && !cs && !lin && m.f1 == m.f2) ? 1u : 0u;
        T.otab[s * 8 + q * 2 + e] = o1 | (dg << 16);
        const bool qd = m.f1 < NF && m.f2 < NF;
        const uint32_t y1 = qd ? m.f1 * NF + m.f2 : 0xffffu;
        const uint32_t y2 = (qd && m.f1 != m.f2) ? m.f2 * NF + m.f1 : 0xffffu;
        T.x1tab[s * 8 + q * 2 + e] = y1 | (y2 << 16);
      }
  for (int s = 0; s < 88; s++)
    for (int q = 0; q < 4; q++) {
      uint16_t v = 0;
      if (s < 85) {
        const bool ex = s >= 78;
        const int a = s / 13, k = s - 78;
        const int tt = ex ? ((k < 3) ? k : (k < 6 ? k + 3 : 12)) : s % 13;
        const int in = ex ? 24 + (q >> 1) : 8 * (a >> 1) + 2 * q + (a & 1);
        const bool valid = !(ex && tt == 12 && (q & 1));
        const int f0 = Fq(q, tt, 0);
        v = (uint16_t)((f0 >> 1) | ((f0 & 1) << 4) | ((valid ? 1 : 0) << 5) | (in << 6));
      }
      T.ltab[s * 4 + q] = v;
    }
  for (int ln = 0; ln < 32; ln++)
    for (int k = 0; k < 8; k++) {
      const int m = ln >> 3, r = ln & 7;
      const int tt = (k < 6) ? 2 * k + (m >> 1) : 12;
      T.loff[ln * 8 + k] = (uint16_t)(2 * Fq(r >> 1, tt, r & 1));
    }
  return T;
}
static_assert(sizeof(StaticTabs) == 4288, "tabs");
__device__ __align__(128) const StaticTabs g_tabs = make_tabs();

constexpr int SETUP_WARPS = 7;
constexpr int WL_BYTES = NF * NF * NF * 2;
static inline uint2 make_role(int cta) {
  int kind = 5, grp = 0, j = 0, off = 0, bytes = 0;
  const int c = cta, SL = NF * NF * 2;
  if (c < 56) { kind = 1 + c / 28; grp = (c % 28) / 7; j = c % 7; off = kind * WL_BYTES + grp * 8 * SL; bytes = (grp < 3 ? 8 : 2) * SL; }
  else if (c < 80) { kind = 0; grp = (c - 56) / 8; j = (c - 56) % 8; off = 3 * WL_BYTES + grp * 8 * SL; bytes = 8 * SL; }
  else if (c < 83) { kind = 0; grp = 3; j = c - 80; off = 3 * WL_BYTES + 24 * SL; bytes = 2 * SL; }
  else if (c < 95) { kind = 3; grp = (c - 83) / 4; j = (c - 83) % 4; off = grp * 8 * SL; bytes = 8 * SL; }
  const int delta = off & 127;
  uint2 r;
  r.x = (uint32_t)(off - delta) | ((uint32_t)kind << 24);
  r.y = (uint32_t)(bytes + delta) | ((uint32_t)delta << 16) | ((uint32_t)grp << 24) | ((uint32_t)j << 28);
  return r;
}

__device__ __forceinline__ uint32_t layer_row(int li, int grp, int r, int lane, const unsigned char* raw, const StaticTabs* T,
                                              uint32_t bar, uint32_t tbar, const bf16* __restrict__ wout, uint32_t* img32) {
  const int ks = li ? r : 13 * grp + (r >> 2), ng = li ? grp : (r & 3);
  if (ks >= 43 || (!li && grp < 3 && r >= 52)) return 0;
  const uint32_t* w32 = reinterpret_cast<const uint32_t*>(raw);
  const int n8 = lane >> 2, q = lane & 3;
  const int o = (ng < 3) ? ng * 8 + n8 : 24 + (n8 >> 2);
  const bool vo = (ng < 3) || !(n8 & 1);
  const int ob = li ? (o - 8 * grp) * 338 : o * 13 - 8 * grp * 338;
  const int si = li ? 13 : 338;
  uint32_t bias = 0;
  if (vo && ks == 42 && li == 0 && q == 0) bias = (uint32_t)__ldg(reinterpret_cast<const unsigned short*>(wout) + 2 * NF + o);
  uint32_t* dst = img32 + G0_BYTES / 4 + li * (L_BYTES / 4) + (ks * 4 + ng) * 64 + lane;
  mbar_wait(tbar, 0);
  const uint32_t e0 = T->ltab[8 * ks + q], e1 = T->ltab[8 * ks + 4 + q];
  const bool v0 = vo && (e0 & 32), v1 = vo && (e1 & 32);
  const int s0 = v0 ? ob + (e0 >> 6) * si + (e0 & 15) : 0, s1 = v1 ? ob + (e1 >> 6) * si + (e1 & 15) : 0;
  TL(33);
  mbar_wait(bar, 0);
  TL(36);
  uint32_t w0 = w32[s0], w1 = w32[s1];
  w0 = (e0 & 16) ? __funnelshift_l(w0, w0, 16) : w0;
  w1 = (e1 & 16) ? __funnelshift_l(w1, w1, 16) : w1;
  w0 = v0 ? w0 : 0u;
  w1 = v1 ? w1 : bias;
  st_img(dst, w0); st_img(dst + 32, w1);
  return (ld_back(dst) ^ w0) | (ld_back(dst + 32) ^ w1);
}
__device__ __forceinline__ float x1_val(const unsigned short* wh, uint32_t e) {
  const uint32_t a = e & 0xffff, b = e >> 16;
  const uint32_t x = wh[a == 0xffff ? 0 : a], y = wh[b == 0xffff ? 0 : b];
  return (a == 0xffff ? 0.f : __uint_as_float(x << 16)) + (b == 0xffff ? 0.f : __uint_as_float(y << 16));
}
__device__ __forceinline__ uint32_t x1_row(int ng, int ks, int lane, const unsigned char* raw, const StaticTabs* T, uint32_t bar, uint32_t tbar, uint32_t* img32) {
  if (ks >= 24) return 0;
  const int n8 = lane >> 2, q = lane & 3;
  const unsigned short* wh = reinterpret_cast<const unsigned short*>(raw) + n8 * (NF * NF);
  uint32_t* dst = img32 + ks * (G0_SLAB / 4) + ng * 64 + lane;
  mbar_wait(tbar, 0);
  const uint2 ea = *reinterpret_cast<const uint2*>(&T->x1tab[16 * ks + 2 * q]), eb = *reinterpret_cast<const uint2*>(&T->x1tab[16 * ks + 8 + 2 * q]);
  mbar_wait(bar, 0);
  const uint32_t w0 = pack_bf16(x1_val(wh, ea.x), x1_val(wh, ea.y)), w1 = pack_bf16(x1_val(wh, eb.x), x1_val(wh, eb.y));
  st_img(dst, w0); st_img(dst + 32, w1);
  return (ld_back(dst) ^ w0) | (ld_back(dst + 32) ^ w1);
}

constexpr int NHELP = 4;
constexpr int H_MS = 32 * QM_RS + 4;
constexpr int H_W5 = 0, H_W4 = 35328, H_W0 = 70656, H_TAB = 73472, H_B = 77824, H_M = 82944, H_XE = H_M + 8 * H_MS * 4, H_BAR = H_XE + 1536;
struct HB { bf16 Bh[32][40]; };
__device__ __forceinline__ void mma_bf16(float (&c)[4], uint32_t a0, uint32_t a1, uint32_t a2, uint32_t a3, uint32_t b0, uint32_t b1) {
  asm volatile("mma.sync.aligned.m16n8k16.row.col.f32.bf16.bf16.f32 {%0,%1,%2,%3}, {%4,%5,%6,%7}, {%8,%9}, {%0,%1,%2,%3};"
               : "+f"(c[0]), "+f"(c[1]), "+f"(c[2]), "+f"(c[3]) : "r"(a0), "r"(a1), "r"(a2), "r"(a3), "r"(b0), "r"(b1));
}
__device__ __forceinline__ void helper_role(int hk, const Params& P, unsigned char* smem, uint32_t sb) {
  const int t = threadIdx.x, warp = __shfl_sync(0xffffffffu, t >> 5, 0), lane = t & 31;
  const uint32_t d5bar = sb + H_BAR, d4bar = sb + H_BAR + 8, tbar = sb + H_BAR + 16;
  const unsigned char* wsb = reinterpret_cast<const unsigned char*>(P.ws);
  HB* Q = reinterpret_cast<HB*>(smem + H_B);
  float* M = reinterpret_cast<float*>(smem + H_M);
  if (warp < 3 && elect_one()) {
    mbar_init(sb + H_BAR + 8 * warp, 1);
    asm volatile("fence.mbarrier_init.release.cluster;" ::: "memory");
  }
  for (int i = t; i < 640; i += 512) reinterpret_cast<uint32_t*>(Q)[i] = 0;
  __syncthreads();
  constexpr uint32_t W5B = WL_BYTES + ((5 * WL_BYTES) & 127), W4B = WL_BYTES + ((4 * WL_BYTES) & 127);
  if (warp < 12 && elect_one()) {
    if (warp < 5) {
      if (warp == 0) mbar_expect_tx(d5bar, W5B);
      bulk_g2s(sb + H_W5 + warp * 8192, wsb + ((5 * WL_BYTES) & ~127) + warp * 8192, warp < 4 ? 8192u : W5B - 4 * 8192, d5bar);
    } else if (warp < 10) {
      const int c = warp - 5;
      if (c == 0) mbar_expect_tx(d4bar, W4B + (hk == 3 ? 2768 : 0));
      bulk_g2s(sb + H_W4 + c * 8192, wsb + ((4 * WL_BYTES) & ~127) + c * 8192, c < 4 ? 8192u : W4B - 4 * 8192, d4bar);
    } else if (warp == 10) {
      mbar_expect_tx(tbar, sizeof(StaticTabs));
      bulk_g2s(sb + H_TAB, P.tabs, sizeof(StaticTabs), tbar);
    } else if (hk == 3) {
      bulk_g2s(sb + H_W0, wsb + ((24 * NF * NF * 2) & ~127), 2768, d4bar);
    }
  }
  const unsigned short* wo16 = reinterpret_cast<const unsigned short*>(P.wout);
  uint32_t c5[13];
#pragma unroll
  for (int k = 0; k < 13; k++) c5[k] = __ldg(reinterpret_cast<const uint32_t*>(P.wout + 5 * NF) + k);
  unsigned short wv = 0;
  const int io0 = (hk < 3) ? 8 * hk : 24;
  if (t >= 352 && t < 352 + NF) wv = __ldg(wo16 + 4 * NF + t - 352);
  else if (t >= 384 && t < 392 && io0 + t - 384 < NF) wv = __ldg(wo16 + 3 * NF + io0 + t - 384);
  const StaticTabs* T = reinterpret_cast<const StaticTabs*>(smem + H_TAB);
  const int n8 = lane >> 2, q = lane & 3, g = n8;
  const int fil = (hk < 3) ? n8 : (n8 >> 2);
  const bool fx1 = (hk == 3) && !(n8 & 1);
  uint32_t* dst = reinterpret_cast<uint32_t*>(P.img) + (warp >> 1) * (G0_SLAB / 4) + (warp & 1) * 32 + (3 + hk) * 64 + lane;
  if (t >= 352 && t < 352 + NF) reinterpret_cast<unsigned short*>(&Q->Bh[26][t - 352])[0] = wv;
  if (t >= 384 && t < 392) { M[(t - 384) * H_MS + O_ZERO] = 0.f; M[(t - 384) * H_MS + O_CONST] = __uint_as_float((uint32_t)wv << 16); }
  mbar_wait(d5bar, 0);
  if (t < 338) {
    const uint32_t* w5 = reinterpret_cast<const uint32_t*>(smem + H_W5 + ((5 * WL_BYTES) & 127)) + t;
    float s0 = 0.f, s1 = 0.f, s2 = 0.f, s3 = 0.f;
#pragma unroll
    for (int k = 0; k < 13; k++) {
      const uint32_t wa = w5[(2 * k) * 338], wb = w5[(2 * k + 1) * 338];
      const float ca = bflo(c5[k]), cb = bfhi(c5[k]);
      s0 = fmaf(ca, bflo(wa), s0); s1 = fmaf(ca, bfhi(wa), s1);
      s2 = fmaf(cb, bflo(wb), s2); s3 = fmaf(cb, bfhi(wb), s3);
    }
    const int h = (t * 79) >> 10, tp = t - 13 * h;
    Q->Bh[2 * tp][h] = __float2bfloat16(s0 + s2);
    Q->Bh[2 * tp + 1][h] = __float2bfloat16(s1 + s3);
  }
  mbar_wait(tbar, 0);
  uint2 fot[3];
#pragma unroll
  for (int r = 0; r < 3; r++) fot[r] = *reinterpret_cast<const uint2*>(&T->otab[(warp + 16 * r) * 8 + q * 2]);
  mbar_wait(d4bar, 0);
  const int il = warp - 8;
  const bool mma_warp = (warp >= 8) && (hk < 3 || il < 2);
  uint32_t u[4][4];
  if (mma_warp) {
    const unsigned short* A = reinterpret_cast<const unsigned short*>(smem + H_W4 + ((4 * WL_BYTES) & 127)) + (io0 + il) * NF + g;
#pragma unroll
    for (int rb = 0; rb < 4; rb++) {
#pragma unroll
      for (int kh = 0; kh < 4; kh++) {
        const int k = 8 * kh + 2 * q;
        const bool ok = (k < NF) && (8 * rb + g < NF);
        const int kc = (k < NF) ? k : 0;
        const uint32_t lo = A[kc * (NF * NF) + 8 * rb], hi = A[(kc + 1) * (NF * NF) + 8 * rb];
        u[rb][kh] = ok ? (lo | (hi << 16)) : 0u;
      }
    }
  }
  if (hk == 3) {
    const int u0 = (warp < 8) ? t : (warp >= 10 && warp < 14) ? t - 64 : -1;
    if (u0 >= 0) {
      const int sl = u0 >> 3, xl = (u0 >> 2) & 1, xq = u0 & 3;
      const uint2 xt = *reinterpret_cast<const uint2*>(&T->x1tab[sl * 8 + xq * 2]);
      const unsigned short* wh = reinterpret_cast<const unsigned short*>(smem + H_W0 + ((24 * NF * NF * 2) & 127)) + xl * (NF * NF);
      reinterpret_cast<uint32_t*>(smem + H_XE)[u0] = pack_bf16(x1_val(wh, xt.x), x1_val(wh, xt.y));
    }
  }
  __syncthreads();
  if (mma_warp) {
    uint32_t w[4][4];
#pragma unroll
    for (int rb = 0; rb < 4; rb++)
#pragma unroll
      for (int kh = 0; kh < 4; kh++) w[rb][kh] = *reinterpret_cast<const uint32_t*>(&Q->Bh[8 * rb + g][8 * kh + 2 * q]);
    float* Mi = M + il * H_MS;
    float c[2][4][4];
#pragma unroll
    for (int mt = 0; mt < 2; mt++)
#pragma unroll
      for (int nt = 0; nt < 4; nt++) { c[mt][nt][0] = c[mt][nt][1] = c[mt][nt][2] = c[mt][nt][3] = 0.f; }
#pragma unroll
    for (int kk = 0; kk < 2; kk++) {
#pragma unroll
      for (int mt = 0; mt < 2; mt++)
#pragma unroll
        for (int nt = 0; nt < 4; nt++)
          mma_bf16(c[mt][nt], u[2 * mt][2 * kk], u[2 * mt + 1][2 * kk], u[2 * mt][2 * kk + 1], u[2 * mt + 1][2 * kk + 1], w[nt][2 * kk], w[nt][2 * kk + 1]);
#pragma unroll
      for (int mt = 0; mt < 2; mt++)
#pragma unroll
        for (int nt = 0; nt < 4; nt++)
          mma_bf16(c[mt][nt], w[2 * mt][2 * kk], w[2 * mt + 1][2 * kk], w[2 * mt][2 * kk + 1], w[2 * mt + 1][2 * kk + 1], u[nt][2 * kk], u[nt][2 * kk + 1]);
    }
#pragma unroll
    for (int mt = 0; mt < 2; mt++)
#pragma unroll
      for (int nt = 0; nt < 4; nt++) {
        *reinterpret_cast<float2*>(&Mi[(mt * 16 + g) * QM_RS + nt * 8 + 2 * q]) = make_float2(c[mt][nt][0], c[mt][nt][1]);
        *reinterpret_cast<float2*>(&Mi[(mt * 16 + g + 8) * QM_RS + nt * 8 + 2 * q]) = make_float2(c[mt][nt][2], c[mt][nt][3]);
      }
  }
  __syncthreads();
  uint32_t val[3], chk = 0;
#pragma unroll
  for (int r = 0; r < 3; r++) {
    const float* Mf = M + fil * H_MS;
    float v0 = Mf[fot[r].x & 0xffff], v1 = Mf[fot[r].y & 0xffff];
    v0 = (fot[r].x >> 16) ? 0.5f * v0 : v0;
    v1 = (fot[r].y >> 16) ? 0.5f * v1 : v1;
    const uint32_t xe = reinterpret_cast<const uint32_t*>(smem + H_XE)[(warp + 16 * r) * 8 + (n8 >> 2) * 4 + q];
    val[r] = fx1 ? xe : pack_bf16(v0, v1);
    st_img(dst + r * 8 * (G0_SLAB / 4), val[r]);
  }
#pragma unroll
  for (int r = 0; r < 3; r++) chk |= ld_back(dst + r * 8 * (G0_SLAB / 4)) ^ val[r];
  if (__any_sync(0xffffffffu, chk != 0)) __trap();
  __syncthreads();
  if (t == 0) asm volatile("red.relaxed.gpu.global.add.u32 [%0], 32;" ::"l"(P.ctr) : "memory");
}

template <int S>
__device__ __forceinline__ uint32_t l_prod(const uint32_t (&vp)[4], const uint32_t (&X)[13]) {
  if constexpr (S < 78) {
    constexpr int a = S / 13, t = S % 13;
    return (a & 1) ? mul_hi(vp[a >> 1], X[t]) : mul_lo(vp[a >> 1], X[t]);
  } else if constexpr (S < 85) {
    constexpr int k = S - 78;
    constexpr int t = (k < 3) ? k : (k < 6 ? k + 3 : 12);
    return mul_lo(vp[3], X[t]);
  } else {
    return 0x00003F80u;
  }
}
template <int S>
__device__ __forceinline__ uint32_t g0_prod(const uint32_t (&X)[13], uint32_t selU, uint32_t selV) {
  if constexpr (S < 30) {
    constexpr int d = S / 6 + 1, a = (S % 6) >> 1;
    return (S & 1) ? mul_hi(X[a], X[a + d]) : mul_lo(X[a], X[a + d]);
  } else if constexpr (S < 33) {
    return mul_ew(X[S - 30], X[S - 24]);
  } else if constexpr (S < 35) {
    return mul_ew(X[S - 33], X[S - 33]);
  } else if constexpr (S == 35) {
    return mul_ew(__byte_perm(X[0], X[1], 0x5410), __byte_perm(X[0], X[1], 0x7632));
  } else if constexpr (S == 36) {
    return mul_lo(X[2], X[2]);
  } else if constexpr (S == 37) {
    return mul_hi(X[2], X[2]);
  } else if constexpr (S < 44) {
    constexpr int a = (S - 38) >> 1;
    return ((S - 38) & 1) ? mul_hi(X[12], X[a]) : mul_lo(X[12], X[a]);
  } else if constexpr (S < 47) {
    return X[S - 44];
  } else {
    return mul_ew(__byte_perm(X[12], 0x3F803F80u, selU), __byte_perm(X[12], 0x3F803F80u, selV));
  }
}

constexpr int NBK = 4;

template <int KS, int KE>
__device__ __forceinline__ void l_fill(uint32_t (*A)[4], const uint32_t (&vp)[2][4], const uint32_t (&X)[2][13]) {
  A[0][0] = l_prod<2 * KS>(vp[0], X[0]);
  A[0][1] = l_prod<2 * KS>(vp[1], X[1]);
  A[0][2] = l_prod<2 * KS + 1>(vp[0], X[0]);
  A[0][3] = l_prod<2 * KS + 1>(vp[1], X[1]);
  if constexpr (KS + 1 < KE) l_fill<KS + 1, KE>(A + 1, vp, X);
}
template <int KS, int OFF>
__device__ __forceinline__ void layer_rec(float (&d)[16], const uint32_t (&vp)[2][4], const uint32_t (&X)[2][13], uint64_t dk) {
  constexpr int KE = (KS + NBK < L_KS) ? KS + NBK : L_KS;
  uint32_t A[NBK][4];
  l_fill<KS, KE>(A, vp, X);
  wg_fence();
#pragma unroll
  for (int k = 0; k < KE - KS; k++)
    wgmma_rs_n32(d, A[k][0], A[k][1], A[k][2], A[k][3], dk + (uint64_t)((OFF + (KS + k) * L_SLAB) >> 4), (KS + k) > 0);
  wg_commit();
  if constexpr (KE < L_KS) {
    wg_wait<1>();
    layer_rec<KE, OFF>(d, vp, X, dk);
  }
}
template <int OFF, int NK>
__device__ __forceinline__ void layer_first(float (&d)[16], const uint32_t (&vp)[2][4], const uint32_t (&X)[2][13], uint64_t dk) {
  uint32_t A[NK][4];
  l_fill<0, NK>(A, vp, X);
  wg_fence();
#pragma unroll
  for (int k = 0; k < NK; k++) wgmma_rs_n32(d, A[k][0], A[k][1], A[k][2], A[k][3], dk + (uint64_t)((OFF + k * L_SLAB) >> 4), k > 0);
  wg_commit();
}
template <int KS, int KE>
__device__ __forceinline__ void g0_fill(uint32_t (*A)[4], const uint32_t (&X)[2][13], uint32_t selU, uint32_t selV) {
  A[0][0] = g0_prod<2 * KS>(X[0], selU, selV);
  A[0][1] = g0_prod<2 * KS>(X[1], selU, selV);
  A[0][2] = g0_prod<2 * KS + 1>(X[0], selU, selV);
  A[0][3] = g0_prod<2 * KS + 1>(X[1], selU, selV);
  if constexpr (KS + 1 < KE) g0_fill<KS + 1, KE>(A + 1, X, selU, selV);
}
template <int B0>
__device__ __forceinline__ void g0_rec(float (&d)[28], const uint32_t (&X)[2][13], uint32_t selU, uint32_t selV, uint64_t dk, uint32_t bar2) {
  constexpr int KS = B0 * NBK;
  if constexpr (KS == 12) mbar_wait(bar2, 0);
  constexpr int KE = (KS + NBK < G0_KS) ? KS + NBK : G0_KS;
  uint32_t A[NBK][4];
  g0_fill<KS, KE>(A, X, selU, selV);
  wg_fence();
#pragma unroll
  for (int k = 0; k < KE - KS; k++)
    wgmma_rs_n56(d, A[k][0], A[k][1], A[k][2], A[k][3], dk + (uint64_t)((OFF_G0 + (KS + k) * G0_SLAB) >> 4), (KS + k) > 0);
  wg_commit();
  if constexpr (KE < G0_KS) {
    wg_wait<1>();
    g0_rec<B0 + 1>(d, X, selU, selV, dk, bar2);
  }
}

__device__ __forceinline__ void ldsm_x4_t(uint32_t addr, uint32_t& r0, uint32_t& r1, uint32_t& r2, uint32_t& r3) {
  asm volatile("ldmatrix.sync.aligned.m8n8.x4.trans.shared.b16 {%0,%1,%2,%3}, [%4];"
               : "=r"(r0), "=r"(r1), "=r"(r2), "=r"(r3) : "r"(addr) : "memory");
}
__device__ __forceinline__ void ldsm_x2_t(uint32_t addr, uint32_t& r0, uint32_t& r1) {
  asm volatile("ldmatrix.sync.aligned.m8n8.x2.trans.shared.b16 {%0,%1}, [%2];" : "=r"(r0), "=r"(r1) : "r"(addr) : "memory");
}
__device__ __forceinline__ float tanh_fast(float x) { float y; asm("tanh.approx.f32 %0, %1;" : "=f"(y) : "f"(x)); return y; }

__device__ __forceinline__ uint32_t gelu2_pair(float lo, float hi, uint32_t bias) {
  uint32_t x = pack_bf16(lo, hi), t, u;
  asm("add.rn.bf16x2 %0, %0, %1;" : "+r"(x) : "r"(bias));
  asm("mul.rn.bf16x2 %0, %1, %1;" : "=r"(t) : "r"(x));
  asm("fma.rn.bf16x2 %0, %0, %1, %2;" : "+r"(t) : "r"(0x3D123D12u), "r"(0x3F4C3F4Cu));
  asm("mul.rn.bf16x2 %0, %1, %2;" : "=r"(u) : "r"(x), "r"(t));
  asm("tanh.approx.bf16x2 %0, %0;" : "+r"(u));
  asm("fma.rn.bf16x2 %0, %1, %0, %1;" : "+r"(u) : "r"(x));
  return u;
}

__device__ __forceinline__ void ldsm_x4(uint32_t addr, uint32_t (&r)[4]) {
  asm volatile("ldmatrix.sync.aligned.m8n8.x4.shared.b16 {%0,%1,%2,%3}, [%4];"
               : "=r"(r[0]), "=r"(r[1]), "=r"(r[2]), "=r"(r[3]) : "r"(addr) : "memory");
}
__device__ __forceinline__ uint32_t lds_u16(uint32_t addr) {
  unsigned short v;
  asm volatile("ld.shared.u16 %0, [%1];" : "=h"(v) : "r"(addr) : "memory");
  return v;
}
__device__ __forceinline__ uint32_t lds_u32(uint32_t addr) {
  uint32_t v;
  asm volatile("ld.shared.u32 %0, [%1];" : "=r"(v) : "r"(addr) : "memory");
  return v;
}

__global__ void __launch_bounds__(512, 1)
main_kernel(const __grid_constant__ Params P, const __grid_constant__ TmaMaps tms) {
  extern __shared__ __align__(1024) unsigned char smem[];
  const uint32_t sb = smem_u32(smem);
  const int tid = threadIdx.x, warp = __shfl_sync(0xffffffffu, tid >> 5, 0), lane = tid & 31;
  if (blockIdx.x < NHELP) {
    helper_role(blockIdx.x, P, smem, sb);
    return;
  }
  const int cta = blockIdx.x - NHELP, nq = cta & 3, grp = cta >> 2;
  const uint2 role = P.role[cta];
  const uint32_t bar0 = sb + OFF_BAR;
  auto BAR = [&](int i) { return bar0 + 8 * i; };
  const int wg = warp >> 2, w4 = warp & 3, g = lane >> 2, q = lane & 3;
  const uint64_t dk = P.dk;
  const long long tl_c0 = TL_START();
  TL_INIT();
  TL_PUT0(tl_c0);

  if (tid < 256) {
    const unsigned char* isrc = reinterpret_cast<const unsigned char*>(P.idx + grp * 128 * NF);
#pragma unroll
    for (int k = 0; k < 4; k++) {
      const int c = tid + 256 * k;
      if (c < 832) cp_async16(sb + OFF_IDX + c * 16, isrc + c * 16);
    }
    asm volatile("cp.async.commit_group;" ::: "memory");
#pragma unroll
    for (int k = 0; k < 8; k++) {
      const int c = tid + 256 * k;
      if (c < 2000) cp_async16(sb + OFF_TAB + ((c ^ ((c >> 3) & 1)) << 4), reinterpret_cast<const unsigned char*>(P.table) + c * 16);
    }
    asm volatile("cp.async.commit_group;" ::: "memory");
  }
  if (elect_one()) {
    mbar_init(BAR(warp), (warp == BAR_W1FREE || warp == BAR_W1DONE) ? 2 : 1);
    if (warp < NBAR - 16)
      mbar_init(BAR(16 + warp), (16 + warp == BAR_X0) ? 256 : (16 + warp == BAR_SETUP) ? SETUP_WARPS : (16 + warp == BAR_TABS) ? 224 : 1);
    asm volatile("fence.mbarrier_init.release.cluster;" ::: "memory");
  }
  __syncthreads();
  TL(26);

  if (warp == 15) {
    if (elect_one()) {
      mbar_expect_tx(BAR(BAR_STAB), sizeof(StaticTabs));
      bulk_g2s(sb + OFF_STAB, P.tabs, sizeof(StaticTabs), BAR(BAR_STAB));
      if ((sb & 0x3FFFF) != SMEM_BASE) __trap();
      const CUtensorMap* tm0 = &tms.m[nq];
      asm volatile("prefetch.tensormap [%0];" ::"l"(tm0) : "memory");
#pragma unroll
      for (int st = 0; st < W1_STAGES; st++) {
        if (st == 1 && (role.x >> 24) < 5) mbar_wait(BAR(BAR_Q), 0);
        mbar_expect_tx(BAR(BAR_W1FULL + st), W1_STAGE_BYTES);
        tma_2d(sb + w1_off(st), tm0, 0, st * 64, BAR(BAR_W1FULL + st));
        tma_2d(sb + w1_off(st) + 8192, tm0, 64, st * 64, BAR(BAR_W1FULL + st));
      }
      TLP(22);
      mbar_wait(BAR(BAR_EPOCH), 0);
      TLP(23);
      const unsigned target = lds_u32(sb + OFF_EPOCH) << 8;
      {
        unsigned v;
        uint32_t it = 0;
#pragma unroll 1
        do {
          asm volatile("ld.relaxed.gpu.global.u32 %0, [%1];" : "=r"(v) : "l"(P.ctr) : "memory");
          if (++it > (1u << 22)) __trap();
        } while ((int)(v - target) < 0);
        asm volatile("fence.acq_rel.cta;" ::: "memory");
      }
      fence_proxy_async_all();
      mbar_wait(BAR(BAR_X0), 0);
      TLP(24);
      mbar_expect_tx(BAR(BAR_IMG + 0), G0_BYTES / 2);
      mbar_expect_tx(BAR(BAR_G0B), G0_BYTES / 2);
#pragma unroll
      for (int i = 0; i < 6; i++)
        bulk_g2s(sb + OFF_G0 + i * (G0_BYTES / 6), P.img + i * (G0_BYTES / 6), G0_BYTES / 6, i < 3 ? BAR(BAR_IMG + 0) : BAR(BAR_G0B));
      mbar_wait(BAR(BAR_W1FREE), 0);
      mbar_expect_tx(BAR(BAR_IMG + 2), L_BYTES);
#pragma unroll
      for (int i = 0; i < 4; i++)
        bulk_g2s(sb + OFF_LB + i * (L_BYTES / 4), P.img + G0_BYTES + L_BYTES + i * (L_BYTES / 4), L_BYTES / 4, BAR(BAR_IMG + 2));
      mbar_wait(BAR(BAR_W1DONE), 0);
      mbar_expect_tx(BAR(BAR_IMG + 1), L_BYTES);
      mbar_expect_tx(BAR(BAR_IMG + 3), L_BYTES);
#pragma unroll
      for (int i = 0; i < 2; i++)
        bulk_g2s(sb + OFF_LA + i * (L_BYTES / 2), P.img + G0_BYTES + i * (L_BYTES / 2), L_BYTES / 2, BAR(BAR_IMG + 1));
#pragma unroll
      for (int i = 0; i < 2; i++)
        bulk_g2s(sb + OFF_LC + i * (L_BYTES / 2), P.img + G0_BYTES + 2 * L_BYTES + i * (L_BYTES / 2), L_BYTES / 2, BAR(BAR_IMG + 3));
      TLP(25);
    }
    __syncwarp();
    mbar_wait(BAR(BAR_X0), 0);
    mbar_wait(BAR(BAR_TABS), 0);
  } else if (wg < 2) {
    asm volatile("cp.async.wait_group 1;" ::: "memory");
    named_bar(1, 256);
#pragma unroll
    for (int k = 0; k < 7; k++) {
      const int p = tid + 256 * k;
      if (p < 64 * NF) {
        const uint2 v = reinterpret_cast<const uint2*>(smem + OFF_IDX)[p];
        const uint32_t o0 = v.x * 32 + ((v.x >> 2) & 1) * 16, o1 = v.y * 32 + ((v.y >> 2) & 1) * 16;
        reinterpret_cast<uint32_t*>(smem + OFF_XOFF)[p] = o0 | (o1 << 16);
      }
    }
    TL(1);
    asm volatile("cp.async.wait_all;" ::: "memory");
    mbar_arrive(BAR(BAR_X0));
    mbar_wait(BAR(BAR_X0), 0);
    TL(3);
    float acc[56];
    {
      const uint32_t xo = sb + OFF_XOFF + (wg * 64 + w4 * 16 + (lane & 15)) * 52;
      const uint32_t tb = sb + OFF_TAB, hx = (lane >> 4) << 4;
      const uint64_t db0 = P.dmn;
      uint32_t A[3][2][4];
#pragma unroll
      for (int pr = 0; pr < 2; pr++) {
        const uint32_t oa = lds_u32(xo + 4 * pr);
        ldsm_x4(tb + ((oa & 0xffff) ^ hx), A[pr][0]); ldsm_x4(tb + ((oa >> 16) ^ hx), A[pr][1]);
      }
#pragma unroll
      for (int pr = 0; pr < 13; pr++) {
        const int st = pr >> 1;
        uint32_t oa = 0;
        if (pr + 2 < 13) oa = lds_u32(xo + 4 * (pr + 2));
        if (!(pr & 1)) mbar_wait(BAR(BAR_W1FULL + st), 0);
        if (pr == 0) TL(28); if (pr == 6) TL(29);
        const uint64_t db = db0 + (uint64_t)((w1_off(st) + (pr & 1) * 4096) >> 4);
        wg_fence();
        wgmma_rs_n112_tb(acc, A[pr % 3][0][0], A[pr % 3][0][1], A[pr % 3][0][2], A[pr % 3][0][3], db, pr > 0);
        wgmma_rs_n112_tb(acc, A[pr % 3][1][0], A[pr % 3][1][1], A[pr % 3][1][2], A[pr % 3][1][3], db + (2048 >> 4), 1);
        wg_commit();
        wg_wait<1>();
        if (pr == 4 && (tid & 127) == 0) mbar_arrive(BAR(BAR_W1FREE));
        if (pr + 2 < 13) { ldsm_x4(tb + ((oa & 0xffff) ^ hx), A[(pr + 2) % 3][0]); ldsm_x4(tb + ((oa >> 16) ^ hx), A[(pr + 2) % 3][1]); }
      }
      wg_wait<0>();
      reg_fence(acc);
      if ((tid & 127) == 0) mbar_arrive(BAR(BAR_W1DONE));
    }
    TL(4);
    float dot[4];
    {
      mbar_wait(BAR(BAR_TABS), 0);
      uint32_t bb[16];
      const uint4* bp = reinterpret_cast<const uint4*>(smem + OFF_BW + q * 64);
#pragma unroll
      for (int i = 0; i < 4; i++) { const uint4 v = bp[i]; bb[4 * i] = v.x; bb[4 * i + 1] = v.y; bb[4 * i + 2] = v.z; bb[4 * i + 3] = v.w; }
      uint32_t H[14][2];
#pragma unroll
      for (int c = 0; c < 14; c++) {
        H[c][0] = gelu2_pair(acc[4 * c], acc[4 * c + 1], bb[c]);
        H[c][1] = gelu2_pair(acc[4 * c + 2], acc[4 * c + 3], bb[c]);
      }
      wg_fence();
#pragma unroll
      for (int j = 0; j < 7; j++)
        wgmma_rs_n8(dot, H[2 * j][0], H[2 * j][1], H[2 * j + 1][0], H[2 * j + 1][1], dk + (uint64_t)((OFF_W2 + j * 256) >> 4), j > 0);
      wg_commit();
      wg_wait<0>();
      reg_fence(dot);
    }
    __syncwarp();
    mbar_wait(BAR(BAR_EPOCH), 0);
    if (q == 0) {
      const unsigned epoch = lds_u32(sb + OFF_EPOCH);
#pragma unroll
      for (int r = 0; r < 2; r++) {
        const int row = wg * 64 + w4 * 16 + g + 8 * r;
        const unsigned long long pk = ((unsigned long long)epoch << 32) | (unsigned long long)__float_as_uint(dot[2 * r]);
        asm volatile("st.relaxed.gpu.global.u64 [%0], %1;" ::"l"(P.part + cta * 128 + row), "l"(pk) : "memory");
      }
    }
    __syncwarp();
  } else {
    const int t = tid - 256;
    const bool is_arr = (t == 192);
    unsigned ctr0 = 0;
    if (is_arr) asm volatile("ld.relaxed.gpu.global.u32 %0, [%1];" : "=r"(ctr0) : "l"(P.ctr) : "memory");
    {
      const int kind = role.x >> 24, w = warp - 8, rgrp = (role.y >> 24) & 15, rj = role.y >> 28;
      const unsigned char* wsb = reinterpret_cast<const unsigned char*>(P.ws);
      if (kind < 5 && elect_one()) {
        const uint32_t bytes = role.y & 0xffff;
        const uint32_t o = w * 8192;
        if (w == 0) mbar_expect_tx(BAR(BAR_Q), bytes);
        if (o < bytes) bulk_g2s(sb + OFF_G0 + o, wsb + (role.x & 0xffffff) + o, min(bytes - o, 8192u), BAR(BAR_Q));
      }
      TL(40);
      __syncwarp();
      const StaticTabs* T = reinterpret_cast<const StaticTabs*>(smem + OFF_STAB);
      uint32_t* img32 = reinterpret_cast<uint32_t*>(P.img);
      const unsigned char* raw = smem + OFF_G0 + ((role.y >> 16) & 127);
      uint32_t chk = 0;
      if (kind < 3) chk = layer_row(kind, rgrp, rj * SETUP_WARPS + w, lane, raw, T, BAR(BAR_Q), BAR(BAR_STAB), P.wout, img32);
      else if (kind == 3) chk = x1_row(rgrp, rj * SETUP_WARPS + w, lane, raw, T, BAR(BAR_Q), BAR(BAR_STAB), img32);
      if (__any_sync(0xffffffffu, chk != 0)) __trap();
      if (lane == 0) mbar_arrive(BAR(BAR_SETUP));
    }
    TL(1);
    if (is_arr) {
      asm volatile("" : "+r"(ctr0));
      *reinterpret_cast<volatile unsigned*>(smem + OFF_EPOCH) = (ctr0 >> 8) + 1;
      mbar_wait(BAR(BAR_SETUP), 0);
      TLA(30);
      asm volatile("red.relaxed.gpu.global.add.u32 [%0], 1;" ::"l"(P.ctr) : "memory");
      mbar_arrive(BAR(BAR_EPOCH));
      TLA(31);
    }
    __syncwarp();
    {
      const int c0 = (nq >> 1) * 208 + (nq & 1) * 96, nw = (nq & 1) ? 112 : 96;
      if (t < 56) {
        const int n = 2 * t;
        const uint32_t v = (n < nw) ? __ldg(reinterpret_cast<const uint32_t*>(P.b1 + c0 + n)) : 0u;
        reinterpret_cast<uint32_t*>(smem + OFF_BW)[(t & 3) * 16 + (t >> 2)] = v;
      }
      if (t >= 64 && t < 64 + 112) {
        const int k = t - 64;
        const float w = (k < nw) ? 0.5f * bf2f(__ldg(P.w2 + c0 + k)) : 0.f;
        unsigned char* base = smem + OFF_W2 + (k >> 4) * 256 + ((k >> 3) & 1) * 128;
        *reinterpret_cast<bf16*>(base + (k & 7) * 2) = __float2bfloat16(w);
        if ((k & 7) == 0) {
#pragma unroll
          for (int r = 1; r < 8; r++) *reinterpret_cast<uint4*>(base + r * 16) = make_uint4(0, 0, 0, 0);
        }
      }
      fence_proxy_async();
    }
    if (t >= 128 && t < 192) {
      int u = t - 128, l = u >> 5, qq = (u >> 3) & 3, a = u & 7;
      float wtv = 0.f;
      if (a < 6) wtv = bf2f(__ldg(P.wout + l * NF + 8 * (a >> 1) + 2 * qq + (a & 1)));
      else if (a == 6 && !(qq & 1)) wtv = bf2f(__ldg(P.wout + l * NF + 24 + (qq >> 1)));
      reinterpret_cast<float*>(smem + OFF_WTAB)[u] = wtv;
    }
    mbar_arrive(BAR(BAR_TABS));
    TL(2);
    mbar_wait(BAR(BAR_X0), 0);
    mbar_wait(BAR(BAR_TABS), 0);
  }

  TL(5);
  const uint32_t selU = (q == 0) ? 0x1010u : (q == 1) ? 0x3232u : (q == 2) ? 0x3210u : 0x7654u;
  const uint32_t selV = (q < 2) ? 0x3210u : 0x7654u;
  uint32_t bo_raw = __ldg(reinterpret_cast<const unsigned short*>(P.bout));
  mbar_wait(BAR(BAR_EPOCH), 0);
  mbar_wait(BAR(BAR_STAB), 0);
  const unsigned epoch = lds_u32(sb + OFF_EPOCH);

  uint32_t X[2][13];
  auto load_x = [&](int sl) {
    const uint4 o = *reinterpret_cast<const uint4*>(smem + OFF_LOFF + lane * 16);
    const uint32_t xo = sb + OFF_XOFF + sl * 52;
    const uint32_t tb = sb + OFF_TAB, hx = ((lane >> 3) & 1) << 4;
    const uint32_t a0 = lds_u16(xo + (o.x & 0xffff)), a1 = lds_u16(xo + (o.x >> 16));
    const uint32_t a2 = lds_u16(xo + (o.y & 0xffff)), a3 = lds_u16(xo + (o.y >> 16));
    const uint32_t a4 = lds_u16(xo + (o.z & 0xffff)), a5 = lds_u16(xo + (o.z >> 16));
    const uint32_t a6 = lds_u16(xo + (o.w & 0xffff));
    ldsm_x4_t(tb + (a0 ^ hx), X[0][0], X[1][0], X[0][1], X[1][1]);
    ldsm_x4_t(tb + (a1 ^ hx), X[0][2], X[1][2], X[0][3], X[1][3]);
    ldsm_x4_t(tb + (a2 ^ hx), X[0][4], X[1][4], X[0][5], X[1][5]);
    ldsm_x4_t(tb + (a3 ^ hx), X[0][6], X[1][6], X[0][7], X[1][7]);
    ldsm_x4_t(tb + (a4 ^ hx), X[0][8], X[1][8], X[0][9], X[1][9]);
    ldsm_x4_t(tb + (a5 ^ hx), X[0][10], X[1][10], X[0][11], X[1][11]);
    ldsm_x2_t(tb + (a6 ^ hx), X[0][12], X[1][12]);
  };
  load_x(nq * 32 + wg * 4 + w4);
#pragma unroll 1
  for (int it = 0; it < 2; it++) {
    const int sl = nq * 32 + (wg + 4 * it) * 4 + w4;
    float S = 0.f;
    uint32_t vx[2][4], vg[2][4];
    {
      float a0[28];
      mbar_wait(BAR(BAR_IMG + 0), 0);
      if (it < 2) TL(6 + it * 8);
      g0_rec<0>(a0, X, selU, selV, dk, BAR(BAR_G0B));
      wg_wait<0>();
      reg_fence(a0);
      const float4* wt = reinterpret_cast<const float4*>(smem + OFF_WTAB) + q * 2;
      float4 wa = wt[0], wb = wt[1];
#pragma unroll
      for (int r = 0; r < 2; r++) {
        S = fmaf(wa.x, a0[0 + 2 * r], S); S = fmaf(wa.y, a0[1 + 2 * r], S);
        S = fmaf(wa.z, a0[4 + 2 * r], S); S = fmaf(wa.w, a0[5 + 2 * r], S);
        S = fmaf(wb.x, a0[8 + 2 * r], S); S = fmaf(wb.y, a0[9 + 2 * r], S);
        S = fmaf(wb.z, a0[24 + 2 * r], S);
#pragma unroll
        for (int c = 0; c < 3; c++) {
          vx[r][c] = pack_bf16(a0[4 * c + 2 * r], a0[4 * c + 2 * r + 1]);
          vg[r][c] = pack_bf16(a0[12 + 4 * c + 2 * r], a0[12 + 4 * c + 2 * r + 1]);
        }
        vx[r][3] = pack_bf16(a0[24 + 2 * r], 0.f);
        vg[r][3] = pack_bf16(a0[24 + 2 * r + 1], 0.f);
      }
    }
    float g3[16], xa[16];
    if (it < 2) TL(7 + it * 8);
    mbar_wait(BAR(BAR_IMG + 2), 0);
    mbar_wait(BAR(BAR_IMG + 1), 0);
    mbar_wait(BAR(BAR_IMG + 3), 0);
    if (it < 2) TL(8 + it * 8);
    layer_rec<0, OFF_LB>(xa, vx, X, dk);
    if (it < 2) TL(9 + it * 8);
    wg_wait<1>();
    layer_first<OFF_LA, 3>(g3, vg, X, dk);
    wg_wait<1>();
    reg_fence(xa);
    {
      const float4* wt = reinterpret_cast<const float4*>(smem + OFF_WTAB) + 8 + q * 2;
      float4 wa = wt[0], wb = wt[1];
#pragma unroll
      for (int r = 0; r < 2; r++) {
        S = fmaf(wa.x, xa[0 + 2 * r], S); S = fmaf(wa.y, xa[1 + 2 * r], S);
        S = fmaf(wa.z, xa[4 + 2 * r], S); S = fmaf(wa.w, xa[5 + 2 * r], S);
        S = fmaf(wb.x, xa[8 + 2 * r], S); S = fmaf(wb.y, xa[9 + 2 * r], S);
        S = fmaf(wb.z, xa[12 + 2 * r], S);
#pragma unroll
        for (int c = 0; c < 3; c++) vx[r][c] = pack_bf16(xa[4 * c + 2 * r], xa[4 * c + 2 * r + 1]);
        vx[r][3] = pack_bf16(xa[12 + 2 * r], 0.f);
      }
    }
    layer_rec<3, OFF_LA>(g3, vg, X, dk);
    if (it < 2) TL(10 + it * 8);
    wg_wait<1>();
    const unsigned long long* pp = P.part + (grp * 4 + (lane & 3)) * 128 + sl;
    unsigned long long pk;
    asm volatile("ld.relaxed.gpu.global.u64 %0, [%1];" : "=l"(pk) : "l"(pp) : "memory");
    float xc[16];
    layer_rec<0, OFF_LC>(xc, vx, X, dk);
    if (it == 0) load_x(sl + 16);
    wg_wait<0>();
    reg_fence(xc);
    reg_fence(g3);
    {
      float Se = 0.f;
#pragma unroll
      for (int r = 0; r < 2; r++) {
#pragma unroll
        for (int c = 0; c < 3; c++) {
          S = fmaf(g3[4 * c + 2 * r], xc[4 * c + 2 * r], S);
          S = fmaf(g3[4 * c + 2 * r + 1], xc[4 * c + 2 * r + 1], S);
        }
        Se = fmaf(g3[12 + 2 * r], xc[12 + 2 * r], Se);
      }
      if (!(q & 1)) S += Se;
    }
#pragma unroll
    for (int o = 16; o > 0; o >>= 1) S += __shfl_xor_sync(0xffffffffu, S, o);
    if (it < 2) TL(12 + it * 8);
    {
      uint32_t spin = 0;
      while (lane < 4 && (unsigned)(pk >> 32) != epoch) {
        asm volatile("ld.relaxed.gpu.global.u64 %0, [%1];" : "=l"(pk) : "l"(pp) : "memory");
        if (++spin > (1u << 24)) __trap();
      }
      __syncwarp();
      float dv = __uint_as_float((unsigned)pk);
      float d01 = dv + __shfl_xor_sync(0xffffffffu, dv, 1);
      float dsum = d01 + __shfl_xor_sync(0xffffffffu, d01, 2);
      asm volatile("" : "+r"(bo_raw));
      if (lane == 0) P.out[grp * 128 + sl] = __float2bfloat16(S + dsum + __uint_as_float(bo_raw << 16));
    }
    __syncwarp();
    if (it < 2) TL(13 + it * 8);
  }
  TL_DUMP();
}

__global__ void __launch_bounds__(128) fallback_kernel(const int* __restrict__ idx, const bf16* __restrict__ table, const bf16* __restrict__ ws,
                                                       const bf16* __restrict__ wout, const bf16* __restrict__ w1, const bf16* __restrict__ b1,
                                                       const bf16* __restrict__ w2, const bf16* __restrict__ bout, bf16* __restrict__ out) {
  __shared__ float x0[416], xa[416], xb[416], red[128];
  const int b = blockIdx.x, t = threadIdx.x;
  for (int i = t; i < 416; i += 128) { x0[i] = bf2f(table[idx[b * NF + i / 16] * 16 + (i & 15)]); xa[i] = x0[i]; }
  __syncthreads();
  float acc = 0.f;
  float* cur = xa;
  float* nxt = xb;
  for (int l = 0; l < 6; l++) {
    for (int o = t; o < 416; o += 128) {
      const int h = o >> 4, d = o & 15;
      const bf16* w = ws + (l * NF + h) * NF * NF;
      float s = 0.f;
      for (int i = 0; i < NF; i++) {
        float u = 0.f;
        for (int j = 0; j < NF; j++) u = fmaf(bf2f(w[i * NF + j]), x0[j * 16 + d], u);
        s = fmaf(u, cur[i * 16 + d], s);
      }
      nxt[o] = s;
      acc = fmaf(s, bf2f(wout[l * NF + h]), acc);
    }
    __syncthreads();
    float* tmp = cur; cur = nxt; nxt = tmp;
  }
  for (int n = t; n < 416; n += 128) {
    float h = 0.f;
    for (int k = 0; k < 416; k++) h = fmaf(x0[k], bf2f(w1[k * 416 + n]), h);
    h += bf2f(b1[n]);
    const float gl = 0.5f * h * (1.f + tanhf(0.7978845608028654f * (h + 0.044715f * h * h * h)));
    acc = fmaf(gl, bf2f(w2[n]), acc);
  }
  red[t] = acc;
  __syncthreads();
  for (int o = 64; o > 0; o >>= 1) { if (t < o) red[t] += red[t + o]; __syncthreads(); }
  if (t == 0) out[b] = __float2bfloat16(red[0] + bf2f(bout[0]));
}

typedef CUresult (*EncodeFn)(CUtensorMap*, CUtensorMapDataType, cuuint32_t, void*, const cuuint64_t*, const cuuint64_t*,
                             const cuuint32_t*, const cuuint32_t*, CUtensorMapInterleave, CUtensorMapSwizzle,
                             CUtensorMapL2promotion, CUtensorMapFloatOOBfill);

extern "C" void kernel_launch(void* const* d_in, const int* in_sizes, int n_in, void* d_out, int out_size) {
  const int* idx = (const int*)d_in[0];
  const bf16* table = (const bf16*)d_in[1];
  const bf16* ws = (const bf16*)d_in[2];
  const bf16* wout = (const bf16*)d_in[3];
  const bf16* w1 = (const bf16*)d_in[4];
  const bf16* b1 = (const bf16*)d_in[5];
  const bf16* w2 = (const bf16*)d_in[6];
  const bf16* bo = (const bf16*)d_in[7];
  bf16* out = (bf16*)d_out;

  static EncodeFn enc = nullptr;
  static Params P;
  static int n_sm = 0;
  if (!n_sm) {
    int dev = 0;
    cudaGetDevice(&dev);
    cudaDeviceGetAttribute(&n_sm, cudaDevAttrMultiProcessorCount, dev);
  }
  if (n_sm < NCTA + NHELP) {
    fallback_kernel<<<4096, 128, 0, cudaStreamPerThread>>>(idx, table, ws, wout, w1, b1, w2, bo, out);
    return;
  }
  if (!enc) {
    void* fn = nullptr;
    cudaDriverEntryPointQueryResult qr;
    cudaGetDriverEntryPoint("cuTensorMapEncodeTiled", &fn, cudaEnableDefault, &qr);
    enc = (EncodeFn)fn;
    cudaFuncSetAttribute(main_kernel, cudaFuncAttributeMaxDynamicSharedMemorySize, LAUNCH_SMEM);
    void* p;
    cudaGetSymbolAddress(&p, g_img); P.img = (unsigned char*)p;
    cudaGetSymbolAddress(&p, g_part); P.part = (unsigned long long*)p;
    cudaGetSymbolAddress(&p, g_ctr); P.ctr = (unsigned*)p;
    cudaGetSymbolAddress(&p, g_tabs); P.tabs = p;
    P.dk = make_desc(0, 128, 256, 0);
    P.dmn = make_desc(0, 8192, 1024, 1);
    for (int c = 0; c < NCTA; c++) P.role[c] = make_role(c);
  }
  P.idx = idx; P.table = table; P.ws = ws; P.wout = wout; P.b1 = b1; P.w2 = w2; P.bout = bo; P.out = out;
  TmaMaps tms;
  for (int h = 0; h < 4; h++) {
    const int c0 = (h >> 1) * 208 + (h & 1) * 96, nw = (h & 1) ? 112 : 96;
    cuuint64_t dims[2] = {(cuuint64_t)nw, 416};
    cuuint64_t strides[1] = {832};
    cuuint32_t box[2] = {64, 64};
    cuuint32_t es[2] = {1, 1};
    enc(&tms.m[h], CU_TENSOR_MAP_DATA_TYPE_BFLOAT16, 2, (void*)(w1 + c0), dims, strides, box, es,
        CU_TENSOR_MAP_INTERLEAVE_NONE, CU_TENSOR_MAP_SWIZZLE_128B, CU_TENSOR_MAP_L2_PROMOTION_L2_128B,
        CU_TENSOR_MAP_FLOAT_OOB_FILL_NONE);
  }
  main_kernel<<<NCTA + NHELP, 512, LAUNCH_SMEM, cudaStreamPerThread>>>(P, tms);
}
```

```cpp
#include <cuda_runtime.h>
#include <cuda_bf16.h>
#include <cuda.h>
#include <stdint.h>

typedef __nv_bfloat16 bf16;

constexpr int NF = 26;
constexpr int NCTA = 128;

constexpr int G0_KS = 24, G0_N = 56, G0_SLAB = G0_N * 32;
constexpr int L_KS = 43, L_SLAB = 1024;
constexpr int G0_BYTES = G0_KS * G0_SLAB;
constexpr int L_BYTES = L_KS * L_SLAB;
constexpr int IMG_BYTES = G0_BYTES + 3 * L_BYTES;

constexpr int W1_STAGES = 7;
constexpr int W1_STAGE_BYTES = 16384;
constexpr int OFF_LB = 0;
constexpr int OFF_LA = 44032;
constexpr int OFF_LC = 88064;
__host__ __device__ constexpr int w1_off(int st) { return st < 2 ? st * W1_STAGE_BYTES : OFF_LA + (st - 2) * W1_STAGE_BYTES; }
constexpr int OFF_G0 = 132096;
constexpr int OFF_IDX = 132096 + 16384;
constexpr int OFF_TAB = OFF_G0 + G0_BYTES;
constexpr int OFF_XOFF = OFF_TAB + 32000;
constexpr int OFF_BAR = OFF_XOFF + 6656;
constexpr int OFF_BW = OFF_BAR + 256;
constexpr int OFF_W2 = OFF_BW + 256;
constexpr int OFF_WTAB = OFF_W2 + 1792;
constexpr int OFF_EPOCH = OFF_WTAB + 256;
constexpr int OFF_STAB = (OFF_EPOCH + 16 + 127) / 128 * 128;
constexpr int OFF_LOFF = OFF_STAB + 3072 + 704;
constexpr int SMEM_BYTES = OFF_STAB + 4288;
static_assert(SMEM_BYTES <= 229376, "smem");
constexpr int LAUNCH_SMEM = SMEM_BYTES;

constexpr int BAR_W1FULL = 0  , BAR_W1FREE = 10  , BAR_W1DONE = 11  ,
              BAR_IMG = 14  , BAR_X0 = 18, BAR_SETUP = 19, BAR_EPOCH = 20, BAR_TABS = 21,
              BAR_Q = 22, BAR_STAB = 23, BAR_G0B = 24, NBAR = 25;

struct TmaMaps { CUtensorMap m[4]; };
struct Params {
  const int* idx; const bf16* table; const bf16* ws; const bf16* wout; const bf16* w1; const bf16* b1; const bf16* w2; const bf16* bout;
  bf16* out;
  unsigned char* img; unsigned long long* part; unsigned* ctr; const void* tabs;
  uint64_t dk, dmn;
  uint2 role[NCTA];
};

__device__ __align__(1024) unsigned char g_img[IMG_BYTES];
__device__ unsigned long long g_part[NCTA * 128];
__device__ unsigned g_ctr;

#define GT(i) do {} while (0)
#define TL(i) do {} while (0)
#define TLP(i) do {} while (0)
#define TLA(i) do {} while (0)
#define TLW(w, i) do {} while (0)
#define TL_INIT() do {} while (0)
#define TL_START() 0
#define TL_PUT0(c) do {} while (0)
#define TL_DUMP() do {} while (0)
__device__ __forceinline__ uint32_t smem_u32(const void* p) { return (uint32_t)__cvta_generic_to_shared(p); }
__device__ __forceinline__ bool elect_one() {
  uint32_t pred;
  asm volatile("{\n.reg .pred p;\nelect.sync _|p, 0xffffffff;\nselp.u32 %0, 1, 0, p;\n}\n" : "=r"(pred));
  return pred != 0;
}
__device__ __forceinline__ void mbar_init(uint32_t bar, uint32_t cnt) {
  asm volatile("mbarrier.init.shared::cta.b64 [%0], %1;" ::"r"(bar), "r"(cnt) : "memory");
}
__device__ __forceinline__ void mbar_expect_tx(uint32_t bar, uint32_t bytes) {
  asm volatile("mbarrier.arrive.expect_tx.shared::cta.b64 _, [%0], %1;" ::"r"(bar), "r"(bytes) : "memory");
}
__device__ __forceinline__ void mbar_arrive(uint32_t bar) {
  asm volatile("mbarrier.arrive.shared::cta.b64 _, [%0];" ::"r"(bar) : "memory");
}
__device__ __forceinline__ bool mbar_try(uint32_t bar, uint32_t parity) {
  uint32_t ok;
  asm volatile("{\n.reg .pred p;\nmbarrier.try_wait.parity.shared::cta.b64 p, [%1], %2;\nselp.u32 %0, 1, 0, p;\n}\n"
               : "=r"(ok) : "r"(bar), "r"(parity) : "memory");
  return ok != 0;
}
__device__ __forceinline__ void mbar_wait(uint32_t bar, uint32_t parity) {
#pragma unroll 1
  for (uint32_t it = 0; it < (1u << 26); it++)
    if (mbar_try(bar, parity)) return;
  __trap();
}
__device__ __forceinline__ void bulk_g2s(uint32_t dst, const void* src, uint32_t bytes, uint32_t bar) {
  asm volatile("cp.async.bulk.shared::cluster.global.mbarrier::complete_tx::bytes [%0], [%1], %2, [%3];"
               ::"r"(dst), "l"(src), "r"(bytes), "r"(bar) : "memory");
}
__device__ __forceinline__ void tma_2d(uint32_t dst, const CUtensorMap* tm, int x, int y, uint32_t bar) {
  asm volatile("cp.async.bulk.tensor.2d.shared::cluster.global.mbarrier::complete_tx::bytes [%0], [%1, {%3, %4}], [%2];"
               ::"r"(dst), "l"(tm), "r"(bar), "r"(x), "r"(y) : "memory");
}
__device__ __forceinline__ void cp_async16(uint32_t dst, const void* src) {
  asm volatile("cp.async.cg.shared.global [%0], [%1], 16;" ::"r"(dst), "l"(src) : "memory");
}
__device__ __forceinline__ void fence_proxy_async() { asm volatile("fence.proxy.async.shared::cta;" ::: "memory"); }
__device__ __forceinline__ void fence_proxy_async_all() { asm volatile("fence.proxy.async;" ::: "memory"); }
template <int ID, int N> __device__ __forceinline__ void named_bar_t() { asm volatile("bar.sync %0, %1;" ::"n"(ID), "n"(N) : "memory"); }
#define named_bar(id, n) named_bar_t<id, n>()

__device__ __forceinline__ void wg_fence() { asm volatile("wgmma.fence.sync.aligned;" ::: "memory"); }
__device__ __forceinline__ void wg_commit() { asm volatile("wgmma.commit_group.sync.aligned;" ::: "memory"); }
template <int N> __device__ __forceinline__ void wg_wait() { asm volatile("wgmma.wait_group.sync.aligned %0;" ::"n"(N) : "memory"); }
template <int N> __device__ __forceinline__ void reg_fence(float (&d)[N]) {
#pragma unroll
  for (int i = 0; i < N; i++) asm volatile("" : "+f"(d[i])::"memory");
}
constexpr uint32_t SMEM_BASE = 1024;
__host__ __device__ constexpr uint64_t make_desc(uint32_t off, uint32_t lbo, uint32_t sbo, uint32_t swz) {
  return (uint64_t)(((SMEM_BASE + off) & 0x3FFFF) >> 4) | ((uint64_t)(lbo >> 4) << 16) | ((uint64_t)(sbo >> 4) << 32) | ((uint64_t)swz << 62);
}

#define ACC4(d, o) "+f"(d[o]), "+f"(d[o + 1]), "+f"(d[o + 2]), "+f"(d[o + 3])
#define ACC8(d, o) ACC4(d, o), ACC4(d, o + 4)

__device__ __forceinline__ void wgmma_rs_n32(float (&d)[16], uint32_t a0, uint32_t a1, uint32_t a2, uint32_t a3, uint64_t db, int sc) {
  asm volatile("{\n.reg .pred p;\nsetp.ne.b32 p, %21, 0;\n"
               "wgmma.mma_async.sync.aligned.m64n32k16.f32.bf16.bf16 "
               "{%0,%1,%2,%3,%4,%5,%6,%7,%8,%9,%10,%11,%12,%13,%14,%15}, {%16,%17,%18,%19}, %20, p, 1, 1, 0;\n}\n"
               : ACC8(d, 0), ACC8(d, 8)
               : "r"(a0), "r"(a1), "r"(a2), "r"(a3), "l"(db), "r"(sc));
}
__device__ __forceinline__ void wgmma_rs_n56(float (&d)[28], uint32_t a0, uint32_t a1, uint32_t a2, uint32_t a3, uint64_t db, int sc) {
  asm volatile("{\n.reg .pred p;\nsetp.ne.b32 p, %33, 0;\n"
               "wgmma.mma_async.sync.aligned.m64n56k16.f32.bf16.bf16 "
               "{%0,%1,%2,%3,%4,%5,%6,%7,%8,%9,%10,%11,%12,%13,%14,%15,%16,%17,%18,%19,%20,%21,%22,%23,%24,%25,%26,%27}, "
               "{%28,%29,%30,%31}, %32, p, 1, 1, 0;\n}\n"
               : ACC8(d, 0), ACC8(d, 8), ACC8(d, 16), ACC4(d, 24)
               : "r"(a0), "r"(a1), "r"(a2), "r"(a3), "l"(db), "r"(sc));
}
__device__ __forceinline__ void wgmma_rs_n112_tb(float (&d)[56], uint32_t a0, uint32_t a1, uint32_t a2, uint32_t a3, uint64_t db, int sc) {
  asm volatile("{\n.reg .pred p;\nsetp.ne.b32 p, %61, 0;\n"
               "wgmma.mma_async.sync.aligned.m64n112k16.f32.bf16.bf16 "
               "{%0,%1,%2,%3,%4,%5,%6,%7,%8,%9,%10,%11,%12,%13,%14,%15,%16,%17,%18,%19,%20,%21,%22,%23,%24,%25,%26,%27,%28,%29,%30,%31,%32,%33,%34,%35,%36,%37,%38,%39,%40,%41,%42,%43,%44,%45,%46,%47,%48,%49,%50,%51,%52,%53,%54,%55}, "
               "{%56,%57,%58,%59}, %60, p, 1, 1, 1;\n}\n"
               : ACC8(d, 0), ACC8(d, 8), ACC8(d, 16), ACC8(d, 24), ACC8(d, 32), ACC8(d, 40), ACC8(d, 48)
               : "r"(a0), "r"(a1), "r"(a2), "r"(a3), "l"(db), "r"(sc));
}

__device__ __forceinline__ void wgmma_rs_n8(float (&d)[4], uint32_t a0, uint32_t a1, uint32_t a2, uint32_t a3, uint64_t db, int sc) {
  asm volatile("{\n.reg .pred p;\nsetp.ne.b32 p, %9, 0;\n"
               "wgmma.mma_async.sync.aligned.m64n8k16.f32.bf16.bf16 {%0,%1,%2,%3}, {%4,%5,%6,%7}, %8, p, 1, 1, 0;\n}\n"
               : ACC4(d, 0)
               : "r"(a0), "r"(a1), "r"(a2), "r"(a3), "l"(db), "r"(sc));
}
__device__ __forceinline__ uint32_t mul_lo(uint32_t v, uint32_t r) {
  __nv_bfloat162 a = *reinterpret_cast<__nv_bfloat162*>(&v), b = *reinterpret_cast<__nv_bfloat162*>(&r);
  __nv_bfloat162 c = __hmul2(__low2bfloat162(a), b);
  return *reinterpret_cast<uint32_t*>(&c);
}
__device__ __forceinline__ uint32_t mul_hi(uint32_t v, uint32_t r) {
  __nv_bfloat162 a = *reinterpret_cast<__nv_bfloat162*>(&v), b = *reinterpret_cast<__nv_bfloat162*>(&r);
  __nv_bfloat162 c = __hmul2(__high2bfloat162(a), b);
  return *reinterpret_cast<uint32_t*>(&c);
}
__device__ __forceinline__ uint32_t mul_ew(uint32_t v, uint32_t r) {
  __nv_bfloat162 a = *reinterpret_cast<__nv_bfloat162*>(&v), b = *reinterpret_cast<__nv_bfloat162*>(&r);
  __nv_bfloat162 c = __hmul2(a, b);
  return *reinterpret_cast<uint32_t*>(&c);
}
__device__ __forceinline__ uint32_t pack_bf16(float lo, float hi) {
  uint32_t r;
  asm("cvt.rn.bf16x2.f32 %0, %1, %2;" : "=r"(r) : "f"(hi), "f"(lo));
  return r;
}
__device__ __forceinline__ float bf2f(bf16 v) { return __bfloat162float(v); }
__device__ __forceinline__ float bflo(uint32_t w) { return __uint_as_float(w << 16); }
__device__ __forceinline__ float bfhi(uint32_t w) { return __uint_as_float(w & 0xffff0000u); }

__device__ __forceinline__ void st_img(uint32_t* p, uint32_t v) {
  asm volatile("st.relaxed.gpu.global.u32 [%0], %1;" ::"l"(p), "r"(v) : "memory");
}
__device__ __forceinline__ uint32_t ld_back(const uint32_t* p) {
  uint32_t v;
  asm volatile("ld.relaxed.gpu.global.u32 %0, [%1];" : "=r"(v) : "l"(p) : "memory");
  return v;
}
__host__ __device__ constexpr int Fq(int q, int t, int e) {
  if (t == 12) return 24 + e;
  const int u = (t + 3 * q) % 12;
  const int sw = (q >= 2 && u >= 6) ? 1 : 0;
  return 2 * u + (e ^ sw);
}
constexpr int M_ONE = 26, M_NONE = 27;
struct Mono { int f1, f2; };
__host__ __device__ constexpr Mono g0_mono(int s, int q, int e) {
  if (s < 30) { const int d = s / 6 + 1, a = (s % 6) >> 1; return {Fq(q, a, s & 1), Fq(q, a + d, e)}; }
  if (s < 33) return {Fq(q, s - 30, e), Fq(q, s - 24, e)};
  if (s < 35) return {Fq(q, s - 33, e), Fq(q, s - 33, e)};
  if (s == 35) return {Fq(q, e, 0), Fq(q, e, 1)};
  if (s == 36) return {Fq(q, 2, 0), Fq(q, 2, e)};
  if (s == 37) return e ? Mono{Fq(q, 2, 1), Fq(q, 2, 1)} : Mono{M_NONE, M_NONE};
  if (s < 44) return {24 + ((s - 38) & 1), Fq(q, (s - 38) >> 1, e)};
  if (s < 47) return {Fq(q, s - 44, e), M_ONE};
  if (q == 0) return {24, 24 + e};
  if (q == 1) return e ? Mono{25, 25} : Mono{M_NONE, M_NONE};
  if (q == 2) return {24 + e, M_ONE};
  return e ? Mono{M_NONE, M_NONE} : Mono{M_ONE, M_ONE};
}
constexpr int QM_RS = 40;
constexpr int O_ZERO = 31 * QM_RS + 39, O_CONST = 30 * QM_RS + 39;
struct StaticTabs {
  uint32_t otab[48 * 8];
  uint32_t x1tab[48 * 8];
  uint16_t ltab[88 * 4];
  uint16_t loff[32 * 8];
};
constexpr StaticTabs make_tabs() {
  StaticTabs T{};
  for (int s = 0; s < 48; s++)
    for (int q = 0; q < 4; q++)
      for (int e = 0; e < 2; e++) {
        const Mono m = g0_mono(s, q, e);
        const bool none = m.f1 == M_NONE, cs = m.f1 == M_ONE, lin = m.f2 == M_ONE;
        const uint32_t o1 = none ? O_ZERO : cs ? O_CONST : m.f1 * QM_RS + (lin ? 26 : m.f2);
        const uint32_t dg = (!none && !cs && !lin && m.f1 == m.f2) ? 1u : 0u;
        T.otab[s * 8 + q * 2 + e] = o1 | (dg << 16);
        const bool qd = m.f1 < NF && m.f2 < NF;
        const uint32_t y1 = qd ? m.f1 * NF + m.f2 : 0xffffu;
        const uint32_t y2 = (qd && m.f1 != m.f2) ? m.f2 * NF + m.f1 : 0xffffu;
        T.x1tab[s * 8 + q * 2 + e] = y1 | (y2 << 16);
      }
  for (int s = 0; s < 88; s++)
    for (int q = 0; q < 4; q++) {
      uint16_t v = 0;
      if (s < 85) {
        const bool ex = s >= 78;
        const int a = s / 13, k = s - 78;
        const int tt = ex ? ((k < 3) ? k : (k < 6 ? k + 3 : 12)) : s % 13;
        const int in = ex ? 24 + (q >> 1) : 8 * (a >> 1) + 2 * q + (a & 1);
        const bool valid = !(ex && tt == 12 && (q & 1));
        const int f0 = Fq(q, tt, 0);
        v = (uint16_t)((f0 >> 1) | ((f0 & 1) << 4) | ((valid ? 1 : 0) << 5) | (in << 6));
      }
      T.ltab[s * 4 + q] = v;
    }
  for (int ln = 0; ln < 32; ln++)
    for (int k = 0; k < 8; k++) {
      const int m = ln >> 3, r = ln & 7;
      const int tt = (k < 6) ? 2 * k + (m >> 1) : 12;
      T.loff[ln * 8 + k] = (uint16_t)(2 * Fq(r >> 1, tt, r & 1));
    }
  return T;
}
static_assert(sizeof(StaticTabs) == 4288, "tabs");
__device__ __align__(128) const StaticTabs g_tabs = make_tabs();

constexpr int SETUP_WARPS = 7;
constexpr int WL_BYTES = NF * NF * NF * 2;
static inline uint2 make_role(int cta) {
  int kind = 5, grp = 0, j = 0, off = 0, bytes = 0;
  const int c = cta, SL = NF * NF * 2;
  if (c < 56) { kind = 1 + c / 28; grp = (c % 28) / 7; j = c % 7; off = kind * WL_BYTES + grp * 8 * SL; bytes = (grp < 3 ? 8 : 2) * SL; }
  else if (c < 80) { kind = 0; grp = (c - 56) / 8; j = (c - 56) % 8; off = 3 * WL_BYTES + grp * 8 * SL; bytes = 8 * SL; }
  else if (c < 83) { kind = 0; grp = 3; j = c - 80; off = 3 * WL_BYTES + 24 * SL; bytes = 2 * SL; }
  else if (c < 95) { kind = 3; grp = (c - 83) / 4; j = (c - 83) % 4; off = grp * 8 * SL; bytes = 8 * SL; }
  const int delta = off & 127;
  uint2 r;
  r.x = (uint32_t)(off - delta) | ((uint32_t)kind << 24);
  r.y = (uint32_t)(bytes + delta) | ((uint32_t)delta << 16) | ((uint32_t)grp << 24) | ((uint32_t)j << 28);
  return r;
}

__device__ __forceinline__ uint32_t layer_row(int li, int grp, int r, int lane, const unsigned char* raw, const StaticTabs* T,
                                              uint32_t bar, uint32_t tbar, const bf16* __restrict__ wout, uint32_t* img32) {
  const int ks = li ? r : 13 * grp + (r >> 2), ng = li ? grp : (r & 3);
  if (ks >= 43 || (!li && grp < 3 && r >= 52)) return 0;
  const uint32_t* w32 = reinterpret_cast<const uint32_t*>(raw);
  const int n8 = lane >> 2, q = lane & 3;
  const int o = (ng < 3) ? ng * 8 + n8 : 24 + (n8 >> 2);
  const bool vo = (ng < 3) || !(n8 & 1);
  const int ob = li ? (o - 8 * grp) * 338 : o * 13 - 8 * grp * 338;
  const int si = li ? 13 : 338;
  uint32_t bias = 0;
  if (vo && ks == 42 && li == 0 && q == 0) bias = (uint32_t)__ldg(reinterpret_cast<const unsigned short*>(wout) + 2 * NF + o);
  uint32_t* dst = img32 + G0_BYTES / 4 + li * (L_BYTES / 4) + (ks * 4 + ng) * 64 + lane;
  mbar_wait(tbar, 0);
  const uint32_t e0 = T->ltab[8 * ks + q], e1 = T->ltab[8 * ks + 4 + q];
  const bool v0 = vo && (e0 & 32), v1 = vo && (e1 & 32);
  const int s0 = v0 ? ob + (e0 >> 6) * si + (e0 & 15) : 0, s1 = v1 ? ob + (e1 >> 6) * si + (e1 & 15) : 0;
  TL(33);
  mbar_wait(bar, 0);
  TL(36);
  uint32_t w0 = w32[s0], w1 = w32[s1];
  w0 = (e0 & 16) ? __funnelshift_l(w0, w0, 16) : w0;
  w1 = (e1 & 16) ? __funnelshift_l(w1, w1, 16) : w1;
  w0 = v0 ? w0 : 0u;
  w1 = v1 ? w1 : bias;
  st_img(dst, w0); st_img(dst + 32, w1);
  return (ld_back(dst) ^ w0) | (ld_back(dst + 32) ^ w1);
}
__device__ __forceinline__ float x1_val(const unsigned short* wh, uint32_t e) {
  const uint32_t a = e & 0xffff, b = e >> 16;
  const uint32_t x = wh[a == 0xffff ? 0 : a], y = wh[b == 0xffff ? 0 : b];
  return (a == 0xffff ? 0.f : __uint_as_float(x << 16)) + (b == 0xffff ? 0.f : __uint_as_float(y << 16));
}
__device__ __forceinline__ uint32_t x1_row(int ng, int ks, int lane, const unsigned char* raw, const StaticTabs* T, uint32_t bar, uint32_t tbar, uint32_t* img32) {
  if (ks >= 24) return 0;
  const int n8 = lane >> 2, q = lane & 3;
  const unsigned short* wh = reinterpret_cast<const unsigned short*>(raw) + n8 * (NF * NF);
  uint32_t* dst = img32 + ks * (G0_SLAB / 4) + ng * 64 + lane;
  mbar_wait(tbar, 0);
  const uint2 ea = *reinterpret_cast<const uint2*>(&T->x1tab[16 * ks + 2 * q]), eb = *reinterpret_cast<const uint2*>(&T->x1tab[16 * ks + 8 + 2 * q]);
  mbar_wait(bar, 0);
  const uint32_t w0 = pack_bf16(x1_val(wh, ea.x), x1_val(wh, ea.y)), w1 = pack_bf16(x1_val(wh, eb.x), x1_val(wh, eb.y));
  st_img(dst, w0); st_img(dst + 32, w1);
  return (ld_back(dst) ^ w0) | (ld_back(dst + 32) ^ w1);
}

constexpr int NHELP = 4;
constexpr int H_MS = 32 * QM_RS + 4;
constexpr int H_W5 = 0, H_W4 = 35328, H_W0 = 70656, H_TAB = 73472, H_B = 77824, H_M = 82944, H_XE = H_M + 8 * H_MS * 4, H_BAR = H_XE + 1536;
struct HB { bf16 Bh[32][40]; };
__device__ __forceinline__ void mma_bf16(float (&c)[4], uint32_t a0, uint32_t a1, uint32_t a2, uint32_t a3, uint32_t b0, uint32_t b1) {
  asm volatile("mma.sync.aligned.m16n8k16.row.col.f32.bf16.bf16.f32 {%0,%1,%2,%3}, {%4,%5,%6,%7}, {%8,%9}, {%0,%1,%2,%3};"
               : "+f"(c[0]), "+f"(c[1]), "+f"(c[2]), "+f"(c[3]) : "r"(a0), "r"(a1), "r"(a2), "r"(a3), "r"(b0), "r"(b1));
}
__device__ __forceinline__ void helper_role(int hk, const Params& P, unsigned char* smem, uint32_t sb) {
  const int t = threadIdx.x, warp = __shfl_sync(0xffffffffu, t >> 5, 0), lane = t & 31;
  const uint32_t d5bar = sb + H_BAR, d4bar = sb + H_BAR + 8, tbar = sb + H_BAR + 16;
  const unsigned char* wsb = reinterpret_cast<const unsigned char*>(P.ws);
  HB* Q = reinterpret_cast<HB*>(smem + H_B);
  float* M = reinterpret_cast<float*>(smem + H_M);
  if (warp < 3 && elect_one()) {
    mbar_init(sb + H_BAR + 8 * warp, 1);
    asm volatile("fence.mbarrier_init.release.cluster;" ::: "memory");
  }
  for (int i = t; i < 640; i += 512) reinterpret_cast<uint32_t*>(Q)[i] = 0;
  __syncthreads();
  constexpr uint32_t W5B = WL_BYTES + ((5 * WL_BYTES) & 127), W4B = WL_BYTES + ((4 * WL_BYTES) & 127);
  if (warp < 12 && elect_one()) {
    if (warp < 5) {
      if (warp == 0) mbar_expect_tx(d5bar, W5B);
      bulk_g2s(sb + H_W5 + warp * 8192, wsb + ((5 * WL_BYTES) & ~127) + warp * 8192, warp < 4 ? 8192u : W5B - 4 * 8192, d5bar);
    } else if (warp < 10) {
      const int c = warp - 5;
      if (c == 0) mbar_expect_tx(d4bar, W4B + (hk == 3 ? 2768 : 0));
      bulk_g2s(sb + H_W4 + c * 8192, wsb + ((4 * WL_BYTES) & ~127) + c * 8192, c < 4 ? 8192u : W4B - 4 * 8192, d4bar);
    } else if (warp == 10) {
      mbar_expect_tx(tbar, sizeof(StaticTabs));
      bulk_g2s(sb + H_TAB, P.tabs, sizeof(StaticTabs), tbar);
    } else if (hk == 3) {
      bulk_g2s(sb + H_W0, wsb + ((24 * NF * NF * 2) & ~127), 2768, d4bar);
    }
  }
  const unsigned short* wo16 = reinterpret_cast<const unsigned short*>(P.wout);
  uint32_t c5[13];
#pragma unroll
  for (int k = 0; k < 13; k++) c5[k] = __ldg(reinterpret_cast<const uint32_t*>(P.wout + 5 * NF) + k);
  unsigned short wv = 0;
  const int io0 = (hk < 3) ? 8 * hk : 24;
  if (t >= 352 && t < 352 + NF) wv = __ldg(wo16 + 4 * NF + t - 352);
  else if (t >= 384 && t < 392 && io0 + t - 384 < NF) wv = __ldg(wo16 + 3 * NF + io0 + t - 384);
  const StaticTabs* T = reinterpret_cast<const StaticTabs*>(smem + H_TAB);
  const int n8 = lane >> 2, q = lane & 3, g = n8;
  const int fil = (hk < 3) ? n8 : (n8 >> 2);
  const bool fx1 = (hk == 3) && !(n8 & 1);
  uint32_t* dst = reinterpret_cast<uint32_t*>(P.img) + (warp >> 1) * (G0_SLAB / 4) + (warp & 1) * 32 + (3 + hk) * 64 + lane;
  if (t >= 352 && t < 352 + NF) reinterpret_cast<unsigned short*>(&Q->Bh[26][t - 352])[0] = wv;
  if (t >= 384 && t < 392) { M[(t - 384) * H_MS + O_ZERO] = 0.f; M[(t - 384) * H_MS + O_CONST] = __uint_as_float((uint32_t)wv << 16); }
  mbar_wait(d5bar, 0);
  if (t < 338) {
    const uint32_t* w5 = reinterpret_cast<const uint32_t*>(smem + H_W5 + ((5 * WL_BYTES) & 127)) + t;
    float s0 = 0.f, s1 = 0.f, s2 = 0.f, s3 = 0.f;
#pragma unroll
    for (int k = 0; k < 13; k++) {
      const uint32_t wa = w5[(2 * k) * 338], wb = w5[(2 * k + 1) * 338];
      const float ca = bflo(c5[k]), cb = bfhi(c5[k]);
      s0 = fmaf(ca, bflo(wa), s0); s1 = fmaf(ca, bfhi(wa), s1);
      s2 = fmaf(cb, bflo(wb), s2); s3 = fmaf(cb, bfhi(wb), s3);
    }
    const int h = (t * 79) >> 10, tp = t - 13 * h;
    Q->Bh[2 * tp][h] = __float2bfloat16(s0 + s2);
    Q->Bh[2 * tp + 1][h] = __float2bfloat16(s1 + s3);
  }
  mbar_wait(tbar, 0);
  uint2 fot[3];
#pragma unroll
  for (int r = 0; r < 3; r++) fot[r] = *reinterpret_cast<const uint2*>(&T->otab[(warp + 16 * r) * 8 + q * 2]);
  mbar_wait(d4bar, 0);
  const int il = warp - 8;
  const bool mma_warp = (warp >= 8) && (hk < 3 || il < 2);
  uint32_t u[4][4];
  if (mma_warp) {
    const unsigned short* A = reinterpret_cast<const unsigned short*>(smem + H_W4 + ((4 * WL_BYTES) & 127)) + (io0 + il) * NF + g;
#pragma unroll
    for (int rb = 0; rb < 4; rb++) {
#pragma unroll
      for (int kh = 0; kh < 4; kh++) {
        const int k = 8 * kh + 2 * q;
        const bool ok = (k < NF) && (8 * rb + g < NF);
        const int kc = (k < NF) ? k : 0;
        const uint32_t lo = A[kc * (NF * NF) + 8 * rb], hi = A[(kc + 1) * (NF * NF) + 8 * rb];
        u[rb][kh] = ok ? (lo | (hi << 16)) : 0u;
      }
    }
  }
  if (hk == 3) {
    const int u0 = (warp < 8) ? t : (warp >= 10 && warp < 14) ? t - 64 : -1;
    if (u0 >= 0) {
      const int sl = u0 >> 3, xl = (u0 >> 2) & 1, xq = u0 & 3;
      const uint2 xt = *reinterpret_cast<const uint2*>(&T->x1tab[sl * 8 + xq * 2]);
      const unsigned short* wh = reinterpret_cast<const unsigned short*>(smem + H_W0 + ((24 * NF * NF * 2) & 127)) + xl * (NF * NF);
      reinterpret_cast<uint32_t*>(smem + H_XE)[u0] = pack_bf16(x1_val(wh, xt.x), x1_val(wh, xt.y));
    }
  }
  __syncthreads();
  if (mma_warp) {
    uint32_t w[4][4];
#pragma unroll
    for (int rb = 0; rb < 4; rb++)
#pragma unroll
      for (int kh = 0; kh < 4; kh++) w[rb][kh] = *reinterpret_cast<const uint32_t*>(&Q->Bh[8 * rb + g][8 * kh + 2 * q]);
    float* Mi = M + il * H_MS;
    float c[2][4][4];
#pragma unroll
    for (int mt = 0; mt < 2; mt++)
#pragma unroll
      for (int nt = 0; nt < 4; nt++) { c[mt][nt][0] = c[mt][nt][1] = c[mt][nt][2] = c[mt][nt][3] = 0.f; }
#pragma unroll
    for (int kk = 0; kk < 2; kk++) {
#pragma unroll
      for (int mt = 0; mt < 2; mt++)
#pragma unroll
        for (int nt = 0; nt < 4; nt++)
          mma_bf16(c[mt][nt], u[2 * mt][2 * kk], u[2 * mt + 1][2 * kk], u[2 * mt][2 * kk + 1], u[2 * mt + 1][2 * kk + 1], w[nt][2 * kk], w[nt][2 * kk + 1]);
#pragma unroll
      for (int mt = 0; mt < 2; mt++)
#pragma unroll
        for (int nt = 0; nt < 4; nt++)
          mma_bf16(c[mt][nt], w[2 * mt][2 * kk], w[2 * mt + 1][2 * kk], w[2 * mt][2 * kk + 1], w[2 * mt + 1][2 * kk + 1], u[nt][2 * kk], u[nt][2 * kk + 1]);
    }
#pragma unroll
    for (int mt = 0; mt < 2; mt++)
#pragma unroll
      for (int nt = 0; nt < 4; nt++) {
        *reinterpret_cast<float2*>(&Mi[(mt * 16 + g) * QM_RS + nt * 8 + 2 * q]) = make_float2(c[mt][nt][0], c[mt][nt][1]);
        *reinterpret_cast<float2*>(&Mi[(mt * 16 + g + 8) * QM_RS + nt * 8 + 2 * q]) = make_float2(c[mt][nt][2], c[mt][nt][3]);
      }
  }
  __syncthreads();
  uint32_t val[3], chk = 0;
#pragma unroll
  for (int r = 0; r < 3; r++) {
    const float* Mf = M + fil * H_MS;
    float v0 = Mf[fot[r].x & 0xffff], v1 = Mf[fot[r].y & 0xffff];
    v0 = (fot[r].x >> 16) ? 0.5f * v0 : v0;
    v1 = (fot[r].y >> 16) ? 0.5f * v1 : v1;
    const uint32_t xe = reinterpret_cast<const uint32_t*>(smem + H_XE)[(warp + 16 * r) * 8 + (n8 >> 2) * 4 + q];
    val[r] = fx1 ? xe : pack_bf16(v0, v1);
    st_img(dst + r * 8 * (G0_SLAB / 4), val[r]);
  }
#pragma unroll
  for (int r = 0; r < 3; r++) chk |= ld_back(dst + r * 8 * (G0_SLAB / 4)) ^ val[r];
  if (__any_sync(0xffffffffu, chk != 0)) __trap();
  __syncthreads();
  if (t == 0) asm volatile("red.relaxed.gpu.global.add.u32 [%0], 32;" ::"l"(P.ctr) : "memory");
}

template <int S>
__device__ __forceinline__ uint32_t l_prod(const uint32_t (&vp)[4], const uint32_t (&X)[13]) {
  if constexpr (S < 78) {
    constexpr int a = S / 13, t = S % 13;
    return (a & 1) ? mul_hi(vp[a >> 1], X[t]) : mul_lo(vp[a >> 1], X[t]);
  } else if constexpr (S < 85) {
    constexpr int k = S - 78;
    constexpr int t = (k < 3) ? k : (k < 6 ? k + 3 : 12);
    return mul_lo(vp[3], X[t]);
  } else {
    return 0x00003F80u;
  }
}
template <int S>
__device__ __forceinline__ uint32_t g0_prod(const uint32_t (&X)[13], uint32_t selU, uint32_t selV) {
  if constexpr (S < 30) {
    constexpr int d = S / 6 + 1, a = (S % 6) >> 1;
    return (S & 1) ? mul_hi(X[a], X[a + d]) : mul_lo(X[a], X[a + d]);
  } else if constexpr (S < 33) {
    return mul_ew(X[S - 30], X[S - 24]);
  } else if constexpr (S < 35) {
    return mul_ew(X[S - 33], X[S - 33]);
  } else if constexpr (S == 35) {
    return mul_ew(__byte_perm(X[0], X[1], 0x5410), __byte_perm(X[0], X[1], 0x7632));
  } else if constexpr (S == 36) {
    return mul_lo(X[2], X[2]);
  } else if constexpr (S == 37) {
    return mul_hi(X[2], X[2]);
  } else if constexpr (S < 44) {
    constexpr int a = (S - 38) >> 1;
    return ((S - 38) & 1) ? mul_hi(X[12], X[a]) : mul_lo(X[12], X[a]);
  } else if constexpr (S < 47) {
    return X[S - 44];
  } else {
    return mul_ew(__byte_perm(X[12], 0x3F803F80u, selU), __byte_perm(X[12], 0x3F803F80u, selV));
  }
}

constexpr int NBK = 4;

template <int KS, int KE>
__device__ __forceinline__ void l_fill(uint32_t (*A)[4], const uint32_t (&vp)[2][4], const uint32_t (&X)[2][13]) {
  A[0][0] = l_prod<2 * KS>(vp[0], X[0]);
  A[0][1] = l_prod<2 * KS>(vp[1], X[1]);
  A[0][2] = l_prod<2 * KS + 1>(vp[0], X[0]);
  A[0][3] = l_prod<2 * KS + 1>(vp[1], X[1]);
  if constexpr (KS + 1 < KE) l_fill<KS + 1, KE>(A + 1, vp, X);
}
template <int KS, int OFF>
__device__ __forceinline__ void layer_rec(float (&d)[16], const uint32_t (&vp)[2][4], const uint32_t (&X)[2][13], uint64_t dk) {
  constexpr int KE = (KS + NBK < L_KS) ? KS + NBK : L_KS;
  uint32_t A[NBK][4];
  l_fill<KS, KE>(A, vp, X);
  wg_fence();
#pragma unroll
  for (int k = 0; k < KE - KS; k++)
    wgmma_rs_n32(d, A[k][0], A[k][1], A[k][2], A[k][3], dk + (uint64_t)((OFF + (KS + k) * L_SLAB) >> 4), (KS + k) > 0);
  wg_commit();
  if constexpr (KE < L_KS) {
    wg_wait<1>();
    layer_rec<KE, OFF>(d, vp, X, dk);
  }
}
template <int OFF, int NK>
__device__ __forceinline__ void layer_first(float (&d)[16], const uint32_t (&vp)[2][4], const uint32_t (&X)[2][13], uint64_t dk) {
  uint32_t A[NK][4];
  l_fill<0, NK>(A, vp, X);
  wg_fence();
#pragma unroll
  for (int k = 0; k < NK; k++) wgmma_rs_n32(d, A[k][0], A[k][1], A[k][2], A[k][3], dk + (uint64_t)((OFF + k * L_SLAB) >> 4), k > 0);
  wg_commit();
}
template <int KS, int KE>
__device__ __forceinline__ void g0_fill(uint32_t (*A)[4], const uint32_t (&X)[2][13], uint32_t selU, uint32_t selV) {
  A[0][0] = g0_prod<2 * KS>(X[0], selU, selV);
  A[0][1] = g0_prod<2 * KS>(X[1], selU, selV);
  A[0][2] = g0_prod<2 * KS + 1>(X[0], selU, selV);
  A[0][3] = g0_prod<2 * KS + 1>(X[1], selU, selV);
  if constexpr (KS + 1 < KE) g0_fill<KS + 1, KE>(A + 1, X, selU, selV);
}
template <int B0>
__device__ __forceinline__ void g0_rec(float (&d)[28], const uint32_t (&X)[2][13], uint32_t selU, uint32_t selV, uint64_t dk, uint32_t bar2) {
  constexpr int KS = B0 * NBK;
  if constexpr (KS == 12) mbar_wait(bar2, 0);
  constexpr int KE = (KS + NBK < G0_KS) ? KS + NBK : G0_KS;
  uint32_t A[NBK][4];
  g0_fill<KS, KE>(A, X, selU, selV);
  wg_fence();
#pragma unroll
  for (int k = 0; k < KE - KS; k++)
    wgmma_rs_n56(d, A[k][0], A[k][1], A[k][2], A[k][3], dk + (uint64_t)((OFF_G0 + (KS + k) * G0_SLAB) >> 4), (KS + k) > 0);
  wg_commit();
  if constexpr (KE < G0_KS) {
    wg_wait<1>();
    g0_rec<B0 + 1>(d, X, selU, selV, dk, bar2);
  }
}

__device__ __forceinline__ void ldsm_x4_t(uint32_t addr, uint32_t& r0, uint32_t& r1, uint32_t& r2, uint32_t& r3) {
  asm volatile("ldmatrix.sync.aligned.m8n8.x4.trans.shared.b16 {%0,%1,%2,%3}, [%4];"
               : "=r"(r0), "=r"(r1), "=r"(r2), "=r"(r3) : "r"(addr) : "memory");
}
__device__ __forceinline__ void ldsm_x2_t(uint32_t addr, uint32_t& r0, uint32_t& r1) {
  asm volatile("ldmatrix.sync.aligned.m8n8.x2.trans.shared.b16 {%0,%1}, [%2];" : "=r"(r0), "=r"(r1) : "r"(addr) : "memory");
}
__device__ __forceinline__ float tanh_fast(float x) { float y; asm("tanh.approx.f32 %0, %1;" : "=f"(y) : "f"(x)); return y; }

__device__ __forceinline__ uint32_t gelu2_pair(float lo, float hi, uint32_t bias) {
  uint32_t x = pack_bf16(lo, hi), t, u;
  asm("add.rn.bf16x2 %0, %0, %1;" : "+r"(x) : "r"(bias));
  asm("mul.rn.bf16x2 %0, %1, %1;" : "=r"(t) : "r"(x));
  asm("fma.rn.bf16x2 %0, %0, %1, %2;" : "+r"(t) : "r"(0x3D123D12u), "r"(0x3F4C3F4Cu));
  asm("mul.rn.bf16x2 %0, %1, %2;" : "=r"(u) : "r"(x), "r"(t));
  asm("tanh.approx.bf16x2 %0, %0;" : "+r"(u));
  asm("fma.rn.bf16x2 %0, %1, %0, %1;" : "+r"(u) : "r"(x));
  return u;
}

__device__ __forceinline__ void ldsm_x4(uint32_t addr, uint32_t (&r)[4]) {
  asm volatile("ldmatrix.sync.aligned.m8n8.x4.shared.b16 {%0,%1,%2,%3}, [%4];"
               : "=r"(r[0]), "=r"(r[1]), "=r"(r[2]), "=r"(r[3]) : "r"(addr) : "memory");
}
__device__ __forceinline__ uint32_t lds_u16(uint32_t addr) {
  unsigned short v;
  asm volatile("ld.shared.u16 %0, [%1];" : "=h"(v) : "r"(addr) : "memory");
  return v;
}
__device__ __forceinline__ uint32_t lds_u32(uint32_t addr) {
  uint32_t v;
  asm volatile("ld.shared.u32 %0, [%1];" : "=r"(v) : "r"(addr) : "memory");
  return v;
}

__global__ void __launch_bounds__(512, 1)
main_kernel(const __grid_constant__ Params P, const __grid_constant__ TmaMaps tms) {
  extern __shared__ __align__(1024) unsigned char smem[];
  const uint32_t sb = smem_u32(smem);
  const int tid = threadIdx.x, warp = __shfl_sync(0xffffffffu, tid >> 5, 0), lane = tid & 31;
  if (blockIdx.x < NHELP) {
    helper_role(blockIdx.x, P, smem, sb);
    return;
  }
  const int cta = blockIdx.x - NHELP, nq = cta & 3, grp = cta >> 2;
  const uint2 role = P.role[cta];
  const uint32_t bar0 = sb + OFF_BAR;
  auto BAR = [&](int i) { return bar0 + 8 * i; };
  const int wg = warp >> 2, w4 = warp & 3, g = lane >> 2, q = lane & 3;
  const uint64_t dk = P.dk;
  const long long tl_c0 = TL_START();
  TL_INIT();
  TL_PUT0(tl_c0);

  if (tid < 256) {
    const unsigned char* isrc = reinterpret_cast<const unsigned char*>(P.idx + grp * 128 * NF);
#pragma unroll
    for (int k = 0; k < 4; k++) {
      const int c = tid + 256 * k;
      if (c < 832) cp_async16(sb + OFF_IDX + c * 16, isrc + c * 16);
    }
    asm volatile("cp.async.commit_group;" ::: "memory");
#pragma unroll
    for (int k = 0; k < 8; k++) {
      const int c = tid + 256 * k;
      if (c < 2000) cp_async16(sb + OFF_TAB + ((c ^ ((c >> 3) & 1)) << 4), reinterpret_cast<const unsigned char*>(P.table) + c * 16);
    }
    asm volatile("cp.async.commit_group;" ::: "memory");
  }
  if (elect_one()) {
    mbar_init(BAR(warp), (warp == BAR_W1FREE || warp == BAR_W1DONE) ? 2 : (warp < W1_STAGES && (warp & 1)) ? 256 : 1);
    if (warp < NBAR - 16)
      mbar_init(BAR(16 + warp), (16 + warp == BAR_X0) ? 256 : (16 + warp == BAR_SETUP) ? SETUP_WARPS : (16 + warp == BAR_TABS) ? 224 : 1);
    asm volatile("fence.mbarrier_init.release.cluster;" ::: "memory");
  }
  __syncthreads();
  TL(26);

  if (warp == 15) {
    if (elect_one()) {
      mbar_expect_tx(BAR(BAR_STAB), sizeof(StaticTabs));
      bulk_g2s(sb + OFF_STAB, P.tabs, sizeof(StaticTabs), BAR(BAR_STAB));
      if ((sb & 0x3FFFF) != SMEM_BASE) __trap();
      const CUtensorMap* tm0 = &tms.m[nq];
      asm volatile("prefetch.tensormap [%0];" ::"l"(tm0) : "memory");
#pragma unroll
      for (int st = 0; st < W1_STAGES; st += 2) {
        if (st == 2 && (role.x >> 24) < 5) mbar_wait(BAR(BAR_Q), 0);
        mbar_expect_tx(BAR(BAR_W1FULL + st), W1_STAGE_BYTES);
        tma_2d(sb + w1_off(st), tm0, 0, st * 64, BAR(BAR_W1FULL + st));
        tma_2d(sb + w1_off(st) + 8192, tm0, 64, st * 64, BAR(BAR_W1FULL + st));
      }
      TLP(22);
      mbar_wait(BAR(BAR_EPOCH), 0);
      TLP(23);
      const unsigned target = lds_u32(sb + OFF_EPOCH) << 8;
      {
        unsigned v;
        uint32_t it = 0;
#pragma unroll 1
        do {
          asm volatile("ld.relaxed.gpu.global.u32 %0, [%1];" : "=r"(v) : "l"(P.ctr) : "memory");
          if (++it > (1u << 22)) __trap();
        } while ((int)(v - target) < 0);
        asm volatile("fence.acq_rel.cta;" ::: "memory");
      }
      fence_proxy_async_all();
      mbar_wait(BAR(BAR_X0), 0);
      TLP(24);
      mbar_expect_tx(BAR(BAR_IMG + 0), G0_BYTES / 2);
      mbar_expect_tx(BAR(BAR_G0B), G0_BYTES / 2);
#pragma unroll
      for (int i = 0; i < 6; i++)
        bulk_g2s(sb + OFF_G0 + i * (G0_BYTES / 6), P.img + i * (G0_BYTES / 6), G0_BYTES / 6, i < 3 ? BAR(BAR_IMG + 0) : BAR(BAR_G0B));
      mbar_wait(BAR(BAR_W1FREE), 0);
      mbar_expect_tx(BAR(BAR_IMG + 2), L_BYTES);
#pragma unroll
      for (int i = 0; i < 4; i++)
        bulk_g2s(sb + OFF_LB + i * (L_BYTES / 4), P.img + G0_BYTES + L_BYTES + i * (L_BYTES / 4), L_BYTES / 4, BAR(BAR_IMG + 2));
      mbar_wait(BAR(BAR_W1DONE), 0);
      mbar_expect_tx(BAR(BAR_IMG + 1), L_BYTES);
      mbar_expect_tx(BAR(BAR_IMG + 3), L_BYTES);
#pragma unroll
      for (int i = 0; i < 2; i++)
        bulk_g2s(sb + OFF_LA + i * (L_BYTES / 2), P.img + G0_BYTES + i * (L_BYTES / 2), L_BYTES / 2, BAR(BAR_IMG + 1));
#pragma unroll
      for (int i = 0; i < 2; i++)
        bulk_g2s(sb + OFF_LC + i * (L_BYTES / 2), P.img + G0_BYTES + 2 * L_BYTES + i * (L_BYTES / 2), L_BYTES / 2, BAR(BAR_IMG + 3));
      TLP(25);
    }
    __syncwarp();
    mbar_wait(BAR(BAR_X0), 0);
    mbar_wait(BAR(BAR_TABS), 0);
  } else if (wg < 2) {
    {
      const int c0 = (nq >> 1) * 208 + (nq & 1) * 96, nch = (nq & 1) ? 14 : 12;
      const unsigned char* wsrc = reinterpret_cast<const unsigned char*>(P.w1 + c0);
#pragma unroll
      for (int st = 1; st < W1_STAGES; st += 2) {
#pragma unroll
        for (int k = 0; k < 4; k++) {
          const int u = tid + 256 * k, row = u / 14, ch = u - 14 * row;
          if (u < 896) {
            const uint32_t dst = sb + w1_off(st) + (ch >> 3) * 8192 + row * 128 + (((ch & 7) ^ (row & 7)) << 4);
            const unsigned char* src = wsrc + (st * 64 + row) * 832 + (ch < nch ? ch : 0) * 16;
            asm volatile("cp.async.cg.shared.global [%0], [%1], 16, %2;" ::"r"(dst), "l"(src), "r"(ch < nch ? 16 : 0) : "memory");
          }
        }
        asm volatile("cp.async.mbarrier.arrive.noinc.shared::cta.b64 [%0];" ::"r"(BAR(BAR_W1FULL + st)) : "memory");
      }
      asm volatile("cp.async.commit_group;" ::: "memory");
    }
    asm volatile("cp.async.wait_group 2;" ::: "memory");
    named_bar(1, 256);
#pragma unroll
    for (int k = 0; k < 7; k++) {
      const int p = tid + 256 * k;
      if (p < 64 * NF) {
        const uint2 v = reinterpret_cast<const uint2*>(smem + OFF_IDX)[p];
        const uint32_t o0 = v.x * 32 + ((v.x >> 2) & 1) * 16, o1 = v.y * 32 + ((v.y >> 2) & 1) * 16;
        reinterpret_cast<uint32_t*>(smem + OFF_XOFF)[p] = o0 | (o1 << 16);
      }
    }
    TL(1);
    asm volatile("cp.async.wait_group 1;" ::: "memory");
    mbar_arrive(BAR(BAR_X0));
    mbar_wait(BAR(BAR_X0), 0);
    TL(3);
    float acc[56];
    {
      const uint32_t xo = sb + OFF_XOFF + (wg * 64 + w4 * 16 + (lane & 15)) * 52;
      const uint32_t tb = sb + OFF_TAB, hx = (lane >> 4) << 4;
      const uint64_t db0 = P.dmn;
      uint32_t A[3][2][4];
#pragma unroll
      for (int pr = 0; pr < 2; pr++) {
        const uint32_t oa = lds_u32(xo + 4 * pr);
        ldsm_x4(tb + ((oa & 0xffff) ^ hx), A[pr][0]); ldsm_x4(tb + ((oa >> 16) ^ hx), A[pr][1]);
      }
#pragma unroll
      for (int pr = 0; pr < 13; pr++) {
        const int st = pr >> 1;
        uint32_t oa = 0;
        if (pr + 2 < 13) oa = lds_u32(xo + 4 * (pr + 2));
        if (!(pr & 1)) { mbar_wait(BAR(BAR_W1FULL + st), 0); if (st & 1) fence_proxy_async(); }
        if (pr == 0) TL(28); if (pr == 6) TL(29);
        const uint64_t db = db0 + (uint64_t)((w1_off(st) + (pr & 1) * 4096) >> 4);
        wg_fence();
        wgmma_rs_n112_tb(acc, A[pr % 3][0][0], A[pr % 3][0][1], A[pr % 3][0][2], A[pr % 3][0][3], db, pr > 0);
        wgmma_rs_n112_tb(acc, A[pr % 3][1][0], A[pr % 3][1][1], A[pr % 3][1][2], A[pr % 3][1][3], db + (2048 >> 4), 1);
        wg_commit();
        wg_wait<1>();
        if (pr == 4 && (tid & 127) == 0) mbar_arrive(BAR(BAR_W1FREE));
        if (pr + 2 < 13) { ldsm_x4(tb + ((oa & 0xffff) ^ hx), A[(pr + 2) % 3][0]); ldsm_x4(tb + ((oa >> 16) ^ hx), A[(pr + 2) % 3][1]); }
      }
      wg_wait<0>();
      reg_fence(acc);
      if ((tid & 127) == 0) mbar_arrive(BAR(BAR_W1DONE));
    }
    TL(4);
    float dot[4];
    {
      mbar_wait(BAR(BAR_TABS), 0);
      uint32_t bb[16];
      const uint4* bp = reinterpret_cast<const uint4*>(smem + OFF_BW + q * 64);
#pragma unroll
      for (int i = 0; i < 4; i++) { const uint4 v = bp[i]; bb[4 * i] = v.x; bb[4 * i + 1] = v.y; bb[4 * i + 2] = v.z; bb[4 * i + 3] = v.w; }
      uint32_t H[14][2];
#pragma unroll
      for (int c = 0; c < 14; c++) {
        H[c][0] = gelu2_pair(acc[4 * c], acc[4 * c + 1], bb[c]);
        H[c][1] = gelu2_pair(acc[4 * c + 2], acc[4 * c + 3], bb[c]);
      }
      wg_fence();
#pragma unroll
      for (int j = 0; j < 7; j++)
        wgmma_rs_n8(dot, H[2 * j][0], H[2 * j][1], H[2 * j + 1][0], H[2 * j + 1][1], dk + (uint64_t)((OFF_W2 + j * 256) >> 4), j > 0);
      wg_commit();
      wg_wait<0>();
      reg_fence(dot);
    }
    __syncwarp();
    mbar_wait(BAR(BAR_EPOCH), 0);
    if (q == 0) {
      const unsigned epoch = lds_u32(sb + OFF_EPOCH);
#pragma unroll
      for (int r = 0; r < 2; r++) {
        const int row = wg * 64 + w4 * 16 + g + 8 * r;
        const unsigned long long pk = ((unsigned long long)epoch << 32) | (unsigned long long)__float_as_uint(dot[2 * r]);
        asm volatile("st.relaxed.gpu.global.u64 [%0], %1;" ::"l"(P.part + cta * 128 + row), "l"(pk) : "memory");
      }
    }
    __syncwarp();
  } else {
    const int t = tid - 256;
    const bool is_arr = (t == 192);
    unsigned ctr0 = 0;
    if (is_arr) asm volatile("ld.relaxed.gpu.global.u32 %0, [%1];" : "=r"(ctr0) : "l"(P.ctr) : "memory");
    {
      const int kind = role.x >> 24, w = warp - 8, rgrp = (role.y >> 24) & 15, rj = role.y >> 28;
      const unsigned char* wsb = reinterpret_cast<const unsigned char*>(P.ws);
      if (kind < 5 && elect_one()) {
        const uint32_t bytes = role.y & 0xffff;
        const uint32_t o = w * 8192;
        if (w == 0) mbar_expect_tx(BAR(BAR_Q), bytes);
        if (o < bytes) bulk_g2s(sb + OFF_G0 + o, wsb + (role.x & 0xffffff) + o, min(bytes - o, 8192u), BAR(BAR_Q));
      }
      TL(40);
      __syncwarp();
      const StaticTabs* T = reinterpret_cast<const StaticTabs*>(smem + OFF_STAB);
      uint32_t* img32 = reinterpret_cast<uint32_t*>(P.img);
      const unsigned char* raw = smem + OFF_G0 + ((role.y >> 16) & 127);
      uint32_t chk = 0;
      if (kind < 3) chk = layer_row(kind, rgrp, rj * SETUP_WARPS + w, lane, raw, T, BAR(BAR_Q), BAR(BAR_STAB), P.wout, img32);
      else if (kind == 3) chk = x1_row(rgrp, rj * SETUP_WARPS + w, lane, raw, T, BAR(BAR_Q), BAR(BAR_STAB), img32);
      if (__any_sync(0xffffffffu, chk != 0)) __trap();
      if (lane == 0) mbar_arrive(BAR(BAR_SETUP));
    }
    TL(1);
    if (is_arr) {
      asm volatile("" : "+r"(ctr0));
      *reinterpret_cast<volatile unsigned*>(smem + OFF_EPOCH) = (ctr0 >> 8) + 1;
      mbar_wait(BAR(BAR_SETUP), 0);
      TLA(30);
      asm volatile("red.relaxed.gpu.global.add.u32 [%0], 1;" ::"l"(P.ctr) : "memory");
      mbar_arrive(BAR(BAR_EPOCH));
      TLA(31);
    }
    __syncwarp();
    {
      const int c0 = (nq >> 1) * 208 + (nq & 1) * 96, nw = (nq & 1) ? 112 : 96;
      if (t < 56) {
        const int n = 2 * t;
        const uint32_t v = (n < nw) ? __ldg(reinterpret_cast<const uint32_t*>(P.b1 + c0 + n)) : 0u;
        reinterpret_cast<uint32_t*>(smem + OFF_BW)[(t & 3) * 16 + (t >> 2)] = v;
      }
      if (t >= 64 && t < 64 + 112) {
        const int k = t - 64;
        const float w = (k < nw) ? 0.5f * bf2f(__ldg(P.w2 + c0 + k)) : 0.f;
        unsigned char* base = smem + OFF_W2 + (k >> 4) * 256 + ((k >> 3) & 1) * 128;
        *reinterpret_cast<bf16*>(base + (k & 7) * 2) = __float2bfloat16(w);
        if ((k & 7) == 0) {
#pragma unroll
          for (int r = 1; r < 8; r++) *reinterpret_cast<uint4*>(base + r * 16) = make_uint4(0, 0, 0, 0);
        }
      }
      fence_proxy_async();
    }
    if (t >= 128 && t < 192) {
      int u = t - 128, l = u >> 5, qq = (u >> 3) & 3, a = u & 7;
      float wtv = 0.f;
      if (a < 6) wtv = bf2f(__ldg(P.wout + l * NF + 8 * (a >> 1) + 2 * qq + (a & 1)));
      else if (a == 6 && !(qq & 1)) wtv = bf2f(__ldg(P.wout + l * NF + 24 + (qq >> 1)));
      reinterpret_cast<float*>(smem + OFF_WTAB)[u] = wtv;
    }
    mbar_arrive(BAR(BAR_TABS));
    TL(2);
    mbar_wait(BAR(BAR_X0), 0);
    mbar_wait(BAR(BAR_TABS), 0);
  }

  TL(5);
  const uint32_t selU = (q == 0) ? 0x1010u : (q == 1) ? 0x3232u : (q == 2) ? 0x3210u : 0x7654u;
  const uint32_t selV = (q < 2) ? 0x3210u : 0x7654u;
  uint32_t bo_raw = __ldg(reinterpret_cast<const unsigned short*>(P.bout));
  mbar_wait(BAR(BAR_EPOCH), 0);
  mbar_wait(BAR(BAR_STAB), 0);
  const unsigned epoch = lds_u32(sb + OFF_EPOCH);

  uint32_t X[2][13];
  auto load_x = [&](int sl) {
    const uint4 o = *reinterpret_cast<const uint4*>(smem + OFF_LOFF + lane * 16);
    const uint32_t xo = sb + OFF_XOFF + sl * 52;
    const uint32_t tb = sb + OFF_TAB, hx = ((lane >> 3) & 1) << 4;
    const uint32_t a0 = lds_u16(xo + (o.x & 0xffff)), a1 = lds_u16(xo + (o.x >> 16));
    const uint32_t a2 = lds_u16(xo + (o.y & 0xffff)), a3 = lds_u16(xo + (o.y >> 16));
    const uint32_t a4 = lds_u16(xo + (o.z & 0xffff)), a5 = lds_u16(xo + (o.z >> 16));
    const uint32_t a6 = lds_u16(xo + (o.w & 0xffff));
    ldsm_x4_t(tb + (a0 ^ hx), X[0][0], X[1][0], X[0][1], X[1][1]);
    ldsm_x4_t(tb + (a1 ^ hx), X[0][2], X[1][2], X[0][3], X[1][3]);
    ldsm_x4_t(tb + (a2 ^ hx), X[0][4], X[1][4], X[0][5], X[1][5]);
    ldsm_x4_t(tb + (a3 ^ hx), X[0][6], X[1][6], X[0][7], X[1][7]);
    ldsm_x4_t(tb + (a4 ^ hx), X[0][8], X[1][8], X[0][9], X[1][9]);
    ldsm_x4_t(tb + (a5 ^ hx), X[0][10], X[1][10], X[0][11], X[1][11]);
    ldsm_x2_t(tb + (a6 ^ hx), X[0][12], X[1][12]);
  };
  load_x(nq * 32 + wg * 4 + w4);
#pragma unroll 1
  for (int it = 0; it < 2; it++) {
    const int sl = nq * 32 + (wg + 4 * it) * 4 + w4;
    float S = 0.f;
    uint32_t vx[2][4], vg[2][4];
    {
      float a0[28];
      mbar_wait(BAR(BAR_IMG + 0), 0);
      if (it < 2) TL(6 + it * 8);
      g0_rec<0>(a0, X, selU, selV, dk, BAR(BAR_G0B));
      wg_wait<0>();
      reg_fence(a0);
      const float4* wt = reinterpret_cast<const float4*>(smem + OFF_WTAB) + q * 2;
      float4 wa = wt[0], wb = wt[1];
#pragma unroll
      for (int r = 0; r < 2; r++) {
        S = fmaf(wa.x, a0[0 + 2 * r], S); S = fmaf(wa.y, a0[1 + 2 * r], S);
        S = fmaf(wa.z, a0[4 + 2 * r], S); S = fmaf(wa.w, a0[5 + 2 * r], S);
        S = fmaf(wb.x, a0[8 + 2 * r], S); S = fmaf(wb.y, a0[9 + 2 * r], S);
        S = fmaf(wb.z, a0[24 + 2 * r], S);
#pragma unroll
        for (int c = 0; c < 3; c++) {
          vx[r][c] = pack_bf16(a0[4 * c + 2 * r], a0[4 * c + 2 * r + 1]);
          vg[r][c] = pack_bf16(a0[12 + 4 * c + 2 * r], a0[12 + 4 * c + 2 * r + 1]);
        }
        vx[r][3] = pack_bf16(a0[24 + 2 * r], 0.f);
        vg[r][3] = pack_bf16(a0[24 + 2 * r + 1], 0.f);
      }
    }
    float g3[16], xa[16];
    if (it < 2) TL(7 + it * 8);
    mbar_wait(BAR(BAR_IMG + 2), 0);
    mbar_wait(BAR(BAR_IMG + 1), 0);
    mbar_wait(BAR(BAR_IMG + 3), 0);
    if (it < 2) TL(8 + it * 8);
    layer_rec<0, OFF_LB>(xa, vx, X, dk);
    if (it < 2) TL(9 + it * 8);
    wg_wait<1>();
    layer_first<OFF_LA, 3>(g3, vg, X, dk);
    wg_wait<1>();
    reg_fence(xa);
    {
      const float4* wt = reinterpret_cast<const float4*>(smem + OFF_WTAB) + 8 + q * 2;
      float4 wa = wt[0], wb = wt[1];
#pragma unroll
      for (int r = 0; r < 2; r++) {
        S = fmaf(wa.x, xa[0 + 2 * r], S); S = fmaf(wa.y, xa[1 + 2 * r], S);
        S = fmaf(wa.z, xa[4 + 2 * r], S); S = fmaf(wa.w, xa[5 + 2 * r], S);
        S = fmaf(wb.x, xa[8 + 2 * r], S); S = fmaf(wb.y, xa[9 + 2 * r], S);
        S = fmaf(wb.z, xa[12 + 2 * r], S);
#pragma unroll
        for (int c = 0; c < 3; c++) vx[r][c] = pack_bf16(xa[4 * c + 2 * r], xa[4 * c + 2 * r + 1]);
        vx[r][3] = pack_bf16(xa[12 + 2 * r], 0.f);
      }
    }
    layer_rec<3, OFF_LA>(g3, vg, X, dk);
    if (it < 2) TL(10 + it * 8);
    wg_wait<1>();
    const unsigned long long* pp = P.part + (grp * 4 + (lane & 3)) * 128 + sl;
    unsigned long long pk;
    asm volatile("ld.relaxed.gpu.global.u64 %0, [%1];" : "=l"(pk) : "l"(pp) : "memory");
    float xc[16];
    layer_rec<0, OFF_LC>(xc, vx, X, dk);
    if (it == 0) load_x(sl + 16);
    wg_wait<0>();
    reg_fence(xc);
    reg_fence(g3);
    {
      float Se = 0.f;
#pragma unroll
      for (int r = 0; r < 2; r++) {
#pragma unroll
        for (int c = 0; c < 3; c++) {
          S = fmaf(g3[4 * c + 2 * r], xc[4 * c + 2 * r], S);
          S = fmaf(g3[4 * c + 2 * r + 1], xc[4 * c + 2 * r + 1], S);
        }
        Se = fmaf(g3[12 + 2 * r], xc[12 + 2 * r], Se);
      }
      if (!(q & 1)) S += Se;
    }
#pragma unroll
    for (int o = 16; o > 0; o >>= 1) S += __shfl_xor_sync(0xffffffffu, S, o);
    if (it < 2) TL(12 + it * 8);
    {
      uint32_t spin = 0;
      while (lane < 4 && (unsigned)(pk >> 32) != epoch) {
        asm volatile("ld.relaxed.gpu.global.u64 %0, [%1];" : "=l"(pk) : "l"(pp) : "memory");
        if (++spin > (1u << 24)) __trap();
      }
      __syncwarp();
      float dv = __uint_as_float((unsigned)pk);
      float d01 = dv + __shfl_xor_sync(0xffffffffu, dv, 1);
      float dsum = d01 + __shfl_xor_sync(0xffffffffu, d01, 2);
      asm volatile("" : "+r"(bo_raw));
      if (lane == 0) P.out[grp * 128 + sl] = __float2bfloat16(S + dsum + __uint_as_float(bo_raw << 16));
    }
    __syncwarp();
    if (it < 2) TL(13 + it * 8);
  }
  TL_DUMP();
}

__global__ void __launch_bounds__(128) fallback_kernel(const int* __restrict__ idx, const bf16* __restrict__ table, const bf16* __restrict__ ws,
                                                       const bf16* __restrict__ wout, const bf16* __restrict__ w1, const bf16* __restrict__ b1,
                                                       const bf16* __restrict__ w2, const bf16* __restrict__ bout, bf16* __restrict__ out) {
  __shared__ float x0[416], xa[416], xb[416], red[128];
  const int b = blockIdx.x, t = threadIdx.x;
  for (int i = t; i < 416; i += 128) { x0[i] = bf2f(table[idx[b * NF + i / 16] * 16 + (i & 15)]); xa[i] = x0[i]; }
  __syncthreads();
  float acc = 0.f;
  float* cur = xa;
  float* nxt = xb;
  for (int l = 0; l < 6; l++) {
    for (int o = t; o < 416; o += 128) {
      const int h = o >> 4, d = o & 15;
      const bf16* w = ws + (l * NF + h) * NF * NF;
      float s = 0.f;
      for (int i = 0; i < NF; i++) {
        float u = 0.f;
        for (int j = 0; j < NF; j++) u = fmaf(bf2f(w[i * NF + j]), x0[j * 16 + d], u);
        s = fmaf(u, cur[i * 16 + d], s);
      }
      nxt[o] = s;
      acc = fmaf(s, bf2f(wout[l * NF + h]), acc);
    }
    __syncthreads();
    float* tmp = cur; cur = nxt; nxt = tmp;
  }
  for (int n = t; n < 416; n += 128) {
    float h = 0.f;
    for (int k = 0; k < 416; k++) h = fmaf(x0[k], bf2f(w1[k * 416 + n]), h);
    h += bf2f(b1[n]);
    const float gl = 0.5f * h * (1.f + tanhf(0.7978845608028654f * (h + 0.044715f * h * h * h)));
    acc = fmaf(gl, bf2f(w2[n]), acc);
  }
  red[t] = acc;
  __syncthreads();
  for (int o = 64; o > 0; o >>= 1) { if (t < o) red[t] += red[t + o]; __syncthreads(); }
  if (t == 0) out[b] = __float2bfloat16(red[0] + bf2f(bout[0]));
}

typedef CUresult (*EncodeFn)(CUtensorMap*, CUtensorMapDataType, cuuint32_t, void*, const cuuint64_t*, const cuuint64_t*,
                             const cuuint32_t*, const cuuint32_t*, CUtensorMapInterleave, CUtensorMapSwizzle,
                             CUtensorMapL2promotion, CUtensorMapFloatOOBfill);

extern "C" void kernel_launch(void* const* d_in, const int* in_sizes, int n_in, void* d_out, int out_size) {
  const int* idx = (const int*)d_in[0];
  const bf16* table = (const bf16*)d_in[1];
  const bf16* ws = (const bf16*)d_in[2];
  const bf16* wout = (const bf16*)d_in[3];
  const bf16* w1 = (const bf16*)d_in[4];
  const bf16* b1 = (const bf16*)d_in[5];
  const bf16* w2 = (const bf16*)d_in[6];
  const bf16* bo = (const bf16*)d_in[7];
  bf16* out = (bf16*)d_out;

  static EncodeFn enc = nullptr;
  static Params P;
  static int n_sm = 0;
  if (!n_sm) {
    int dev = 0;
    cudaGetDevice(&dev);
    cudaDeviceGetAttribute(&n_sm, cudaDevAttrMultiProcessorCount, dev);
  }
  if (n_sm < NCTA + NHELP) {
    fallback_kernel<<<4096, 128, 0, cudaStreamPerThread>>>(idx, table, ws, wout, w1, b1, w2, bo, out);
    return;
  }
  if (!enc) {
    void* fn = nullptr;
    cudaDriverEntryPointQueryResult qr;
    cudaGetDriverEntryPoint("cuTensorMapEncodeTiled", &fn, cudaEnableDefault, &qr);
    enc = (EncodeFn)fn;
    cudaFuncSetAttribute(main_kernel, cudaFuncAttributeMaxDynamicSharedMemorySize, LAUNCH_SMEM);
    void* p;
    cudaGetSymbolAddress(&p, g_img); P.img = (unsigned char*)p;
    cudaGetSymbolAddress(&p, g_part); P.part = (unsigned long long*)p;
    cudaGetSymbolAddress(&p, g_ctr); P.ctr = (unsigned*)p;
    cudaGetSymbolAddress(&p, g_tabs); P.tabs = p;
    P.dk = make_desc(0, 128, 256, 0);
    P.dmn = make_desc(0, 8192, 1024, 1);
    for (int c = 0; c < NCTA; c++) P.role[c] = make_role(c);
  }
  P.idx = idx; P.table = table; P.ws = ws; P.wout = wout; P.w1 = w1; P.b1 = b1; P.w2 = w2; P.bout = bo; P.out = out;
  TmaMaps tms;
  for (int h = 0; h < 4; h++) {
    const int c0 = (h >> 1) * 208 + (h & 1) * 96, nw = (h & 1) ? 112 : 96;
    cuuint64_t dims[2] = {(cuuint64_t)nw, 416};
    cuuint64_t strides[1] = {832};
    cuuint32_t box[2] = {64, 64};
    cuuint32_t es[2] = {1, 1};
    enc(&tms.m[h], CU_TENSOR_MAP_DATA_TYPE_BFLOAT16, 2, (void*)(w1 + c0), dims, strides, box, es,
        CU_TENSOR_MAP_INTERLEAVE_NONE, CU_TENSOR_MAP_SWIZZLE_128B, CU_TENSOR_MAP_L2_PROMOTION_L2_128B,
        CU_TENSOR_MAP_FLOAT_OOB_FILL_NONE);
  }
  main_kernel<<<NCTA + NHELP, 512, LAUNCH_SMEM, cudaStreamPerThread>>>(P, tms);
}
```

```cpp
#include <cuda_runtime.h>
#include <cuda_bf16.h>
#include <cuda.h>
#include <stdint.h>

typedef __nv_bfloat16 bf16;

constexpr int NF = 26;
constexpr int NCTA = 128;

constexpr int G0_KS = 24, G0_N = 56, G0_SLAB = G0_N * 32;
constexpr int L_KS = 43, L_SLAB = 1024;
constexpr int G0_BYTES = G0_KS * G0_SLAB;
constexpr int L_BYTES = L_KS * L_SLAB;
constexpr int IMG_BYTES = G0_BYTES + 3 * L_BYTES;

constexpr int W1_STAGES = 7;
constexpr int W1_STAGE_BYTES = 16384;
constexpr int OFF_LB = 0;
constexpr int OFF_LA = 44032;
constexpr int OFF_LC = 88064;
__host__ __device__ constexpr int w1_off(int st) { return st < 2 ? st * W1_STAGE_BYTES : OFF_LA + (st - 2) * W1_STAGE_BYTES; }
constexpr int OFF_G0 = 132096;
constexpr int OFF_IDX = 132096 + 16384;
constexpr int OFF_TAB = OFF_G0 + G0_BYTES;
constexpr int OFF_XOFF = OFF_TAB + 32000;
constexpr int OFF_BAR = OFF_XOFF + 6656;
constexpr int OFF_BW = OFF_BAR + 256;
constexpr int OFF_W2 = OFF_BW + 256;
constexpr int OFF_WTAB = OFF_W2 + 1792;
constexpr int OFF_EPOCH = OFF_WTAB + 256;
constexpr int OFF_STAB = (OFF_EPOCH + 16 + 127) / 128 * 128;
constexpr int OFF_LOFF = OFF_STAB + 3072 + 704;
constexpr int SMEM_BYTES = OFF_STAB + 4288;
static_assert(SMEM_BYTES <= 229376, "smem");
constexpr int LAUNCH_SMEM = SMEM_BYTES;

constexpr int BAR_W1FULL = 0  , BAR_W1FREE = 10  , BAR_W1DONE = 11  ,
              BAR_IMG = 14  , BAR_X0 = 18, BAR_SETUP = 19, BAR_EPOCH = 20, BAR_TABS = 21,
              BAR_Q = 22, BAR_STAB = 23, BAR_G0B = 24  , NBAR = 26;

struct TmaMaps { CUtensorMap m[4]; };
struct Params {
  const int* idx; const bf16* table; const bf16* ws; const bf16* wout; const bf16* b1; const bf16* w2; const bf16* bout;
  bf16* out;
  unsigned char* img; unsigned long long* part; unsigned* ctr; const void* tabs;
  uint64_t dk, dmn;
  uint2 role[NCTA];
};

__device__ __align__(1024) unsigned char g_img[IMG_BYTES];
__device__ unsigned long long g_part[NCTA * 128];
__device__ unsigned g_ctr;

#define GT(i) do {} while (0)
#define TL(i) do {} while (0)
#define TLP(i) do {} while (0)
#define TLA(i) do {} while (0)
#define TLW(w, i) do {} while (0)
#define TL_INIT() do {} while (0)
#define TL_START() 0
#define TL_PUT0(c) do {} while (0)
#define TL_DUMP() do {} while (0)
__device__ __forceinline__ uint32_t smem_u32(const void* p) { return (uint32_t)__cvta_generic_to_shared(p); }
__device__ __forceinline__ bool elect_one() {
  uint32_t pred;
  asm volatile("{\n.reg .pred p;\nelect.sync _|p, 0xffffffff;\nselp.u32 %0, 1, 0, p;\n}\n" : "=r"(pred));
  return pred != 0;
}
__device__ __forceinline__ void mbar_init(uint32_t bar, uint32_t cnt) {
  asm volatile("mbarrier.init.shared::cta.b64 [%0], %1;" ::"r"(bar), "r"(cnt) : "memory");
}
__device__ __forceinline__ void mbar_expect_tx(uint32_t bar, uint32_t bytes) {
  asm volatile("mbarrier.arrive.expect_tx.shared::cta.b64 _, [%0], %1;" ::"r"(bar), "r"(bytes) : "memory");
}
__device__ __forceinline__ void mbar_arrive(uint32_t bar) {
  asm volatile("mbarrier.arrive.shared::cta.b64 _, [%0];" ::"r"(bar) : "memory");
}
__device__ __forceinline__ bool mbar_try(uint32_t bar, uint32_t parity) {
  uint32_t ok;
  asm volatile("{\n.reg .pred p;\nmbarrier.try_wait.parity.shared::cta.b64 p, [%1], %2;\nselp.u32 %0, 1, 0, p;\n}\n"
               : "=r"(ok) : "r"(bar), "r"(parity) : "memory");
  return ok != 0;
}
__device__ __forceinline__ void mbar_wait(uint32_t bar, uint32_t parity) {
#pragma unroll 1
  for (uint32_t it = 0; it < (1u << 26); it++)
    if (mbar_try(bar, parity)) return;
  __trap();
}
__device__ __forceinline__ void bulk_g2s(uint32_t dst, const void* src, uint32_t bytes, uint32_t bar) {
  asm volatile("cp.async.bulk.shared::cluster.global.mbarrier::complete_tx::bytes [%0], [%1], %2, [%3];"
               ::"r"(dst), "l"(src), "r"(bytes), "r"(bar) : "memory");
}
__device__ __forceinline__ void tma_2d(uint32_t dst, const CUtensorMap* tm, int x, int y, uint32_t bar) {
  asm volatile("cp.async.bulk.tensor.2d.shared::cluster.global.mbarrier::complete_tx::bytes [%0], [%1, {%3, %4}], [%2];"
               ::"r"(dst), "l"(tm), "r"(bar), "r"(x), "r"(y) : "memory");
}
__device__ __forceinline__ void cp_async16(uint32_t dst, const void* src) {
  asm volatile("cp.async.cg.shared.global [%0], [%1], 16;" ::"r"(dst), "l"(src) : "memory");
}
__device__ __forceinline__ void fence_proxy_async() { asm volatile("fence.proxy.async.shared::cta;" ::: "memory"); }
__device__ __forceinline__ void fence_proxy_async_all() { asm volatile("fence.proxy.async;" ::: "memory"); }
template <int ID, int N> __device__ __forceinline__ void named_bar_t() { asm volatile("bar.sync %0, %1;" ::"n"(ID), "n"(N) : "memory"); }
#define named_bar(id, n) named_bar_t<id, n>()

__device__ __forceinline__ void wg_fence() { asm volatile("wgmma.fence.sync.aligned;" ::: "memory"); }
__device__ __forceinline__ void wg_commit() { asm volatile("wgmma.commit_group.sync.aligned;" ::: "memory"); }
template <int N> __device__ __forceinline__ void wg_wait() { asm volatile("wgmma.wait_group.sync.aligned %0;" ::"n"(N) : "memory"); }
template <int N> __device__ __forceinline__ void reg_fence(float (&d)[N]) {
#pragma unroll
  for (int i = 0; i < N; i++) asm volatile("" : "+f"(d[i])::"memory");
}
constexpr uint32_t SMEM_BASE = 1024;
__host__ __device__ constexpr uint64_t make_desc(uint32_t off, uint32_t lbo, uint32_t sbo, uint32_t swz) {
  return (uint64_t)(((SMEM_BASE + off) & 0x3FFFF) >> 4) | ((uint64_t)(lbo >> 4) << 16) | ((uint64_t)(sbo >> 4) << 32) | ((uint64_t)swz << 62);
}

#define ACC4(d, o) "+f"(d[o]), "+f"(d[o + 1]), "+f"(d[o + 2]), "+f"(d[o + 3])
#define ACC8(d, o) ACC4(d, o), ACC4(d, o + 4)

__device__ __forceinline__ void wgmma_rs_n32(float (&d)[16], uint32_t a0, uint32_t a1, uint32_t a2, uint32_t a3, uint64_t db, int sc) {
  asm volatile("{\n.reg .pred p;\nsetp.ne.b32 p, %21, 0;\n"
               "wgmma.mma_async.sync.aligned.m64n32k16.f32.bf16.bf16 "
               "{%0,%1,%2,%3,%4,%5,%6,%7,%8,%9,%10,%11,%12,%13,%14,%15}, {%16,%17,%18,%19}, %20, p, 1, 1, 0;\n}\n"
               : ACC8(d, 0), ACC8(d, 8)
               : "r"(a0), "r"(a1), "r"(a2), "r"(a3), "l"(db), "r"(sc));
}
__device__ __forceinline__ void wgmma_rs_n56(float (&d)[28], uint32_t a0, uint32_t a1, uint32_t a2, uint32_t a3, uint64_t db, int sc) {
  asm volatile("{\n.reg .pred p;\nsetp.ne.b32 p, %33, 0;\n"
               "wgmma.mma_async.sync.aligned.m64n56k16.f32.bf16.bf16 "
               "{%0,%1,%2,%3,%4,%5,%6,%7,%8,%9,%10,%11,%12,%13,%14,%15,%16,%17,%18,%19,%20,%21,%22,%23,%24,%25,%26,%27}, "
               "{%28,%29,%30,%31}, %32, p, 1, 1, 0;\n}\n"
               : ACC8(d, 0), ACC8(d, 8), ACC8(d, 16), ACC4(d, 24)
               : "r"(a0), "r"(a1), "r"(a2), "r"(a3), "l"(db), "r"(sc));
}
__device__ __forceinline__ void wgmma_rs_n112_tb(float (&d)[56], uint32_t a0, uint32_t a1, uint32_t a2, uint32_t a3, uint64_t db, int sc) {
  asm volatile("{\n.reg .pred p;\nsetp.ne.b32 p, %61, 0;\n"
               "wgmma.mma_async.sync.aligned.m64n112k16.f32.bf16.bf16 "
               "{%0,%1,%2,%3,%4,%5,%6,%7,%8,%9,%10,%11,%12,%13,%14,%15,%16,%17,%18,%19,%20,%21,%22,%23,%24,%25,%26,%27,%28,%29,%30,%31,%32,%33,%34,%35,%36,%37,%38,%39,%40,%41,%42,%43,%44,%45,%46,%47,%48,%49,%50,%51,%52,%53,%54,%55}, "
               "{%56,%57,%58,%59}, %60, p, 1, 1, 1;\n}\n"
               : ACC8(d, 0), ACC8(d, 8), ACC8(d, 16), ACC8(d, 24), ACC8(d, 32), ACC8(d, 40), ACC8(d, 48)
               : "r"(a0), "r"(a1), "r"(a2), "r"(a3), "l"(db), "r"(sc));
}

__device__ __forceinline__ void wgmma_rs_n8(float (&d)[4], uint32_t a0, uint32_t a1, uint32_t a2, uint32_t a3, uint64_t db, int sc) {
  asm volatile("{\n.reg .pred p;\nsetp.ne.b32 p, %9, 0;\n"
               "wgmma.mma_async.sync.aligned.m64n8k16.f32.bf16.bf16 {%0,%1,%2,%3}, {%4,%5,%6,%7}, %8, p, 1, 1, 0;\n}\n"
               : ACC4(d, 0)
               : "r"(a0), "r"(a1), "r"(a2), "r"(a3), "l"(db), "r"(sc));
}
__device__ __forceinline__ uint32_t mul_lo(uint32_t v, uint32_t r) {
  __nv_bfloat162 a = *reinterpret_cast<__nv_bfloat162*>(&v), b = *reinterpret_cast<__nv_bfloat162*>(&r);
  __nv_bfloat162 c = __hmul2(__low2bfloat162(a), b);
  return *reinterpret_cast<uint32_t*>(&c);
}
__device__ __forceinline__ uint32_t mul_hi(uint32_t v, uint32_t r) {
  __nv_bfloat162 a = *reinterpret_cast<__nv_bfloat162*>(&v), b = *reinterpret_cast<__nv_bfloat162*>(&r);
  __nv_bfloat162 c = __hmul2(__high2bfloat162(a), b);
  return *reinterpret_cast<uint32_t*>(&c);
}
__device__ __forceinline__ uint32_t mul_ew(uint32_t v, uint32_t r) {
  __nv_bfloat162 a = *reinterpret_cast<__nv_bfloat162*>(&v), b = *reinterpret_cast<__nv_bfloat162*>(&r);
  __nv_bfloat162 c = __hmul2(a, b);
  return *reinterpret_cast<uint32_t*>(&c);
}
__device__ __forceinline__ uint32_t pack_bf16(float lo, float hi) {
  uint32_t r;
  asm("cvt.rn.bf16x2.f32 %0, %1, %2;" : "=r"(r) : "f"(hi), "f"(lo));
  return r;
}
__device__ __forceinline__ float bf2f(bf16 v) { return __bfloat162float(v); }
__device__ __forceinline__ float bflo(uint32_t w) { return __uint_as_float(w << 16); }
__device__ __forceinline__ float bfhi(uint32_t w) { return __uint_as_float(w & 0xffff0000u); }

__device__ __forceinline__ void st_img(uint32_t* p, uint32_t v) {
  asm volatile("st.relaxed.gpu.global.u32 [%0], %1;" ::"l"(p), "r"(v) : "memory");
}
__device__ __forceinline__ uint32_t ld_back(const uint32_t* p) {
  uint32_t v;
  asm volatile("ld.relaxed.gpu.global.u32 %0, [%1];" : "=r"(v) : "l"(p) : "memory");
  return v;
}
__host__ __device__ constexpr int Fq(int q, int t, int e) {
  if (t == 12) return 24 + e;
  const int u = (t + 3 * q) % 12;
  const int sw = (q >= 2 && u >= 6) ? 1 : 0;
  return 2 * u + (e ^ sw);
}
constexpr int M_ONE = 26, M_NONE = 27;
struct Mono { int f1, f2; };
__host__ __device__ constexpr Mono g0_mono(int s, int q, int e) {
  if (s < 30) { const int d = s / 6 + 1, a = (s % 6) >> 1; return {Fq(q, a, s & 1), Fq(q, a + d, e)}; }
  if (s < 33) return {Fq(q, s - 30, e), Fq(q, s - 24, e)};
  if (s < 35) return {Fq(q, s - 33, e), Fq(q, s - 33, e)};
  if (s == 35) return {Fq(q, e, 0), Fq(q, e, 1)};
  if (s == 36) return {Fq(q, 2, 0), Fq(q, 2, e)};
  if (s == 37) return e ? Mono{Fq(q, 2, 1), Fq(q, 2, 1)} : Mono{M_NONE, M_NONE};
  if (s < 44) return {24 + ((s - 38) & 1), Fq(q, (s - 38) >> 1, e)};
  if (s < 47) return {Fq(q, s - 44, e), M_ONE};
  if (q == 0) return {24, 24 + e};
  if (q == 1) return e ? Mono{25, 25} : Mono{M_NONE, M_NONE};
  if (q == 2) return {24 + e, M_ONE};
  return e ? Mono{M_NONE, M_NONE} : Mono{M_ONE, M_ONE};
}
constexpr int QM_RS = 40;
constexpr int O_ZERO = 31 * QM_RS + 39, O_CONST = 30 * QM_RS + 39;
struct StaticTabs {
  uint32_t otab[48 * 8];
  uint32_t x1tab[48 * 8];
  uint16_t ltab[88 * 4];
  uint16_t loff[32 * 8];
};
constexpr StaticTabs make_tabs() {
  StaticTabs T{};
  for (int s = 0; s < 48; s++)
    for (int q = 0; q < 4; q++)
      for (int e = 0; e < 2; e++) {
        const Mono m = g0_mono(s, q, e);
        const bool none = m.f1 == M_NONE, cs = m.f1 == M_ONE, lin = m.f2 == M_ONE;
        const uint32_t o1 = none ? O_ZERO : cs ? O_CONST : m.f1 * QM_RS + (lin ? 26 : m.f2);
        const uint32_t dg = (!none && !cs && !lin && m.f1 == m.f2) ? 1u : 0u;
        T.otab[s * 8 + q * 2 + e] = o1 | (dg << 16);
        const bool qd = m.f1 < NF && m.f2 < NF;
        const uint32_t y1 = qd ? m.f1 * NF + m.f2 : 0xffffu;
        const uint32_t y2 = (qd && m.f1 != m.f2) ? m.f2 * NF + m.f1 : 0xffffu;
        T.x1tab[s * 8 + q * 2 + e] = y1 | (y2 << 16);
      }
  for (int s = 0; s < 88; s++)
    for (int q = 0; q < 4; q++) {
      uint16_t v = 0;
      if (s < 85) {
        const bool ex = s >= 78;
        const int a = s / 13, k = s - 78;
        const int tt = ex ? ((k < 3) ? k : (k < 6 ? k + 3 : 12)) : s % 13;
        const int in = ex ? 24 + (q >> 1) : 8 * (a >> 1) + 2 * q + (a & 1);
        const bool valid = !(ex && tt == 12 && (q & 1));
        const int f0 = Fq(q, tt, 0);
        v = (uint16_t)((f0 >> 1) | ((f0 & 1) << 4) | ((valid ? 1 : 0) << 5) | (in << 6));
      }
      T.ltab[s * 4 + q] = v;
    }
  for (int ln = 0; ln < 32; ln++)
    for (int k = 0; k < 8; k++) {
      const int m = ln >> 3, r = ln & 7;
      const int tt = (k < 6) ? 2 * k + (m >> 1) : 12;
      T.loff[ln * 8 + k] = (uint16_t)(2 * Fq(r >> 1, tt, r & 1));
    }
  return T;
}
static_assert(sizeof(StaticTabs) == 4288, "tabs");
__device__ __align__(128) const StaticTabs g_tabs = make_tabs();

constexpr int SETUP_WARPS = 7;
constexpr int WL_BYTES = NF * NF * NF * 2;
static inline uint2 make_role(int cta) {
  int kind = 5, grp = 0, j = 0, off = 0, bytes = 0;
  const int c = cta, SL = NF * NF * 2;
  if (c < 56) { kind = 1 + c / 28; grp = (c % 28) / 7; j = c % 7; off = kind * WL_BYTES + grp * 8 * SL; bytes = (grp < 3 ? 8 : 2) * SL; }
  else if (c < 80) { kind = 0; grp = (c - 56) / 8; j = (c - 56) % 8; off = 3 * WL_BYTES + grp * 8 * SL; bytes = 8 * SL; }
  else if (c < 83) { kind = 0; grp = 3; j = c - 80; off = 3 * WL_BYTES + 24 * SL; bytes = 2 * SL; }
  else if (c < 95) { kind = 3; grp = (c - 83) / 4; j = (c - 83) % 4; off = grp * 8 * SL; bytes = 8 * SL; }
  const int delta = off & 127;
  uint2 r;
  r.x = (uint32_t)(off - delta) | ((uint32_t)kind << 24);
  r.y = (uint32_t)(bytes + delta) | ((uint32_t)delta << 16) | ((uint32_t)grp << 24) | ((uint32_t)j << 28);
  return r;
}

__device__ __forceinline__ uint32_t layer_row(int li, int grp, int r, int lane, const unsigned char* raw, const StaticTabs* T,
                                              uint32_t bar, uint32_t tbar, const bf16* __restrict__ wout, uint32_t* img32) {
  const int ks = li ? r : 13 * grp + (r >> 2), ng = li ? grp : (r & 3);
  if (ks >= 43 || (!li && grp < 3 && r >= 52)) return 0;
  const uint32_t* w32 = reinterpret_cast<const uint32_t*>(raw);
  const int n8 = lane >> 2, q = lane & 3;
  const int o = (ng < 3) ? ng * 8 + n8 : 24 + (n8 >> 2);
  const bool vo = (ng < 3) || !(n8 & 1);
  const int ob = li ? (o - 8 * grp) * 338 : o * 13 - 8 * grp * 338;
  const int si = li ? 13 : 338;
  uint32_t bias = 0;
  if (vo && ks == 42 && li == 0 && q == 0) bias = (uint32_t)__ldg(reinterpret_cast<const unsigned short*>(wout) + 2 * NF + o);
  uint32_t* dst = img32 + G0_BYTES / 4 + li * (L_BYTES / 4) + (ks * 4 + ng) * 64 + lane;
  mbar_wait(tbar, 0);
  const uint32_t e0 = T->ltab[8 * ks + q], e1 = T->ltab[8 * ks + 4 + q];
  const bool v0 = vo && (e0 & 32), v1 = vo && (e1 & 32);
  const int s0 = v0 ? ob + (e0 >> 6) * si + (e0 & 15) : 0, s1 = v1 ? ob + (e1 >> 6) * si + (e1 & 15) : 0;
  TL(33);
  mbar_wait(bar, 0);
  TL(36);
  uint32_t w0 = w32[s0], w1 = w32[s1];
  w0 = (e0 & 16) ? __funnelshift_l(w0, w0, 16) : w0;
  w1 = (e1 & 16) ? __funnelshift_l(w1, w1, 16) : w1;
  w0 = v0 ? w0 : 0u;
  w1 = v1 ? w1 : bias;
  st_img(dst, w0); st_img(dst + 32, w1);
  return (ld_back(dst) ^ w0) | (ld_back(dst + 32) ^ w1);
}
__device__ __forceinline__ float x1_val(const unsigned short* wh, uint32_t e) {
  const uint32_t a = e & 0xffff, b = e >> 16;
  const uint32_t x = wh[a == 0xffff ? 0 : a], y = wh[b == 0xffff ? 0 : b];
  return (a == 0xffff ? 0.f : __uint_as_float(x << 16)) + (b == 0xffff ? 0.f : __uint_as_float(y << 16));
}
__device__ __forceinline__ uint32_t x1_row(int ng, int ks, int lane, const unsigned char* raw, const StaticTabs* T, uint32_t bar, uint32_t tbar, uint32_t* img32) {
  if (ks >= 24) return 0;
  const int n8 = lane >> 2, q = lane & 3;
  const unsigned short* wh = reinterpret_cast<const unsigned short*>(raw) + n8 * (NF * NF);
  uint32_t* dst = img32 + ks * (G0_SLAB / 4) + ng * 64 + lane;
  mbar_wait(tbar, 0);
  const uint2 ea = *reinterpret_cast<const uint2*>(&T->x1tab[16 * ks + 2 * q]), eb = *reinterpret_cast<const uint2*>(&T->x1tab[16 * ks + 8 + 2 * q]);
  mbar_wait(bar, 0);
  const uint32_t w0 = pack_bf16(x1_val(wh, ea.x), x1_val(wh, ea.y)), w1 = pack_bf16(x1_val(wh, eb.x), x1_val(wh, eb.y));
  st_img(dst, w0); st_img(dst + 32, w1);
  return (ld_back(dst) ^ w0) | (ld_back(dst + 32) ^ w1);
}

constexpr int NHELP = 4;
constexpr int H_MS = 32 * QM_RS + 4;
constexpr int H_W5 = 0, H_W4 = 35328, H_W0 = 70656, H_TAB = 73472, H_B = 77824, H_M = 82944, H_XE = H_M + 8 * H_MS * 4, H_BAR = H_XE + 1536;
struct HB { bf16 Bh[32][40]; };
__device__ __forceinline__ void mma_bf16(float (&c)[4], uint32_t a0, uint32_t a1, uint32_t a2, uint32_t a3, uint32_t b0, uint32_t b1) {
  asm volatile("mma.sync.aligned.m16n8k16.row.col.f32.bf16.bf16.f32 {%0,%1,%2,%3}, {%4,%5,%6,%7}, {%8,%9}, {%0,%1,%2,%3};"
               : "+f"(c[0]), "+f"(c[1]), "+f"(c[2]), "+f"(c[3]) : "r"(a0), "r"(a1), "r"(a2), "r"(a3), "r"(b0), "r"(b1));
}
__device__ __forceinline__ void helper_role(int hk, const Params& P, unsigned char* smem, uint32_t sb) {
  const int t = threadIdx.x, warp = __shfl_sync(0xffffffffu, t >> 5, 0), lane = t & 31;
  const uint32_t d5bar = sb + H_BAR, d4bar = sb + H_BAR + 8, tbar = sb + H_BAR + 16;
  const unsigned char* wsb = reinterpret_cast<const unsigned char*>(P.ws);
  HB* Q = reinterpret_cast<HB*>(smem + H_B);
  float* M = reinterpret_cast<float*>(smem + H_M);
  constexpr uint32_t W5B = WL_BYTES + ((5 * WL_BYTES) & 127), W4B = WL_BYTES + ((4 * WL_BYTES) & 127);
  if (warp < 3 && elect_one()) {
    mbar_init(sb + H_BAR + 8 * warp, 1);
    asm volatile("fence.mbarrier_init.release.cluster;" ::: "memory");
    if (warp == 0) {
      mbar_expect_tx(d5bar, W5B);
#pragma unroll
      for (int c = 0; c < 5; c++)
        bulk_g2s(sb + H_W5 + c * 8192, wsb + ((5 * WL_BYTES) & ~127) + c * 8192, c < 4 ? 8192u : W5B - 4 * 8192, d5bar);
    }
  }
  for (int i = t; i < 640; i += 512) reinterpret_cast<uint32_t*>(Q)[i] = 0;
  __syncthreads();
  if (warp >= 5 && warp < 12 && elect_one()) {
    if (warp < 10) {
      const int c = warp - 5;
      if (c == 0) mbar_expect_tx(d4bar, W4B + (hk == 3 ? 2768 : 0));
      bulk_g2s(sb + H_W4 + c * 8192, wsb + ((4 * WL_BYTES) & ~127) + c * 8192, c < 4 ? 8192u : W4B - 4 * 8192, d4bar);
    } else if (warp == 10) {
      mbar_expect_tx(tbar, sizeof(StaticTabs));
      bulk_g2s(sb + H_TAB, P.tabs, sizeof(StaticTabs), tbar);
    } else if (hk == 3) {
      bulk_g2s(sb + H_W0, wsb + ((24 * NF * NF * 2) & ~127), 2768, d4bar);
    }
  }
  const unsigned short* wo16 = reinterpret_cast<const unsigned short*>(P.wout);
  uint32_t c5[13];
#pragma unroll
  for (int k = 0; k < 13; k++) c5[k] = __ldg(reinterpret_cast<const uint32_t*>(P.wout + 5 * NF) + k);
  unsigned short wv = 0;
  const int io0 = (hk < 3) ? 8 * hk : 24;
  if (t >= 352 && t < 352 + NF) wv = __ldg(wo16 + 4 * NF + t - 352);
  else if (t >= 384 && t < 392 && io0 + t - 384 < NF) wv = __ldg(wo16 + 3 * NF + io0 + t - 384);
  const StaticTabs* T = reinterpret_cast<const StaticTabs*>(smem + H_TAB);
  const int n8 = lane >> 2, q = lane & 3, g = n8;
  const int fil = (hk < 3) ? n8 : (n8 >> 2);
  const bool fx1 = (hk == 3) && !(n8 & 1);
  uint32_t* dst = reinterpret_cast<uint32_t*>(P.img) + (warp >> 1) * (G0_SLAB / 4) + (warp & 1) * 32 + (3 + hk) * 64 + lane;
  if (t >= 352 && t < 352 + NF) reinterpret_cast<unsigned short*>(&Q->Bh[26][t - 352])[0] = wv;
  if (t >= 384 && t < 392) { M[(t - 384) * H_MS + O_ZERO] = 0.f; M[(t - 384) * H_MS + O_CONST] = __uint_as_float((uint32_t)wv << 16); }
  mbar_wait(d5bar, 0);
  if (t < 338) {
    const uint32_t* w5 = reinterpret_cast<const uint32_t*>(smem + H_W5 + ((5 * WL_BYTES) & 127)) + t;
    float s0 = 0.f, s1 = 0.f, s2 = 0.f, s3 = 0.f;
#pragma unroll
    for (int k = 0; k < 13; k++) {
      const uint32_t wa = w5[(2 * k) * 338], wb = w5[(2 * k + 1) * 338];
      const float ca = bflo(c5[k]), cb = bfhi(c5[k]);
      s0 = fmaf(ca, bflo(wa), s0); s1 = fmaf(ca, bfhi(wa), s1);
      s2 = fmaf(cb, bflo(wb), s2); s3 = fmaf(cb, bfhi(wb), s3);
    }
    const int h = (t * 79) >> 10, tp = t - 13 * h;
    Q->Bh[2 * tp][h] = __float2bfloat16(s0 + s2);
    Q->Bh[2 * tp + 1][h] = __float2bfloat16(s1 + s3);
  }
  mbar_wait(tbar, 0);
  uint2 fot[3];
#pragma unroll
  for (int r = 0; r < 3; r++) fot[r] = *reinterpret_cast<const uint2*>(&T->otab[(warp + 16 * r) * 8 + q * 2]);
  mbar_wait(d4bar, 0);
  const int il = warp - 8;
  const bool mma_warp = (warp >= 8) && (hk < 3 || il < 2);
  uint32_t u[4][4];
  if (mma_warp) {
    const unsigned short* A = reinterpret_cast<const unsigned short*>(smem + H_W4 + ((4 * WL_BYTES) & 127)) + (io0 + il) * NF + g;
#pragma unroll
    for (int rb = 0; rb < 4; rb++) {
#pragma unroll
      for (int kh = 0; kh < 4; kh++) {
        const int k = 8 * kh + 2 * q;
        const bool ok = (k < NF) && (8 * rb + g < NF);
        const int kc = (k < NF) ? k : 0;
        const uint32_t lo = A[kc * (NF * NF) + 8 * rb], hi = A[(kc + 1) * (NF * NF) + 8 * rb];
        u[rb][kh] = ok ? (lo | (hi << 16)) : 0u;
      }
    }
  }
  if (hk == 3) {
    const int u0 = (warp < 8) ? t : (warp >= 10 && warp < 14) ? t - 64 : -1;
    if (u0 >= 0) {
      const int sl = u0 >> 3, xl = (u0 >> 2) & 1, xq = u0 & 3;
      const uint2 xt = *reinterpret_cast<const uint2*>(&T->x1tab[sl * 8 + xq * 2]);
      const unsigned short* wh = reinterpret_cast<const unsigned short*>(smem + H_W0 + ((24 * NF * NF * 2) & 127)) + xl * (NF * NF);
      reinterpret_cast<uint32_t*>(smem + H_XE)[u0] = pack_bf16(x1_val(wh, xt.x), x1_val(wh, xt.y));
    }
  }
  __syncthreads();
  if (mma_warp) {
    uint32_t w[4][4];
#pragma unroll
    for (int rb = 0; rb < 4; rb++)
#pragma unroll
      for (int kh = 0; kh < 4; kh++) w[rb][kh] = *reinterpret_cast<const uint32_t*>(&Q->Bh[8 * rb + g][8 * kh + 2 * q]);
    float* Mi = M + il * H_MS;
    float c[2][4][4];
#pragma unroll
    for (int mt = 0; mt < 2; mt++)
#pragma unroll
      for (int nt = 0; nt < 4; nt++) { c[mt][nt][0] = c[mt][nt][1] = c[mt][nt][2] = c[mt][nt][3] = 0.f; }
#pragma unroll
    for (int kk = 0; kk < 2; kk++) {
#pragma unroll
      for (int mt = 0; mt < 2; mt++)
#pragma unroll
        for (int nt = 0; nt < 4; nt++)
          mma_bf16(c[mt][nt], u[2 * mt][2 * kk], u[2 * mt + 1][2 * kk], u[2 * mt][2 * kk + 1], u[2 * mt + 1][2 * kk + 1], w[nt][2 * kk], w[nt][2 * kk + 1]);
#pragma unroll
      for (int mt = 0; mt < 2; mt++)
#pragma unroll
        for (int nt = 0; nt < 4; nt++)
          mma_bf16(c[mt][nt], w[2 * mt][2 * kk], w[2 * mt + 1][2 * kk], w[2 * mt][2 * kk + 1], w[2 * mt + 1][2 * kk + 1], u[nt][2 * kk], u[nt][2 * kk + 1]);
    }
#pragma unroll
    for (int mt = 0; mt < 2; mt++)
#pragma unroll
      for (int nt = 0; nt < 4; nt++) {
        *reinterpret_cast<float2*>(&Mi[(mt * 16 + g) * QM_RS + nt * 8 + 2 * q]) = make_float2(c[mt][nt][0], c[mt][nt][1]);
        *reinterpret_cast<float2*>(&Mi[(mt * 16 + g + 8) * QM_RS + nt * 8 + 2 * q]) = make_float2(c[mt][nt][2], c[mt][nt][3]);
      }
  }
  __syncthreads();
  uint32_t val[3], chk = 0;
#pragma unroll
  for (int r = 0; r < 3; r++) {
    const float* Mf = M + fil * H_MS;
    float v0 = Mf[fot[r].x & 0xffff], v1 = Mf[fot[r].y & 0xffff];
    v0 = (fot[r].x >> 16) ? 0.5f * v0 : v0;
    v1 = (fot[r].y >> 16) ? 0.5f * v1 : v1;
    const uint32_t xe = reinterpret_cast<const uint32_t*>(smem + H_XE)[(warp + 16 * r) * 8 + (n8 >> 2) * 4 + q];
    val[r] = fx1 ? xe : pack_bf16(v0, v1);
    st_img(dst + r * 8 * (G0_SLAB / 4), val[r]);
  }
#pragma unroll
  for (int r = 0; r < 3; r++) chk |= ld_back(dst + r * 8 * (G0_SLAB / 4)) ^ val[r];
  if (__any_sync(0xffffffffu, chk != 0)) __trap();
  __syncthreads();
  if (t == 0) asm volatile("red.relaxed.gpu.global.add.u32 [%0], 32;" ::"l"(P.ctr) : "memory");
}

template <int S>
__device__ __forceinline__ uint32_t l_prod(const uint32_t (&vp)[4], const uint32_t (&X)[13]) {
  if constexpr (S < 78) {
    constexpr int a = S / 13, t = S % 13;
    return (a & 1) ? mul_hi(vp[a >> 1], X[t]) : mul_lo(vp[a >> 1], X[t]);
  } else if constexpr (S < 85) {
    constexpr int k = S - 78;
    constexpr int t = (k < 3) ? k : (k < 6 ? k + 3 : 12);
    return mul_lo(vp[3], X[t]);
  } else {
    return 0x00003F80u;
  }
}
template <int S>
__device__ __forceinline__ uint32_t g0_prod(const uint32_t (&X)[13], uint32_t selU, uint32_t selV) {
  if constexpr (S < 30) {
    constexpr int d = S / 6 + 1, a = (S % 6) >> 1;
    return (S & 1) ? mul_hi(X[a], X[a + d]) : mul_lo(X[a], X[a + d]);
  } else if constexpr (S < 33) {
    return mul_ew(X[S - 30], X[S - 24]);
  } else if constexpr (S < 35) {
    return mul_ew(X[S - 33], X[S - 33]);
  } else if constexpr (S == 35) {
    return mul_ew(__byte_perm(X[0], X[1], 0x5410), __byte_perm(X[0], X[1], 0x7632));
  } else if constexpr (S == 36) {
    return mul_lo(X[2], X[2]);
  } else if constexpr (S == 37) {
    return mul_hi(X[2], X[2]);
  } else if constexpr (S < 44) {
    constexpr int a = (S - 38) >> 1;
    return ((S - 38) & 1) ? mul_hi(X[12], X[a]) : mul_lo(X[12], X[a]);
  } else if constexpr (S < 47) {
    return X[S - 44];
  } else {
    return mul_ew(__byte_perm(X[12], 0x3F803F80u, selU), __byte_perm(X[12], 0x3F803F80u, selV));
  }
}

constexpr int NBK = 4;

template <int KS, int KE>
__device__ __forceinline__ void l_fill(uint32_t (*A)[4], const uint32_t (&vp)[2][4], const uint32_t (&X)[2][13]) {
  A[0][0] = l_prod<2 * KS>(vp[0], X[0]);
  A[0][1] = l_prod<2 * KS>(vp[1], X[1]);
  A[0][2] = l_prod<2 * KS + 1>(vp[0], X[0]);
  A[0][3] = l_prod<2 * KS + 1>(vp[1], X[1]);
  if constexpr (KS + 1 < KE) l_fill<KS + 1, KE>(A + 1, vp, X);
}
template <int KS, int OFF>
__device__ __forceinline__ void layer_rec(float (&d)[16], const uint32_t (&vp)[2][4], const uint32_t (&X)[2][13], uint64_t dk) {
  constexpr int KE = (KS + NBK < L_KS) ? KS + NBK : L_KS;
  uint32_t A[NBK][4];
  l_fill<KS, KE>(A, vp, X);
  wg_fence();
#pragma unroll
  for (int k = 0; k < KE - KS; k++)
    wgmma_rs_n32(d, A[k][0], A[k][1], A[k][2], A[k][3], dk + (uint64_t)((OFF + (KS + k) * L_SLAB) >> 4), (KS + k) > 0);
  wg_commit();
  if constexpr (KE < L_KS) {
    wg_wait<1>();
    layer_rec<KE, OFF>(d, vp, X, dk);
  }
}
template <int OFF, int NK>
__device__ __forceinline__ void layer_first(float (&d)[16], const uint32_t (&vp)[2][4], const uint32_t (&X)[2][13], uint64_t dk) {
  uint32_t A[NK][4];
  l_fill<0, NK>(A, vp, X);
  wg_fence();
#pragma unroll
  for (int k = 0; k < NK; k++) wgmma_rs_n32(d, A[k][0], A[k][1], A[k][2], A[k][3], dk + (uint64_t)((OFF + k * L_SLAB) >> 4), k > 0);
  wg_commit();
}
template <int KS, int KE>
__device__ __forceinline__ void g0_fill(uint32_t (*A)[4], const uint32_t (&X)[2][13], uint32_t selU, uint32_t selV) {
  A[0][0] = g0_prod<2 * KS>(X[0], selU, selV);
  A[0][1] = g0_prod<2 * KS>(X[1], selU, selV);
  A[0][2] = g0_prod<2 * KS + 1>(X[0], selU, selV);
  A[0][3] = g0_prod<2 * KS + 1>(X[1], selU, selV);
  if constexpr (KS + 1 < KE) g0_fill<KS + 1, KE>(A + 1, X, selU, selV);
}
template <int B0>
__device__ __forceinline__ void g0_rec(float (&d)[28], const uint32_t (&X)[2][13], uint32_t selU, uint32_t selV, uint64_t dk, uint32_t bar2) {
  constexpr int KS = B0 * NBK;
  if constexpr (KS == 8) mbar_wait(bar2, 0);
  if constexpr (KS == 16) mbar_wait(bar2 + 8, 0);
  constexpr int KE = (KS + NBK < G0_KS) ? KS + NBK : G0_KS;
  uint32_t A[NBK][4];
  g0_fill<KS, KE>(A, X, selU, selV);
  wg_fence();
#pragma unroll
  for (int k = 0; k < KE - KS; k++)
    wgmma_rs_n56(d, A[k][0], A[k][1], A[k][2], A[k][3], dk + (uint64_t)((OFF_G0 + (KS + k) * G0_SLAB) >> 4), (KS + k) > 0);
  wg_commit();
  if constexpr (KE < G0_KS) {
    wg_wait<1>();
    g0_rec<B0 + 1>(d, X, selU, selV, dk, bar2);
  }
}

__device__ __forceinline__ void ldsm_x4_t(uint32_t addr, uint32_t& r0, uint32_t& r1, uint32_t& r2, uint32_t& r3) {
  asm volatile("ldmatrix.sync.aligned.m8n8.x4.trans.shared.b16 {%0,%1,%2,%3}, [%4];"
               : "=r"(r0), "=r"(r1), "=r"(r2), "=r"(r3) : "r"(addr) : "memory");
}
__device__ __forceinline__ void ldsm_x2_t(uint32_t addr, uint32_t& r0, uint32_t& r1) {
  asm volatile("ldmatrix.sync.aligned.m8n8.x2.trans.shared.b16 {%0,%1}, [%2];" : "=r"(r0), "=r"(r1) : "r"(addr) : "memory");
}
__device__ __forceinline__ float tanh_fast(float x) { float y; asm("tanh.approx.f32 %0, %1;" : "=f"(y) : "f"(x)); return y; }

__device__ __forceinline__ uint32_t gelu2_pair(float lo, float hi, uint32_t bias) {
  uint32_t x = pack_bf16(lo, hi), t, u;
  asm("add.rn.bf16x2 %0, %0, %1;" : "+r"(x) : "r"(bias));
  asm("mul.rn.bf16x2 %0, %1, %1;" : "=r"(t) : "r"(x));
  asm("fma.rn.bf16x2 %0, %0, %1, %2;" : "+r"(t) : "r"(0x3D123D12u), "r"(0x3F4C3F4Cu));
  asm("mul.rn.bf16x2 %0, %1, %2;" : "=r"(u) : "r"(x), "r"(t));
  asm("tanh.approx.bf16x2 %0, %0;" : "+r"(u));
  asm("fma.rn.bf16x2 %0, %1, %0, %1;" : "+r"(u) : "r"(x));
  return u;
}

__device__ __forceinline__ void ldsm_x4(uint32_t addr, uint32_t (&r)[4]) {
  asm volatile("ldmatrix.sync.aligned.m8n8.x4.shared.b16 {%0,%1,%2,%3}, [%4];"
               : "=r"(r[0]), "=r"(r[1]), "=r"(r[2]), "=r"(r[3]) : "r"(addr) : "memory");
}
__device__ __forceinline__ uint32_t lds_u16(uint32_t addr) {
  unsigned short v;
  asm volatile("ld.shared.u16 %0, [%1];" : "=h"(v) : "r"(addr) : "memory");
  return v;
}
__device__ __forceinline__ uint32_t lds_u32(uint32_t addr) {
  uint32_t v;
  asm volatile("ld.shared.u32 %0, [%1];" : "=r"(v) : "r"(addr) : "memory");
  return v;
}

__global__ void __launch_bounds__(512, 1)
main_kernel(const __grid_constant__ Params P, const __grid_constant__ TmaMaps tms) {
  extern __shared__ __align__(1024) unsigned char smem[];
  const uint32_t sb = smem_u32(smem);
  const int tid = threadIdx.x, warp = __shfl_sync(0xffffffffu, tid >> 5, 0), lane = tid & 31;
  if (blockIdx.x < NHELP) {
    helper_role(blockIdx.x, P, smem, sb);
    return;
  }
  const int cta = blockIdx.x - NHELP, nq = cta & 3, grp = cta >> 2;
  const uint2 role = P.role[cta];
  const uint32_t bar0 = sb + OFF_BAR;
  auto BAR = [&](int i) { return bar0 + 8 * i; };
  const int wg = warp >> 2, w4 = warp & 3, g = lane >> 2, q = lane & 3;
  const uint64_t dk = P.dk;
  const long long tl_c0 = TL_START();
  TL_INIT();
  TL_PUT0(tl_c0);

  if (tid < 256) {
    const unsigned char* isrc = reinterpret_cast<const unsigned char*>(P.idx + grp * 128 * NF);
#pragma unroll
    for (int k = 0; k < 4; k++) {
      const int c = tid + 256 * k;
      if (c < 832) cp_async16(sb + OFF_IDX + c * 16, isrc + c * 16);
    }
    asm volatile("cp.async.commit_group;" ::: "memory");
#pragma unroll
    for (int k = 0; k < 8; k++) {
      const int c = tid + 256 * k;
      if (c < 2000) cp_async16(sb + OFF_TAB + ((c ^ ((c >> 3) & 1)) << 4), reinterpret_cast<const unsigned char*>(P.table) + c * 16);
    }
    asm volatile("cp.async.commit_group;" ::: "memory");
  }
  if (elect_one()) {
    mbar_init(BAR(warp), (warp == BAR_W1FREE || warp == BAR_W1DONE) ? 2 : 1);
    if (warp < NBAR - 16)
      mbar_init(BAR(16 + warp), (16 + warp == BAR_X0) ? 256 : (16 + warp == BAR_SETUP) ? SETUP_WARPS : (16 + warp == BAR_TABS) ? 224 : 1);
    asm volatile("fence.mbarrier_init.release.cluster;" ::: "memory");
  }
  __syncthreads();
  TL(26);

  if (warp == 15) {
    if (elect_one()) {
      mbar_expect_tx(BAR(BAR_STAB), sizeof(StaticTabs));
      bulk_g2s(sb + OFF_STAB, P.tabs, sizeof(StaticTabs), BAR(BAR_STAB));
      if ((sb & 0x3FFFF) != SMEM_BASE) __trap();
      const CUtensorMap* tm0 = &tms.m[nq];
      asm volatile("prefetch.tensormap [%0];" ::"l"(tm0) : "memory");
#pragma unroll
      for (int st = 0; st < W1_STAGES; st++) {
        if (st == 1 && (role.x >> 24) < 5) mbar_wait(BAR(BAR_Q), 0);
        mbar_expect_tx(BAR(BAR_W1FULL + st), W1_STAGE_BYTES);
        tma_2d(sb + w1_off(st), tm0, 0, st * 64, BAR(BAR_W1FULL + st));
        tma_2d(sb + w1_off(st) + 8192, tm0, 64, st * 64, BAR(BAR_W1FULL + st));
      }
      TLP(22);
      mbar_wait(BAR(BAR_EPOCH), 0);
      TLP(23);
      const unsigned target = lds_u32(sb + OFF_EPOCH) << 8;
      {
        unsigned v;
        uint32_t it = 0;
#pragma unroll 1
        do {
          asm volatile("ld.relaxed.gpu.global.u32 %0, [%1];" : "=r"(v) : "l"(P.ctr) : "memory");
          if (++it > (1u << 22)) __trap();
        } while ((int)(v - target) < 0);
        asm volatile("fence.acq_rel.cta;" ::: "memory");
      }
      fence_proxy_async_all();
      mbar_wait(BAR(BAR_X0), 0);
      TLP(24);
      mbar_expect_tx(BAR(BAR_IMG + 0), G0_BYTES / 3);
      mbar_expect_tx(BAR(BAR_G0B), G0_BYTES / 3);
      mbar_expect_tx(BAR(BAR_G0B + 1), G0_BYTES / 3);
#pragma unroll
      for (int i = 0; i < 6; i++)
        bulk_g2s(sb + OFF_G0 + i * (G0_BYTES / 6), P.img + i * (G0_BYTES / 6), G0_BYTES / 6, i < 2 ? BAR(BAR_IMG + 0) : BAR(BAR_G0B + (i - 2) / 2));
      mbar_wait(BAR(BAR_W1FREE), 0);
      mbar_expect_tx(BAR(BAR_IMG + 2), L_BYTES);
#pragma unroll
      for (int i = 0; i < 4; i++)
        bulk_g2s(sb + OFF_LB + i * (L_BYTES / 4), P.img + G0_BYTES + L_BYTES + i * (L_BYTES / 4), L_BYTES / 4, BAR(BAR_IMG + 2));
      mbar_wait(BAR(BAR_W1DONE), 0);
      mbar_expect_tx(BAR(BAR_IMG + 1), L_BYTES);
      mbar_expect_tx(BAR(BAR_IMG + 3), L_BYTES);
#pragma unroll
      for (int i = 0; i < 2; i++)
        bulk_g2s(sb + OFF_LA + i * (L_BYTES / 2), P.img + G0_BYTES + i * (L_BYTES / 2), L_BYTES / 2, BAR(BAR_IMG + 1));
#pragma unroll
      for (int i = 0; i < 2; i++)
        bulk_g2s(sb + OFF_LC + i * (L_BYTES / 2), P.img + G0_BYTES + 2 * L_BYTES + i * (L_BYTES / 2), L_BYTES / 2, BAR(BAR_IMG + 3));
      TLP(25);
    }
    __syncwarp();
    mbar_wait(BAR(BAR_X0), 0);
    mbar_wait(BAR(BAR_TABS), 0);
  } else if (wg < 2) {
    asm volatile("cp.async.wait_group 1;" ::: "memory");
    named_bar(1, 256);
#pragma unroll
    for (int k = 0; k < 7; k++) {
      const int p = tid + 256 * k;
      if (p < 64 * NF) {
        const uint2 v = reinterpret_cast<const uint2*>(smem + OFF_IDX)[p];
        const uint32_t o0 = v.x * 32 + ((v.x >> 2) & 1) * 16, o1 = v.y * 32 + ((v.y >> 2) & 1) * 16;
        reinterpret_cast<uint32_t*>(smem + OFF_XOFF)[p] = o0 | (o1 << 16);
      }
    }
    TL(1);
    asm volatile("cp.async.wait_all;" ::: "memory");
    mbar_arrive(BAR(BAR_X0));
    mbar_wait(BAR(BAR_X0), 0);
    TL(3);
    float acc[56];
    {
      const uint32_t xo = sb + OFF_XOFF + (wg * 64 + w4 * 16 + (lane & 15)) * 52;
      const uint32_t tb = sb + OFF_TAB, hx = (lane >> 4) << 4;
      const uint64_t db0 = P.dmn;
      uint32_t A[3][2][4];
#pragma unroll
      for (int pr = 0; pr < 2; pr++) {
        const uint32_t oa = lds_u32(xo + 4 * pr);
        ldsm_x4(tb + ((oa & 0xffff) ^ hx), A[pr][0]); ldsm_x4(tb + ((oa >> 16) ^ hx), A[pr][1]);
      }
#pragma unroll
      for (int pr = 0; pr < 13; pr++) {
        const int st = pr >> 1;
        uint32_t oa = 0;
        if (pr + 2 < 13) oa = lds_u32(xo + 4 * (pr + 2));
        if (!(pr & 1)) mbar_wait(BAR(BAR_W1FULL + st), 0);
        if (pr == 0) TL(28); if (pr == 6) TL(29);
        const uint64_t db = db0 + (uint64_t)((w1_off(st) + (pr & 1) * 4096) >> 4);
        wg_fence();
        wgmma_rs_n112_tb(acc, A[pr % 3][0][0], A[pr % 3][0][1], A[pr % 3][0][2], A[pr % 3][0][3], db, pr > 0);
        wgmma_rs_n112_tb(acc, A[pr % 3][1][0], A[pr % 3][1][1], A[pr % 3][1][2], A[pr % 3][1][3], db + (2048 >> 4), 1);
        wg_commit();
        wg_wait<1>();
        if (pr == 4 && (tid & 127) == 0) mbar_arrive(BAR(BAR_W1FREE));
        if (pr + 2 < 13) { ldsm_x4(tb + ((oa & 0xffff) ^ hx), A[(pr + 2) % 3][0]); ldsm_x4(tb + ((oa >> 16) ^ hx), A[(pr + 2) % 3][1]); }
      }
      wg_wait<0>();
      reg_fence(acc);
      if ((tid & 127) == 0) mbar_arrive(BAR(BAR_W1DONE));
    }
    TL(4);
    float dot[4];
    {
      mbar_wait(BAR(BAR_TABS), 0);
      uint32_t bb[16];
      const uint4* bp = reinterpret_cast<const uint4*>(smem + OFF_BW + q * 64);
#pragma unroll
      for (int i = 0; i < 4; i++) { const uint4 v = bp[i]; bb[4 * i] = v.x; bb[4 * i + 1] = v.y; bb[4 * i + 2] = v.z; bb[4 * i + 3] = v.w; }
      uint32_t H[14][2];
#pragma unroll
      for (int c = 0; c < 14; c++) {
        H[c][0] = gelu2_pair(acc[4 * c], acc[4 * c + 1], bb[c]);
        H[c][1] = gelu2_pair(acc[4 * c + 2], acc[4 * c + 3], bb[c]);
      }
      wg_fence();
#pragma unroll
      for (int j = 0; j < 7; j++)
        wgmma_rs_n8(dot, H[2 * j][0], H[2 * j][1], H[2 * j + 1][0], H[2 * j + 1][1], dk + (uint64_t)((OFF_W2 + j * 256) >> 4), j > 0);
      wg_commit();
      wg_wait<0>();
      reg_fence(dot);
    }
    __syncwarp();
    mbar_wait(BAR(BAR_EPOCH), 0);
    if (q == 0) {
      const unsigned epoch = lds_u32(sb + OFF_EPOCH);
#pragma unroll
      for (int r = 0; r < 2; r++) {
        const int row = wg * 64 + w4 * 16 + g + 8 * r;
        const unsigned long long pk = ((unsigned long long)epoch << 32) | (unsigned long long)__float_as_uint(dot[2 * r]);
        asm volatile("st.relaxed.gpu.global.u64 [%0], %1;" ::"l"(P.part + cta * 128 + row), "l"(pk) : "memory");
      }
    }
    __syncwarp();
  } else {
    const int t = tid - 256;
    const bool is_arr = (t == 192);
    unsigned ctr0 = 0;
    if (is_arr) asm volatile("ld.relaxed.gpu.global.u32 %0, [%1];" : "=r"(ctr0) : "l"(P.ctr) : "memory");
    {
      const int kind = role.x >> 24, w = warp - 8, rgrp = (role.y >> 24) & 15, rj = role.y >> 28;
      const unsigned char* wsb = reinterpret_cast<const unsigned char*>(P.ws);
      if (kind < 5 && elect_one()) {
        const uint32_t bytes = role.y & 0xffff;
        const uint32_t o = w * 8192;
        if (w == 0) mbar_expect_tx(BAR(BAR_Q), bytes);
        if (o < bytes) bulk_g2s(sb + OFF_G0 + o, wsb + (role.x & 0xffffff) + o, min(bytes - o, 8192u), BAR(BAR_Q));
      }
      TL(40);
      __syncwarp();
      const StaticTabs* T = reinterpret_cast<const StaticTabs*>(smem + OFF_STAB);
      uint32_t* img32 = reinterpret_cast<uint32_t*>(P.img);
      const unsigned char* raw = smem + OFF_G0 + ((role.y >> 16) & 127);
      uint32_t chk = 0;
      if (kind < 3) chk = layer_row(kind, rgrp, rj * SETUP_WARPS + w, lane, raw, T, BAR(BAR_Q), BAR(BAR_STAB), P.wout, img32);
      else if (kind == 3) chk = x1_row(rgrp, rj * SETUP_WARPS + w, lane, raw, T, BAR(BAR_Q), BAR(BAR_STAB), img32);
      if (__any_sync(0xffffffffu, chk != 0)) __trap();
      if (lane == 0) mbar_arrive(BAR(BAR_SETUP));
    }
    TL(1);
    if (is_arr) {
      asm volatile("" : "+r"(ctr0));
      *reinterpret_cast<volatile unsigned*>(smem + OFF_EPOCH) = (ctr0 >> 8) + 1;
      mbar_wait(BAR(BAR_SETUP), 0);
      TLA(30);
      asm volatile("red.relaxed.gpu.global.add.u32 [%0], 1;" ::"l"(P.ctr) : "memory");
      mbar_arrive(BAR(BAR_EPOCH));
      TLA(31);
    }
    __syncwarp();
    {
      const int c0 = (nq >> 1) * 208 + (nq & 1) * 96, nw = (nq & 1) ? 112 : 96;
      if (t < 56) {
        const int n = 2 * t;
        const uint32_t v = (n < nw) ? __ldg(reinterpret_cast<const uint32_t*>(P.b1 + c0 + n)) : 0u;
        reinterpret_cast<uint32_t*>(smem + OFF_BW)[(t & 3) * 16 + (t >> 2)] = v;
      }
      if (t >= 64 && t < 64 + 112) {
        const int k = t - 64;
        const float w = (k < nw) ? 0.5f * bf2f(__ldg(P.w2 + c0 + k)) : 0.f;
        unsigned char* base = smem + OFF_W2 + (k >> 4) * 256 + ((k >> 3) & 1) * 128;
        *reinterpret_cast<bf16*>(base + (k & 7) * 2) = __float2bfloat16(w);
        if ((k & 7) == 0) {
#pragma unroll
          for (int r = 1; r < 8; r++) *reinterpret_cast<uint4*>(base + r * 16) = make_uint4(0, 0, 0, 0);
        }
      }
      fence_proxy_async();
    }
    if (t >= 128 && t < 192) {
      int u = t - 128, l = u >> 5, qq = (u >> 3) & 3, a = u & 7;
      float wtv = 0.f;
      if (a < 6) wtv = bf2f(__ldg(P.wout + l * NF + 8 * (a >> 1) + 2 * qq + (a & 1)));
      else if (a == 6 && !(qq & 1)) wtv = bf2f(__ldg(P.wout + l * NF + 24 + (qq >> 1)));
      reinterpret_cast<float*>(smem + OFF_WTAB)[u] = wtv;
    }
    mbar_arrive(BAR(BAR_TABS));
    TL(2);
    mbar_wait(BAR(BAR_X0), 0);
    mbar_wait(BAR(BAR_TABS), 0);
  }

  TL(5);
  const uint32_t selU = (q == 0) ? 0x1010u : (q == 1) ? 0x3232u : (q == 2) ? 0x3210u : 0x7654u;
  const uint32_t selV = (q < 2) ? 0x3210u : 0x7654u;
  uint32_t bo_raw = __ldg(reinterpret_cast<const unsigned short*>(P.bout));
  mbar_wait(BAR(BAR_EPOCH), 0);
  mbar_wait(BAR(BAR_STAB), 0);
  const unsigned epoch = lds_u32(sb + OFF_EPOCH);

  uint32_t X[2][13];
  auto load_x = [&](int sl) {
    const uint4 o = *reinterpret_cast<const uint4*>(smem + OFF_LOFF + lane * 16);
    const uint32_t xo = sb + OFF_XOFF + sl * 52;
    const uint32_t tb = sb + OFF_TAB, hx = ((lane >> 3) & 1) << 4;
    const uint32_t a0 = lds_u16(xo + (o.x & 0xffff)), a1 = lds_u16(xo + (o.x >> 16));
    const uint32_t a2 = lds_u16(xo + (o.y & 0xffff)), a3 = lds_u16(xo + (o.y >> 16));
    const uint32_t a4 = lds_u16(xo + (o.z & 0xffff)), a5 = lds_u16(xo + (o.z >> 16));
    const uint32_t a6 = lds_u16(xo + (o.w & 0xffff));
    ldsm_x4_t(tb + (a0 ^ hx), X[0][0], X[1][0], X[0][1], X[1][1]);
    ldsm_x4_t(tb + (a1 ^ hx), X[0][2], X[1][2], X[0][3], X[1][3]);
    ldsm_x4_t(tb + (a2 ^ hx), X[0][4], X[1][4], X[0][5], X[1][5]);
    ldsm_x4_t(tb + (a3 ^ hx), X[0][6], X[1][6], X[0][7], X[1][7]);
    ldsm_x4_t(tb + (a4 ^ hx), X[0][8], X[1][8], X[0][9], X[1][9]);
    ldsm_x4_t(tb + (a5 ^ hx), X[0][10], X[1][10], X[0][11], X[1][11]);
    ldsm_x2_t(tb + (a6 ^ hx), X[0][12], X[1][12]);
  };
  load_x(nq * 32 + wg * 4 + w4);
#pragma unroll 1
  for (int it = 0; it < 2; it++) {
    const int sl = nq * 32 + (wg + 4 * it) * 4 + w4;
    float S = 0.f;
    uint32_t vx[2][4], vg[2][4];
    {
      float a0[28];
      mbar_wait(BAR(BAR_IMG + 0), 0);
      if (it < 2) TL(6 + it * 8);
      g0_rec<0>(a0, X, selU, selV, dk, BAR(BAR_G0B));
      wg_wait<0>();
      reg_fence(a0);
      const float4* wt = reinterpret_cast<const float4*>(smem + OFF_WTAB) + q * 2;
      float4 wa = wt[0], wb = wt[1];
#pragma unroll
      for (int r = 0; r < 2; r++) {
        S = fmaf(wa.x, a0[0 + 2 * r], S); S = fmaf(wa.y, a0[1 + 2 * r], S);
        S = fmaf(wa.z, a0[4 + 2 * r], S); S = fmaf(wa.w, a0[5 + 2 * r], S);
        S = fmaf(wb.x, a0[8 + 2 * r], S); S = fmaf(wb.y, a0[9 + 2 * r], S);
        S = fmaf(wb.z, a0[24 + 2 * r], S);
#pragma unroll
        for (int c = 0; c < 3; c++) {
          vx[r][c] = pack_bf16(a0[4 * c + 2 * r], a0[4 * c + 2 * r + 1]);
          vg[r][c] = pack_bf16(a0[12 + 4 * c + 2 * r], a0[12 + 4 * c + 2 * r + 1]);
        }
        vx[r][3] = pack_bf16(a0[24 + 2 * r], 0.f);
        vg[r][3] = pack_bf16(a0[24 + 2 * r + 1], 0.f);
      }
    }
    float g3[16], xa[16];
    if (it < 2) TL(7 + it * 8);
    mbar_wait(BAR(BAR_IMG + 2), 0);
    mbar_wait(BAR(BAR_IMG + 1), 0);
    mbar_wait(BAR(BAR_IMG + 3), 0);
    if (it < 2) TL(8 + it * 8);
    layer_rec<0, OFF_LB>(xa, vx, X, dk);
    if (it < 2) TL(9 + it * 8);
    wg_wait<1>();
    layer_first<OFF_LA, 3>(g3, vg, X, dk);
    wg_wait<1>();
    reg_fence(xa);
    {
      const float4* wt = reinterpret_cast<const float4*>(smem + OFF_WTAB) + 8 + q * 2;
      float4 wa = wt[0], wb = wt[1];
#pragma unroll
      for (int r = 0; r < 2; r++) {
        S = fmaf(wa.x, xa[0 + 2 * r], S); S = fmaf(wa.y, xa[1 + 2 * r], S);
        S = fmaf(wa.z, xa[4 + 2 * r], S); S = fmaf(wa.w, xa[5 + 2 * r], S);
        S = fmaf(wb.x, xa[8 + 2 * r], S); S = fmaf(wb.y, xa[9 + 2 * r], S);
        S = fmaf(wb.z, xa[12 + 2 * r], S);
#pragma unroll
        for (int c = 0; c < 3; c++) vx[r][c] = pack_bf16(xa[4 * c + 2 * r], xa[4 * c + 2 * r + 1]);
        vx[r][3] = pack_bf16(xa[12 + 2 * r], 0.f);
      }
    }
    layer_rec<3, OFF_LA>(g3, vg, X, dk);
    if (it < 2) TL(10 + it * 8);
    wg_wait<1>();
    const unsigned long long* pp = P.part + (grp * 4 + (lane & 3)) * 128 + sl;
    unsigned long long pk;
    asm volatile("ld.relaxed.gpu.global.u64 %0, [%1];" : "=l"(pk) : "l"(pp) : "memory");
    float xc[16];
    layer_rec<0, OFF_LC>(xc, vx, X, dk);
    if (it == 0) load_x(sl + 16);
    wg_wait<0>();
    reg_fence(xc);
    reg_fence(g3);
    {
      float Se = 0.f;
#pragma unroll
      for (int r = 0; r < 2; r++) {
#pragma unroll
        for (int c = 0; c < 3; c++) {
          S = fmaf(g3[4 * c + 2 * r], xc[4 * c + 2 * r], S);
          S = fmaf(g3[4 * c + 2 * r + 1], xc[4 * c + 2 * r + 1], S);
        }
        Se = fmaf(g3[12 + 2 * r], xc[12 + 2 * r], Se);
      }
      if (!(q & 1)) S += Se;
    }
#pragma unroll
    for (int o = 16; o > 0; o >>= 1) S += __shfl_xor_sync(0xffffffffu, S, o);
    if (it < 2) TL(12 + it * 8);
    {
      uint32_t spin = 0;
      while (lane < 4 && (unsigned)(pk >> 32) != epoch) {
        asm volatile("ld.relaxed.gpu.global.u64 %0, [%1];" : "=l"(pk) : "l"(pp) : "memory");
        if (++spin > (1u << 24)) __trap();
      }
      __syncwarp();
      float dv = __uint_as_float((unsigned)pk);
      float d01 = dv + __shfl_xor_sync(0xffffffffu, dv, 1);
      float dsum = d01 + __shfl_xor_sync(0xffffffffu, d01, 2);
      asm volatile("" : "+r"(bo_raw));
      if (lane == 0) P.out[grp * 128 + sl] = __float2bfloat16(S + dsum + __uint_as_float(bo_raw << 16));
    }
    __syncwarp();
    if (it < 2) TL(13 + it * 8);
  }
  TL_DUMP();
}

__global__ void __launch_bounds__(128) fallback_kernel(const int* __restrict__ idx, const bf16* __restrict__ table, const bf16* __restrict__ ws,
                                                       const bf16* __restrict__ wout, const bf16* __restrict__ w1, const bf16* __restrict__ b1,
                                                       const bf16* __restrict__ w2, const bf16* __restrict__ bout, bf16* __restrict__ out) {
  __shared__ float x0[416], xa[416], xb[416], red[128];
  const int b = blockIdx.x, t = threadIdx.x;
  for (int i = t; i < 416; i += 128) { x0[i] = bf2f(table[idx[b * NF + i / 16] * 16 + (i & 15)]); xa[i] = x0[i]; }
  __syncthreads();
  float acc = 0.f;
  float* cur = xa;
  float* nxt = xb;
  for (int l = 0; l < 6; l++) {
    for (int o = t; o < 416; o += 128) {
      const int h = o >> 4, d = o & 15;
      const bf16* w = ws + (l * NF + h) * NF * NF;
      float s = 0.f;
      for (int i = 0; i < NF; i++) {
        float u = 0.f;
        for (int j = 0; j < NF; j++) u = fmaf(bf2f(w[i * NF + j]), x0[j * 16 + d], u);
        s = fmaf(u, cur[i * 16 + d], s);
      }
      nxt[o] = s;
      acc = fmaf(s, bf2f(wout[l * NF + h]), acc);
    }
    __syncthreads();
    float* tmp = cur; cur = nxt; nxt = tmp;
  }
  for (int n = t; n < 416; n += 128) {
    float h = 0.f;
    for (int k = 0; k < 416; k++) h = fmaf(x0[k], bf2f(w1[k * 416 + n]), h);
    h += bf2f(b1[n]);
    const float gl = 0.5f * h * (1.f + tanhf(0.7978845608028654f * (h + 0.044715f * h * h * h)));
    acc = fmaf(gl, bf2f(w2[n]), acc);
  }
  red[t] = acc;
  __syncthreads();
  for (int o = 64; o > 0; o >>= 1) { if (t < o) red[t] += red[t + o]; __syncthreads(); }
  if (t == 0) out[b] = __float2bfloat16(red[0] + bf2f(bout[0]));
}

typedef CUresult (*EncodeFn)(CUtensorMap*, CUtensorMapDataType, cuuint32_t, void*, const cuuint64_t*, const cuuint64_t*,
                             const cuuint32_t*, const cuuint32_t*, CUtensorMapInterleave, CUtensorMapSwizzle,
                             CUtensorMapL2promotion, CUtensorMapFloatOOBfill);

extern "C" void kernel_launch(void* const* d_in, const int* in_sizes, int n_in, void* d_out, int out_size) {
  const int* idx = (const int*)d_in[0];
  const bf16* table = (const bf16*)d_in[1];
  const bf16* ws = (const bf16*)d_in[2];
  const bf16* wout = (const bf16*)d_in[3];
  const bf16* w1 = (const bf16*)d_in[4];
  const bf16* b1 = (const bf16*)d_in[5];
  const bf16* w2 = (const bf16*)d_in[6];
  const bf16* bo = (const bf16*)d_in[7];
  bf16* out = (bf16*)d_out;

  static EncodeFn enc = nullptr;
  static Params P;
  static int n_sm = 0;
  if (!n_sm) {
    int dev = 0;
    cudaGetDevice(&dev);
    cudaDeviceGetAttribute(&n_sm, cudaDevAttrMultiProcessorCount, dev);
  }
  if (n_sm < NCTA + NHELP) {
    fallback_kernel<<<4096, 128, 0, cudaStreamPerThread>>>(idx, table, ws, wout, w1, b1, w2, bo, out);
    return;
  }
  if (!enc) {
    void* fn = nullptr;
    cudaDriverEntryPointQueryResult qr;
    cudaGetDriverEntryPoint("cuTensorMapEncodeTiled", &fn, cudaEnableDefault, &qr);
    enc = (EncodeFn)fn;
    cudaFuncSetAttribute(main_kernel, cudaFuncAttributeMaxDynamicSharedMemorySize, LAUNCH_SMEM);
    void* p;
    cudaGetSymbolAddress(&p, g_img); P.img = (unsigned char*)p;
    cudaGetSymbolAddress(&p, g_part); P.part = (unsigned long long*)p;
    cudaGetSymbolAddress(&p, g_ctr); P.ctr = (unsigned*)p;
    cudaGetSymbolAddress(&p, g_tabs); P.tabs = p;
    P.dk = make_desc(0, 128, 256, 0);
    P.dmn = make_desc(0, 8192, 1024, 1);
    for (int c = 0; c < NCTA; c++) P.role[c] = make_role(c);
  }
  P.idx = idx; P.table = table; P.ws = ws; P.wout = wout; P.b1 = b1; P.w2 = w2; P.bout = bo; P.out = out;
  TmaMaps tms;
  for (int h = 0; h < 4; h++) {
    const int c0 = (h >> 1) * 208 + (h & 1) * 96, nw = (h & 1) ? 112 : 96;
    cuuint64_t dims[2] = {(cuuint64_t)nw, 416};
    cuuint64_t strides[1] = {832};
    cuuint32_t box[2] = {64, 64};
    cuuint32_t es[2] = {1, 1};
    enc(&tms.m[h], CU_TENSOR_MAP_DATA_TYPE_BFLOAT16, 2, (void*)(w1 + c0), dims, strides, box, es,
        CU_TENSOR_MAP_INTERLEAVE_NONE, CU_TENSOR_MAP_SWIZZLE_128B, CU_TENSOR_MAP_L2_PROMOTION_L2_128B,
        CU_TENSOR_MAP_FLOAT_OOB_FILL_NONE);
  }
  main_kernel<<<NCTA + NHELP, 512, LAUNCH_SMEM, cudaStreamPerThread>>>(P, tms);
}
```

```cpp
#include <cuda_runtime.h>
#include <cuda_bf16.h>
#include <cuda.h>
#include <stdint.h>

typedef __nv_bfloat16 bf16;

constexpr int NF = 26;
constexpr int NCTA = 128;

constexpr int G0_KS = 24, G0_N = 56, G0_SLAB = G0_N * 32;
constexpr int L_KS = 43, L_SLAB = 1024;
constexpr int G0_BYTES = G0_KS * G0_SLAB;
constexpr int L_BYTES = L_KS * L_SLAB;
constexpr int IMG_BYTES = G0_BYTES + 3 * L_BYTES;

constexpr int W1_STAGES = 7;
constexpr int W1_STAGE_BYTES = 16384;
constexpr int OFF_LB = 0;
constexpr int OFF_LA = 44032;
constexpr int OFF_LC = 88064;
__host__ __device__ constexpr int w1_off(int st) { return st < 2 ? st * W1_STAGE_BYTES : OFF_LA + (st - 2) * W1_STAGE_BYTES; }
constexpr int OFF_G0 = 132096;
constexpr int OFF_IDX = 132096 + 16384;
constexpr int OFF_TAB = OFF_G0 + G0_BYTES;
constexpr int OFF_XOFF = OFF_TAB + 32000;
constexpr int OFF_BAR = OFF_XOFF + 6656;
constexpr int OFF_BW = OFF_BAR + 256;
constexpr int OFF_W2 = OFF_BW + 256;
constexpr int OFF_WTAB = OFF_W2 + 1792;
constexpr int OFF_EPOCH = OFF_WTAB + 256;
constexpr int OFF_STAB = (OFF_EPOCH + 16 + 127) / 128 * 128;
constexpr int OFF_LOFF = OFF_STAB + 3072 + 704;
constexpr int SMEM_BYTES = OFF_STAB + 4288;
static_assert(SMEM_BYTES <= 229376, "smem");
constexpr int LAUNCH_SMEM = SMEM_BYTES;

constexpr int BAR_W1FULL = 0  , BAR_W1FREE = 10  , BAR_W1DONE = 11  ,
              BAR_IMG = 14  , BAR_X0 = 18, BAR_SETUP = 19, BAR_EPOCH = 20, BAR_TABS = 21,
              BAR_Q = 22, BAR_STAB = 23, BAR_G0B = 24  , NBAR = 26;

struct TmaMaps { CUtensorMap m[4]; };
struct Params {
  const int* idx; const bf16* table; const bf16* ws; const bf16* wout; const bf16* b1; const bf16* w2; const bf16* bout;
  bf16* out;
  unsigned char* img; unsigned long long* part; unsigned* ctr; const void* tabs;
  uint64_t dk, dmn;
  uint2 role[NCTA];
};

__device__ __align__(1024) unsigned char g_img[IMG_BYTES];
__device__ unsigned long long g_part[NCTA * 128];
__device__ unsigned g_ctr;

#define GT(i) do {} while (0)
#define TL(i) do {} while (0)
#define TLP(i) do {} while (0)
#define TLA(i) do {} while (0)
#define TLW(w, i) do {} while (0)
#define TL_INIT() do {} while (0)
#define TL_START() 0
#define TL_PUT0(c) do {} while (0)
#define TL_DUMP() do {} while (0)
__device__ __forceinline__ uint32_t smem_u32(const void* p) { return (uint32_t)__cvta_generic_to_shared(p); }
__device__ __forceinline__ bool elect_one() {
  uint32_t pred;
  asm volatile("{\n.reg .pred p;\nelect.sync _|p, 0xffffffff;\nselp.u32 %0, 1, 0, p;\n}\n" : "=r"(pred));
  return pred != 0;
}
__device__ __forceinline__ void mbar_init(uint32_t bar, uint32_t cnt) {
  asm volatile("mbarrier.init.shared::cta.b64 [%0], %1;" ::"r"(bar), "r"(cnt) : "memory");
}
__device__ __forceinline__ void mbar_expect_tx(uint32_t bar, uint32_t bytes) {
  asm volatile("mbarrier.arrive.expect_tx.shared::cta.b64 _, [%0], %1;" ::"r"(bar), "r"(bytes) : "memory");
}
__device__ __forceinline__ void mbar_arrive(uint32_t bar) {
  asm volatile("mbarrier.arrive.shared::cta.b64 _, [%0];" ::"r"(bar) : "memory");
}
__device__ __forceinline__ bool mbar_try(uint32_t bar, uint32_t parity) {
  uint32_t ok;
  asm volatile("{\n.reg .pred p;\nmbarrier.try_wait.parity.shared::cta.b64 p, [%1], %2;\nselp.u32 %0, 1, 0, p;\n}\n"
               : "=r"(ok) : "r"(bar), "r"(parity) : "memory");
  return ok != 0;
}
__device__ __forceinline__ void mbar_wait(uint32_t bar, uint32_t parity) {
#pragma unroll 1
  for (uint32_t it = 0; it < (1u << 26); it++)
    if (mbar_try(bar, parity)) return;
  __trap();
}
__device__ __forceinline__ void bulk_g2s(uint32_t dst, const void* src, uint32_t bytes, uint32_t bar) {
  asm volatile("cp.async.bulk.shared::cluster.global.mbarrier::complete_tx::bytes [%0], [%1], %2, [%3];"
               ::"r"(dst), "l"(src), "r"(bytes), "r"(bar) : "memory");
}
__device__ __forceinline__ void tma_2d(uint32_t dst, const CUtensorMap* tm, int x, int y, uint32_t bar) {
  asm volatile("cp.async.bulk.tensor.2d.shared::cluster.global.mbarrier::complete_tx::bytes [%0], [%1, {%3, %4}], [%2];"
               ::"r"(dst), "l"(tm), "r"(bar), "r"(x), "r"(y) : "memory");
}
__device__ __forceinline__ void cp_async16(uint32_t dst, const void* src) {
  asm volatile("cp.async.cg.shared.global [%0], [%1], 16;" ::"r"(dst), "l"(src) : "memory");
}
__device__ __forceinline__ void fence_proxy_async() { asm volatile("fence.proxy.async.shared::cta;" ::: "memory"); }
__device__ __forceinline__ void fence_proxy_async_all() { asm volatile("fence.proxy.async;" ::: "memory"); }
template <int ID, int N> __device__ __forceinline__ void named_bar_t() { asm volatile("bar.sync %0, %1;" ::"n"(ID), "n"(N) : "memory"); }
#define named_bar(id, n) named_bar_t<id, n>()

__device__ __forceinline__ void wg_fence() { asm volatile("wgmma.fence.sync.aligned;" ::: "memory"); }
__device__ __forceinline__ void wg_commit() { asm volatile("wgmma.commit_group.sync.aligned;" ::: "memory"); }
template <int N> __device__ __forceinline__ void wg_wait() { asm volatile("wgmma.wait_group.sync.aligned %0;" ::"n"(N) : "memory"); }
template <int N> __device__ __forceinline__ void reg_fence(float (&d)[N]) {
#pragma unroll
  for (int i = 0; i < N; i++) asm volatile("" : "+f"(d[i])::"memory");
}
constexpr uint32_t SMEM_BASE = 1024;
__host__ __device__ constexpr uint64_t make_desc(uint32_t off, uint32_t lbo, uint32_t sbo, uint32_t swz) {
  return (uint64_t)(((SMEM_BASE + off) & 0x3FFFF) >> 4) | ((uint64_t)(lbo >> 4) << 16) | ((uint64_t)(sbo >> 4) << 32) | ((uint64_t)swz << 62);
}

#define ACC4(d, o) "+f"(d[o]), "+f"(d[o + 1]), "+f"(d[o + 2]), "+f"(d[o + 3])
#define ACC8(d, o) ACC4(d, o), ACC4(d, o + 4)

__device__ __forceinline__ void wgmma_rs_n32(float (&d)[16], uint32_t a0, uint32_t a1, uint32_t a2, uint32_t a3, uint64_t db, int sc) {
  asm volatile("{\n.reg .pred p;\nsetp.ne.b32 p, %21, 0;\n"
               "wgmma.mma_async.sync.aligned.m64n32k16.f32.bf16.bf16 "
               "{%0,%1,%2,%3,%4,%5,%6,%7,%8,%9,%10,%11,%12,%13,%14,%15}, {%16,%17,%18,%19}, %20, p, 1, 1, 0;\n}\n"
               : ACC8(d, 0), ACC8(d, 8)
               : "r"(a0), "r"(a1), "r"(a2), "r"(a3), "l"(db), "r"(sc));
}
__device__ __forceinline__ void wgmma_rs_n56(float (&d)[28], uint32_t a0, uint32_t a1, uint32_t a2, uint32_t a3, uint64_t db, int sc) {
  asm volatile("{\n.reg .pred p;\nsetp.ne.b32 p, %33, 0;\n"
               "wgmma.mma_async.sync.aligned.m64n56k16.f32.bf16.bf16 "
               "{%0,%1,%2,%3,%4,%5,%6,%7,%8,%9,%10,%11,%12,%13,%14,%15,%16,%17,%18,%19,%20,%21,%22,%23,%24,%25,%26,%27}, "
               "{%28,%29,%30,%31}, %32, p, 1, 1, 0;\n}\n"
               : ACC8(d, 0), ACC8(d, 8), ACC8(d, 16), ACC4(d, 24)
               : "r"(a0), "r"(a1), "r"(a2), "r"(a3), "l"(db), "r"(sc));
}
__device__ __forceinline__ void wgmma_rs_n112_tb(float (&d)[56], uint32_t a0, uint32_t a1, uint32_t a2, uint32_t a3, uint64_t db, int sc) {
  asm volatile("{\n.reg .pred p;\nsetp.ne.b32 p, %61, 0;\n"
               "wgmma.mma_async.sync.aligned.m64n112k16.f32.bf16.bf16 "
               "{%0,%1,%2,%3,%4,%5,%6,%7,%8,%9,%10,%11,%12,%13,%14,%15,%16,%17,%18,%19,%20,%21,%22,%23,%24,%25,%26,%27,%28,%29,%30,%31,%32,%33,%34,%35,%36,%37,%38,%39,%40,%41,%42,%43,%44,%45,%46,%47,%48,%49,%50,%51,%52,%53,%54,%55}, "
               "{%56,%57,%58,%59}, %60, p, 1, 1, 1;\n}\n"
               : ACC8(d, 0), ACC8(d, 8), ACC8(d, 16), ACC8(d, 24), ACC8(d, 32), ACC8(d, 40), ACC8(d, 48)
               : "r"(a0), "r"(a1), "r"(a2), "r"(a3), "l"(db), "r"(sc));
}

__device__ __forceinline__ void wgmma_rs_n8(float (&d)[4], uint32_t a0, uint32_t a1, uint32_t a2, uint32_t a3, uint64_t db, int sc) {
  asm volatile("{\n.reg .pred p;\nsetp.ne.b32 p, %9, 0;\n"
               "wgmma.mma_async.sync.aligned.m64n8k16.f32.bf16.bf16 {%0,%1,%2,%3}, {%4,%5,%6,%7}, %8, p, 1, 1, 0;\n}\n"
               : ACC4(d, 0)
               : "r"(a0), "r"(a1), "r"(a2), "r"(a3), "l"(db), "r"(sc));
}
__device__ __forceinline__ uint32_t mul_lo(uint32_t v, uint32_t r) {
  __nv_bfloat162 a = *reinterpret_cast<__nv_bfloat162*>(&v), b = *reinterpret_cast<__nv_bfloat162*>(&r);
  __nv_bfloat162 c = __hmul2(__low2bfloat162(a), b);
  return *reinterpret_cast<uint32_t*>(&c);
}
__device__ __forceinline__ uint32_t mul_hi(uint32_t v, uint32_t r) {
  __nv_bfloat162 a = *reinterpret_cast<__nv_bfloat162*>(&v), b = *reinterpret_cast<__nv_bfloat162*>(&r);
  __nv_bfloat162 c = __hmul2(__high2bfloat162(a), b);
  return *reinterpret_cast<uint32_t*>(&c);
}
__device__ __forceinline__ uint32_t mul_ew(uint32_t v, uint32_t r) {
  __nv_bfloat162 a = *reinterpret_cast<__nv_bfloat162*>(&v), b = *reinterpret_cast<__nv_bfloat162*>(&r);
  __nv_bfloat162 c = __hmul2(a, b);
  return *reinterpret_cast<uint32_t*>(&c);
}
__device__ __forceinline__ uint32_t pack_bf16(float lo, float hi) {
  uint32_t r;
  asm("cvt.rn.bf16x2.f32 %0, %1, %2;" : "=r"(r) : "f"(hi), "f"(lo));
  return r;
}
__device__ __forceinline__ float bf2f(bf16 v) { return __bfloat162float(v); }
__device__ __forceinline__ float bflo(uint32_t w) { return __uint_as_float(w << 16); }
__device__ __forceinline__ float bfhi(uint32_t w) { return __uint_as_float(w & 0xffff0000u); }

__device__ __forceinline__ void st_img(uint32_t* p, uint32_t v) {
  asm volatile("st.relaxed.gpu.global.u32 [%0], %1;" ::"l"(p), "r"(v) : "memory");
}
__device__ __forceinline__ uint32_t ld_back(const uint32_t* p) {
  uint32_t v;
  asm volatile("ld.relaxed.gpu.global.u32 %0, [%1];" : "=r"(v) : "l"(p) : "memory");
  return v;
}
__host__ __device__ constexpr int Fq(int q, int t, int e) {
  if (t == 12) return 24 + e;
  const int u = (t + 3 * q) % 12;
  const int sw = (q >= 2 && u >= 6) ? 1 : 0;
  return 2 * u + (e ^ sw);
}
constexpr int M_ONE = 26, M_NONE = 27;
struct Mono { int f1, f2; };
__host__ __device__ constexpr Mono g0_mono(int s, int q, int e) {
  if (s < 30) { const int d = s / 6 + 1, a = (s % 6) >> 1; return {Fq(q, a, s & 1), Fq(q, a + d, e)}; }
  if (s < 33) return {Fq(q, s - 30, e), Fq(q, s - 24, e)};
  if (s < 35) return {Fq(q, s - 33, e), Fq(q, s - 33, e)};
  if (s == 35) return {Fq(q, e, 0), Fq(q, e, 1)};
  if (s == 36) return {Fq(q, 2, 0), Fq(q, 2, e)};
  if (s == 37) return e ? Mono{Fq(q, 2, 1), Fq(q, 2, 1)} : Mono{M_NONE, M_NONE};
  if (s < 44) return {24 + ((s - 38) & 1), Fq(q, (s - 38) >> 1, e)};
  if (s < 47) return {Fq(q, s - 44, e), M_ONE};
  if (q == 0) return {24, 24 + e};
  if (q == 1) return e ? Mono{25, 25} : Mono{M_NONE, M_NONE};
  if (q == 2) return {24 + e, M_ONE};
  return e ? Mono{M_NONE, M_NONE} : Mono{M_ONE, M_ONE};
}
constexpr int QM_RS = 40;
constexpr int O_ZERO = 31 * QM_RS + 39, O_CONST = 30 * QM_RS + 39;
struct StaticTabs {
  uint32_t otab[48 * 8];
  uint32_t x1tab[48 * 8];
  uint16_t ltab[88 * 4];
  uint16_t loff[32 * 8];
};
constexpr StaticTabs make_tabs() {
  StaticTabs T{};
  for (int s = 0; s < 48; s++)
    for (int q = 0; q < 4; q++)
      for (int e = 0; e < 2; e++) {
        const Mono m = g0_mono(s, q, e);
        const bool none = m.f1 == M_NONE, cs = m.f1 == M_ONE, lin = m.f2 == M_ONE;
        const uint32_t o1 = none ? O_ZERO : cs ? O_CONST : m.f1 * QM_RS + (lin ? 26 : m.f2);
        const uint32_t o2 = (none || cs || lin || m.f1 == m.f2) ? O_ZERO : m.f2 * QM_RS + m.f1;
        T.otab[s * 8 + q * 2 + e] = o1 | (o2 << 16);
        const bool qd = m.f1 < NF && m.f2 < NF;
        const uint32_t y1 = qd ? m.f1 * NF + m.f2 : 0xffffu;
        const uint32_t y2 = (qd && m.f1 != m.f2) ? m.f2 * NF + m.f1 : 0xffffu;
        T.x1tab[s * 8 + q * 2 + e] = y1 | (y2 << 16);
      }
  for (int s = 0; s < 88; s++)
    for (int q = 0; q < 4; q++) {
      uint16_t v = 0;
      if (s < 85) {
        const bool ex = s >= 78;
        const int a = s / 13, k = s - 78;
        const int tt = ex ? ((k < 3) ? k : (k < 6 ? k + 3 : 12)) : s % 13;
        const int in = ex ? 24 + (q >> 1) : 8 * (a >> 1) + 2 * q + (a & 1);
        const bool valid = !(ex && tt == 12 && (q & 1));
        const int f0 = Fq(q, tt, 0);
        v = (uint16_t)((f0 >> 1) | ((f0 & 1) << 4) | ((valid ? 1 : 0) << 5) | (in << 6));
      }
      T.ltab[s * 4 + q] = v;
    }
  for (int ln = 0; ln < 32; ln++)
    for (int k = 0; k < 8; k++) {
      const int m = ln >> 3, r = ln & 7;
      const int tt = (k < 6) ? 2 * k + (m >> 1) : 12;
      T.loff[ln * 8 + k] = (uint16_t)(2 * Fq(r >> 1, tt, r & 1));
    }
  return T;
}
static_assert(sizeof(StaticTabs) == 4288, "tabs");
__device__ __align__(128) const StaticTabs g_tabs = make_tabs();

constexpr int SETUP_WARPS = 7;
constexpr int WL_BYTES = NF * NF * NF * 2;
static inline uint2 make_role(int cta) {
  int kind = 5, grp = 0, j = 0, off = 0, bytes = 0;
  const int c = cta, SL = NF * NF * 2;
  if (c < 56) { kind = 1 + c / 28; grp = (c % 28) / 7; j = c % 7; off = kind * WL_BYTES + grp * 8 * SL; bytes = (grp < 3 ? 8 : 2) * SL; }
  else if (c < 80) { kind = 0; grp = (c - 56) / 8; j = (c - 56) % 8; off = 3 * WL_BYTES + grp * 8 * SL; bytes = 8 * SL; }
  else if (c < 83) { kind = 0; grp = 3; j = c - 80; off = 3 * WL_BYTES + 24 * SL; bytes = 2 * SL; }
  else if (c < 95) { kind = 3; grp = (c - 83) / 4; j = (c - 83) % 4; off = grp * 8 * SL; bytes = 8 * SL; }
  const int delta = off & 127;
  uint2 r;
  r.x = (uint32_t)(off - delta) | ((uint32_t)kind << 24);
  r.y = (uint32_t)(bytes + delta) | ((uint32_t)delta << 16) | ((uint32_t)grp << 24) | ((uint32_t)j << 28);
  return r;
}

__device__ __forceinline__ uint32_t layer_row(int li, int grp, int r, int lane, const unsigned char* raw, const StaticTabs* T,
                                              uint32_t bar, uint32_t tbar, const bf16* __restrict__ wout, uint32_t* img32) {
  const int ks = li ? r : 13 * grp + (r >> 2), ng = li ? grp : (r & 3);
  if (ks >= 43 || (!li && grp < 3 && r >= 52)) return 0;
  const uint32_t* w32 = reinterpret_cast<const uint32_t*>(raw);
  const int n8 = lane >> 2, q = lane & 3;
  const int o = (ng < 3) ? ng * 8 + n8 : 24 + (n8 >> 2);
  const bool vo = (ng < 3) || !(n8 & 1);
  const int ob = li ? (o - 8 * grp) * 338 : o * 13 - 8 * grp * 338;
  const int si = li ? 13 : 338;
  uint32_t bias = 0;
  if (vo && ks == 42 && li == 0 && q == 0) bias = (uint32_t)__ldg(reinterpret_cast<const unsigned short*>(wout) + 2 * NF + o);
  uint32_t* dst = img32 + G0_BYTES / 4 + li * (L_BYTES / 4) + (ks * 4 + ng) * 64 + lane;
  mbar_wait(tbar, 0);
  const uint32_t e0 = T->ltab[8 * ks + q], e1 = T->ltab[8 * ks + 4 + q];
  const bool v0 = vo && (e0 & 32), v1 = vo && (e1 & 32);
  const int s0 = v0 ? ob + (e0 >> 6) * si + (e0 & 15) : 0, s1 = v1 ? ob + (e1 >> 6) * si + (e1 & 15) : 0;
  TL(33);
  mbar_wait(bar, 0);
  TL(36);
  uint32_t w0 = w32[s0], w1 = w32[s1];
  w0 = (e0 & 16) ? __funnelshift_l(w0, w0, 16) : w0;
  w1 = (e1 & 16) ? __funnelshift_l(w1, w1, 16) : w1;
  w0 = v0 ? w0 : 0u;
  w1 = v1 ? w1 : bias;
  st_img(dst, w0); st_img(dst + 32, w1);
  return (ld_back(dst) ^ w0) | (ld_back(dst + 32) ^ w1);
}
__device__ __forceinline__ float x1_val(const unsigned short* wh, uint32_t e) {
  const uint32_t a = e & 0xffff, b = e >> 16;
  const uint32_t x = wh[a == 0xffff ? 0 : a], y = wh[b == 0xffff ? 0 : b];
  return (a == 0xffff ? 0.f : __uint_as_float(x << 16)) + (b == 0xffff ? 0.f : __uint_as_float(y << 16));
}
__device__ __forceinline__ uint32_t x1_row(int ng, int ks, int lane, const unsigned char* raw, const StaticTabs* T, uint32_t bar, uint32_t tbar, uint32_t* img32) {
  if (ks >= 24) return 0;
  const int n8 = lane >> 2, q = lane & 3;
  const unsigned short* wh = reinterpret_cast<const unsigned short*>(raw) + n8 * (NF * NF);
  uint32_t* dst = img32 + ks * (G0_SLAB / 4) + ng * 64 + lane;
  mbar_wait(tbar, 0);
  const uint2 ea = *reinterpret_cast<const uint2*>(&T->x1tab[16 * ks + 2 * q]), eb = *reinterpret_cast<const uint2*>(&T->x1tab[16 * ks + 8 + 2 * q]);
  mbar_wait(bar, 0);
  const uint32_t w0 = pack_bf16(x1_val(wh, ea.x), x1_val(wh, ea.y)), w1 = pack_bf16(x1_val(wh, eb.x), x1_val(wh, eb.y));
  st_img(dst, w0); st_img(dst + 32, w1);
  return (ld_back(dst) ^ w0) | (ld_back(dst + 32) ^ w1);
}

constexpr int NHELP = 4;
constexpr int H_MS = 32 * QM_RS + 4;
constexpr int H_W5 = 0, H_W4 = 35328, H_W0 = 70656, H_TAB = 73472, H_B = 77824, H_M = 82944, H_XE = H_M + 8 * H_MS * 4, H_BAR = H_XE + 1536;
__device__ __forceinline__ int wf_off(int b, int h) { return (b >> 3) * 512 + (h >> 3) * 128 + (b & 7) * 16 + (h & 7) * 2; }
__device__ __forceinline__ void helper_role(int hk, const Params& P, unsigned char* smem, uint32_t sb) {
  const int t = threadIdx.x, warp = __shfl_sync(0xffffffffu, t >> 5, 0), lane = t & 31;
  const uint32_t d5bar = sb + H_BAR, d4bar = sb + H_BAR + 8, tbar = sb + H_BAR + 16;
  const unsigned char* wsb = reinterpret_cast<const unsigned char*>(P.ws);
  unsigned char* WB = smem + H_B;
  float* M = reinterpret_cast<float*>(smem + H_M);
  constexpr uint32_t W5B = WL_BYTES + ((5 * WL_BYTES) & 127), W4B = WL_BYTES + ((4 * WL_BYTES) & 127);
  if (warp < 3 && elect_one()) {
    mbar_init(sb + H_BAR + 8 * warp, 1);
    asm volatile("fence.mbarrier_init.release.cluster;" ::: "memory");
    if (warp == 0) {
      mbar_expect_tx(d5bar, W5B);
#pragma unroll
      for (int c = 0; c < 5; c++)
        bulk_g2s(sb + H_W5 + c * 8192, wsb + ((5 * WL_BYTES) & ~127) + c * 8192, c < 4 ? 8192u : W5B - 4 * 8192, d5bar);
    }
  }
  reinterpret_cast<uint32_t*>(WB)[t] = 0;
  __syncthreads();
  if (warp >= 5 && warp < 12 && elect_one()) {
    if (warp < 10) {
      const int c = warp - 5;
      if (c == 0) mbar_expect_tx(d4bar, W4B + (hk == 3 ? 2768 : 0));
      bulk_g2s(sb + H_W4 + c * 8192, wsb + ((4 * WL_BYTES) & ~127) + c * 8192, c < 4 ? 8192u : W4B - 4 * 8192, d4bar);
    } else if (warp == 10) {
      mbar_expect_tx(tbar, sizeof(StaticTabs));
      bulk_g2s(sb + H_TAB, P.tabs, sizeof(StaticTabs), tbar);
    } else if (hk == 3) {
      bulk_g2s(sb + H_W0, wsb + ((24 * NF * NF * 2) & ~127), 2768, d4bar);
    }
  }
  const unsigned short* wo16 = reinterpret_cast<const unsigned short*>(P.wout);
  uint32_t c5[13];
#pragma unroll
  for (int k = 0; k < 13; k++) c5[k] = __ldg(reinterpret_cast<const uint32_t*>(P.wout + 5 * NF) + k);
  unsigned short wv = 0;
  const int io0 = (hk < 3) ? 8 * hk : 24;
  if (t >= 352 && t < 352 + NF) wv = __ldg(wo16 + 4 * NF + t - 352);
  else if (t >= 384 && t < 392 && io0 + t - 384 < NF) wv = __ldg(wo16 + 3 * NF + io0 + t - 384);
  const StaticTabs* T = reinterpret_cast<const StaticTabs*>(smem + H_TAB);
  const int n8 = lane >> 2, q = lane & 3, g = n8;
  const int fil = (hk < 3) ? n8 : (n8 >> 2);
  const bool fx1 = (hk == 3) && !(n8 & 1);
  uint32_t* dst = reinterpret_cast<uint32_t*>(P.img) + (warp >> 1) * (G0_SLAB / 4) + (warp & 1) * 32 + (3 + hk) * 64 + lane;
  if (t >= 352 && t < 352 + NF) *reinterpret_cast<unsigned short*>(WB + wf_off(26, t - 352)) = wv;
  if (t >= 384 && t < 392) { M[(t - 384) * H_MS + O_ZERO] = 0.f; M[(t - 384) * H_MS + O_CONST] = __uint_as_float((uint32_t)wv << 16); }
  mbar_wait(d5bar, 0);
  if (t < 338) {
    const uint32_t* w5 = reinterpret_cast<const uint32_t*>(smem + H_W5 + ((5 * WL_BYTES) & 127)) + t;
    float s0 = 0.f, s1 = 0.f, s2 = 0.f, s3 = 0.f;
#pragma unroll
    for (int k = 0; k < 13; k++) {
      const uint32_t wa = w5[(2 * k) * 338], wb = w5[(2 * k + 1) * 338];
      const float ca = bflo(c5[k]), cb = bfhi(c5[k]);
      s0 = fmaf(ca, bflo(wa), s0); s1 = fmaf(ca, bfhi(wa), s1);
      s2 = fmaf(cb, bflo(wb), s2); s3 = fmaf(cb, bfhi(wb), s3);
    }
    const int h = (t * 79) >> 10, tp = t - 13 * h;
    *reinterpret_cast<bf16*>(WB + wf_off(2 * tp, h)) = __float2bfloat16(s0 + s2);
    *reinterpret_cast<bf16*>(WB + wf_off(2 * tp + 1, h)) = __float2bfloat16(s1 + s3);
  }
  fence_proxy_async();
  mbar_wait(tbar, 0);
  uint2 fot[3];
#pragma unroll
  for (int r = 0; r < 3; r++) fot[r] = *reinterpret_cast<const uint2*>(&T->otab[(warp + 16 * r) * 8 + q * 2]);
  mbar_wait(d4bar, 0);
  const int wgi = warp >> 2, il = 2 * wgi + ((warp >> 1) & 1), mt = warp & 1;
  const bool mma_wg = (hk < 3) || (wgi == 0);
  uint32_t a[2][4];
  if (mma_wg) {
    const unsigned short* A = reinterpret_cast<const unsigned short*>(smem + H_W4 + ((4 * WL_BYTES) & 127)) + (io0 + il) * NF + mt * 16 + g;
#pragma unroll
    for (int kk = 0; kk < 2; kk++) {
#pragma unroll
      for (int jj = 0; jj < 4; jj++) {
        const int k = kk * 16 + 2 * q + (jj >> 1) * 8, mo = (jj & 1) * 8;
        const int kc = (k < NF) ? k : 0;
        const uint32_t lo = A[kc * (NF * NF) + mo], hi = A[(kc + 1) * (NF * NF) + mo];
        a[kk][jj] = (k < NF) ? (lo | (hi << 16)) : 0u;
      }
    }
  }
  if (hk == 3) {
    const int u0 = (warp >= 4) ? t - 128 : -1;
    if (u0 >= 0) {
      const int sl = u0 >> 3, xl = (u0 >> 2) & 1, xq = u0 & 3;
      const uint2 xt = *reinterpret_cast<const uint2*>(&T->x1tab[sl * 8 + xq * 2]);
      const unsigned short* wh = reinterpret_cast<const unsigned short*>(smem + H_W0 + ((24 * NF * NF * 2) & 127)) + xl * (NF * NF);
      reinterpret_cast<uint32_t*>(smem + H_XE)[u0] = pack_bf16(x1_val(wh, xt.x), x1_val(wh, xt.y));
    }
  }
  __syncthreads();
  if (mma_wg) {
    float c[16];
    wg_fence();
    wgmma_rs_n32(c, a[0][0], a[0][1], a[0][2], a[0][3], make_desc(H_B, 128, 512, 0), 0);
    wgmma_rs_n32(c, a[1][0], a[1][1], a[1][2], a[1][3], make_desc(H_B + 256, 128, 512, 0), 1);
    wg_commit();
    wg_wait<0>();
    reg_fence(c);
    float* Mi = M + il * H_MS;
#pragma unroll
    for (int n = 0; n < 4; n++) {
      *reinterpret_cast<float2*>(&Mi[(mt * 16 + g) * QM_RS + n * 8 + 2 * q]) = make_float2(c[4 * n], c[4 * n + 1]);
      *reinterpret_cast<float2*>(&Mi[(mt * 16 + g + 8) * QM_RS + n * 8 + 2 * q]) = make_float2(c[4 * n + 2], c[4 * n + 3]);
    }
  }
  __syncthreads();
  uint32_t val[3], chk = 0;
#pragma unroll
  for (int r = 0; r < 3; r++) {
    const float* Mf = M + fil * H_MS;
    const float v0 = Mf[fot[r].x & 0xffff] + Mf[fot[r].x >> 16], v1 = Mf[fot[r].y & 0xffff] + Mf[fot[r].y >> 16];
    const uint32_t xe = reinterpret_cast<const uint32_t*>(smem + H_XE)[(warp + 16 * r) * 8 + (n8 >> 2) * 4 + q];
    val[r] = fx1 ? xe : pack_bf16(v0, v1);
    st_img(dst + r * 8 * (G0_SLAB / 4), val[r]);
  }
#pragma unroll
  for (int r = 0; r < 3; r++) chk |= ld_back(dst + r * 8 * (G0_SLAB / 4)) ^ val[r];
  if (__any_sync(0xffffffffu, chk != 0)) __trap();
  __syncthreads();
  if (t == 0) asm volatile("red.relaxed.gpu.global.add.u32 [%0], 32;" ::"l"(P.ctr) : "memory");
}

template <int S>
__device__ __forceinline__ uint32_t l_prod(const uint32_t (&vp)[4], const uint32_t (&X)[13]) {
  if constexpr (S < 78) {
    constexpr int a = S / 13, t = S % 13;
    return (a & 1) ? mul_hi(vp[a >> 1], X[t]) : mul_lo(vp[a >> 1], X[t]);
  } else if constexpr (S < 85) {
    constexpr int k = S - 78;
    constexpr int t = (k < 3) ? k : (k < 6 ? k + 3 : 12);
    return mul_lo(vp[3], X[t]);
  } else {
    return 0x00003F80u;
  }
}
template <int S>
__device__ __forceinline__ uint32_t g0_prod(const uint32_t (&X)[13], uint32_t selU, uint32_t selV) {
  if constexpr (S < 30) {
    constexpr int d = S / 6 + 1, a = (S % 6) >> 1;
    return (S & 1) ? mul_hi(X[a], X[a + d]) : mul_lo(X[a], X[a + d]);
  } else if constexpr (S < 33) {
    return mul_ew(X[S - 30], X[S - 24]);
  } else if constexpr (S < 35) {
    return mul_ew(X[S - 33], X[S - 33]);
  } else if constexpr (S == 35) {
    return mul_ew(__byte_perm(X[0], X[1], 0x5410), __byte_perm(X[0], X[1], 0x7632));
  } else if constexpr (S == 36) {
    return mul_lo(X[2], X[2]);
  } else if constexpr (S == 37) {
    return mul_hi(X[2], X[2]);
  } else if constexpr (S < 44) {
    constexpr int a = (S - 38) >> 1;
    return ((S - 38) & 1) ? mul_hi(X[12], X[a]) : mul_lo(X[12], X[a]);
  } else if constexpr (S < 47) {
    return X[S - 44];
  } else {
    return mul_ew(__byte_perm(X[12], 0x3F803F80u, selU), __byte_perm(X[12], 0x3F803F80u, selV));
  }
}

constexpr int NBK = 4;

template <int KS, int KE>
__device__ __forceinline__ void l_fill(uint32_t (*A)[4], const uint32_t (&vp)[2][4], const uint32_t (&X)[2][13]) {
  A[0][0] = l_prod<2 * KS>(vp[0], X[0]);
  A[0][1] = l_prod<2 * KS>(vp[1], X[1]);
  A[0][2] = l_prod<2 * KS + 1>(vp[0], X[0]);
  A[0][3] = l_prod<2 * KS + 1>(vp[1], X[1]);
  if constexpr (KS + 1 < KE) l_fill<KS + 1, KE>(A + 1, vp, X);
}
template <int KS, int OFF>
__device__ __forceinline__ void layer_rec(float (&d)[16], const uint32_t (&vp)[2][4], const uint32_t (&X)[2][13], uint64_t dk) {
  constexpr int KE = (KS + NBK < L_KS) ? KS + NBK : L_KS;
  uint32_t A[NBK][4];
  l_fill<KS, KE>(A, vp, X);
  wg_fence();
#pragma unroll
  for (int k = 0; k < KE - KS; k++)
    wgmma_rs_n32(d, A[k][0], A[k][1], A[k][2], A[k][3], dk + (uint64_t)((OFF + (KS + k) * L_SLAB) >> 4), (KS + k) > 0);
  wg_commit();
  if constexpr (KE < L_KS) {
    wg_wait<1>();
    layer_rec<KE, OFF>(d, vp, X, dk);
  }
}
template <int OFF, int NK>
__device__ __forceinline__ void layer_first(float (&d)[16], const uint32_t (&vp)[2][4], const uint32_t (&X)[2][13], uint64_t dk) {
  uint32_t A[NK][4];
  l_fill<0, NK>(A, vp, X);
  wg_fence();
#pragma unroll
  for (int k = 0; k < NK; k++) wgmma_rs_n32(d, A[k][0], A[k][1], A[k][2], A[k][3], dk + (uint64_t)((OFF + k * L_SLAB) >> 4), k > 0);
  wg_commit();
}
template <int KS, int KE>
__device__ __forceinline__ void g0_fill(uint32_t (*A)[4], const uint32_t (&X)[2][13], uint32_t selU, uint32_t selV) {
  A[0][0] = g0_prod<2 * KS>(X[0], selU, selV);
  A[0][1] = g0_prod<2 * KS>(X[1], selU, selV);
  A[0][2] = g0_prod<2 * KS + 1>(X[0], selU, selV);
  A[0][3] = g0_prod<2 * KS + 1>(X[1], selU, selV);
  if constexpr (KS + 1 < KE) g0_fill<KS + 1, KE>(A + 1, X, selU, selV);
}
template <int B0>
__device__ __forceinline__ void g0_rec(float (&d)[28], const uint32_t (&X)[2][13], uint32_t selU, uint32_t selV, uint64_t dk, uint32_t bar2, bool first) {
  constexpr int KS = B0 * NBK;
  if constexpr (KS == 8) { if (first) mbar_wait(bar2, 0); }
  if constexpr (KS == 16) { if (first) mbar_wait(bar2 + 8, 0); }
  constexpr int KE = (KS + NBK < G0_KS) ? KS + NBK : G0_KS;
  uint32_t A[NBK][4];
  g0_fill<KS, KE>(A, X, selU, selV);
  wg_fence();
#pragma unroll
  for (int k = 0; k < KE - KS; k++)
    wgmma_rs_n56(d, A[k][0], A[k][1], A[k][2], A[k][3], dk + (uint64_t)((OFF_G0 + (KS + k) * G0_SLAB) >> 4), (KS + k) > 0);
  wg_commit();
  if constexpr (KE < G0_KS) {
    wg_wait<1>();
    g0_rec<B0 + 1>(d, X, selU, selV, dk, bar2, first);
  }
}

__device__ __forceinline__ void ldsm_x4_t(uint32_t addr, uint32_t& r0, uint32_t& r1, uint32_t& r2, uint32_t& r3) {
  asm volatile("ldmatrix.sync.aligned.m8n8.x4.trans.shared.b16 {%0,%1,%2,%3}, [%4];"
               : "=r"(r0), "=r"(r1), "=r"(r2), "=r"(r3) : "r"(addr) : "memory");
}
__device__ __forceinline__ void ldsm_x2_t(uint32_t addr, uint32_t& r0, uint32_t& r1) {
  asm volatile("ldmatrix.sync.aligned.m8n8.x2.trans.shared.b16 {%0,%1}, [%2];" : "=r"(r0), "=r"(r1) : "r"(addr) : "memory");
}
__device__ __forceinline__ float tanh_fast(float x) { float y; asm("tanh.approx.f32 %0, %1;" : "=f"(y) : "f"(x)); return y; }

__device__ __forceinline__ uint32_t gelu2_pair(float lo, float hi, uint32_t bias) {
  uint32_t x = pack_bf16(lo, hi), t, u;
  asm("add.rn.bf16x2 %0, %0, %1;" : "+r"(x) : "r"(bias));
  asm("mul.rn.bf16x2 %0, %1, %1;" : "=r"(t) : "r"(x));
  asm("fma.rn.bf16x2 %0, %0, %1, %2;" : "+r"(t) : "r"(0x3D123D12u), "r"(0x3F4C3F4Cu));
  asm("mul.rn.bf16x2 %0, %1, %2;" : "=r"(u) : "r"(x), "r"(t));
  asm("tanh.approx.bf16x2 %0, %0;" : "+r"(u));
  asm("fma.rn.bf16x2 %0, %1, %0, %1;" : "+r"(u) : "r"(x));
  return u;
}

__device__ __forceinline__ void ldsm_x4(uint32_t addr, uint32_t (&r)[4]) {
  asm volatile("ldmatrix.sync.aligned.m8n8.x4.shared.b16 {%0,%1,%2,%3}, [%4];"
               : "=r"(r[0]), "=r"(r[1]), "=r"(r[2]), "=r"(r[3]) : "r"(addr) : "memory");
}
__device__ __forceinline__ uint32_t lds_u16(uint32_t addr) {
  unsigned short v;
  asm volatile("ld.shared.u16 %0, [%1];" : "=h"(v) : "r"(addr) : "memory");
  return v;
}
__device__ __forceinline__ uint32_t lds_u32(uint32_t addr) {
  uint32_t v;
  asm volatile("ld.shared.u32 %0, [%1];" : "=r"(v) : "r"(addr) : "memory");
  return v;
}

__global__ void __launch_bounds__(512, 1)
main_kernel(const __grid_constant__ Params P, const __grid_constant__ TmaMaps tms) {
  extern __shared__ __align__(1024) unsigned char smem[];
  const uint32_t sb = smem_u32(smem);
  const int tid = threadIdx.x, warp = __shfl_sync(0xffffffffu, tid >> 5, 0), lane = tid & 31;
  if (blockIdx.x < NHELP) {
    helper_role(blockIdx.x, P, smem, sb);
    return;
  }
  const int cta = blockIdx.x - NHELP, nq = cta & 3, grp = cta >> 2;
  const uint2 role = P.role[cta];
  const uint32_t bar0 = sb + OFF_BAR;
  auto BAR = [&](int i) { return bar0 + 8 * i; };
  const int wg = warp >> 2, w4 = warp & 3, g = lane >> 2, q = lane & 3;
  const uint64_t dk = P.dk;
  const long long tl_c0 = TL_START();
  TL_INIT();
  TL_PUT0(tl_c0);

  if (tid < 256) {
    const unsigned char* isrc = reinterpret_cast<const unsigned char*>(P.idx + grp * 128 * NF);
#pragma unroll
    for (int k = 0; k < 4; k++) {
      const int c = tid + 256 * k;
      if (c < 832) cp_async16(sb + OFF_IDX + c * 16, isrc + c * 16);
    }
    asm volatile("cp.async.commit_group;" ::: "memory");
#pragma unroll
    for (int k = 0; k < 8; k++) {
      const int c = tid + 256 * k;
      if (c < 2000) cp_async16(sb + OFF_TAB + ((c ^ ((c >> 3) & 1)) << 4), reinterpret_cast<const unsigned char*>(P.table) + c * 16);
    }
    asm volatile("cp.async.commit_group;" ::: "memory");
  }
  if (elect_one()) {
    mbar_init(BAR(warp), (warp == BAR_W1FREE || warp == BAR_W1DONE) ? 2 : 1);
    if (warp < NBAR - 16)
      mbar_init(BAR(16 + warp), (16 + warp == BAR_X0) ? 256 : (16 + warp == BAR_SETUP) ? SETUP_WARPS : (16 + warp == BAR_TABS) ? 224 : 1);
    asm volatile("fence.mbarrier_init.release.cluster;" ::: "memory");
  }
  __syncthreads();
  TL(26);

  if (warp == 15) {
    if (elect_one()) {
      mbar_expect_tx(BAR(BAR_STAB), sizeof(StaticTabs));
      bulk_g2s(sb + OFF_STAB, P.tabs, sizeof(StaticTabs), BAR(BAR_STAB));
      if ((sb & 0x3FFFF) != SMEM_BASE) __trap();
      const CUtensorMap* tm0 = &tms.m[nq];
      asm volatile("prefetch.tensormap [%0];" ::"l"(tm0) : "memory");
#pragma unroll
      for (int st = 0; st < W1_STAGES; st++) {
        if (st == 1 && (role.x >> 24) < 5) mbar_wait(BAR(BAR_Q), 0);
        mbar_expect_tx(BAR(BAR_W1FULL + st), W1_STAGE_BYTES);
        tma_2d(sb + w1_off(st), tm0, 0, st * 64, BAR(BAR_W1FULL + st));
        tma_2d(sb + w1_off(st) + 8192, tm0, 64, st * 64, BAR(BAR_W1FULL + st));
      }
      TLP(22);
      mbar_wait(BAR(BAR_EPOCH), 0);
      TLP(23);
      const unsigned target = lds_u32(sb + OFF_EPOCH) << 8;
      {
        unsigned v;
        uint32_t it = 0;
#pragma unroll 1
        do {
          asm volatile("ld.relaxed.gpu.global.u32 %0, [%1];" : "=r"(v) : "l"(P.ctr) : "memory");
          if (++it > (1u << 22)) __trap();
        } while ((int)(v - target) < 0);
        asm volatile("fence.acq_rel.cta;" ::: "memory");
      }
      fence_proxy_async_all();
      mbar_wait(BAR(BAR_X0), 0);
      TLP(24);
      mbar_expect_tx(BAR(BAR_IMG + 0), G0_BYTES / 3);
      mbar_expect_tx(BAR(BAR_G0B), G0_BYTES / 3);
      mbar_expect_tx(BAR(BAR_G0B + 1), G0_BYTES / 3);
#pragma unroll
      for (int i = 0; i < 6; i++)
        bulk_g2s(sb + OFF_G0 + i * (G0_BYTES / 6), P.img + i * (G0_BYTES / 6), G0_BYTES / 6, i < 2 ? BAR(BAR_IMG + 0) : BAR(BAR_G0B + (i - 2) / 2));
      mbar_wait(BAR(BAR_W1FREE), 0);
      mbar_expect_tx(BAR(BAR_IMG + 2), L_BYTES);
#pragma unroll
      for (int i = 0; i < 4; i++)
        bulk_g2s(sb + OFF_LB + i * (L_BYTES / 4), P.img + G0_BYTES + L_BYTES + i * (L_BYTES / 4), L_BYTES / 4, BAR(BAR_IMG + 2));
      mbar_wait(BAR(BAR_W1DONE), 0);
      mbar_expect_tx(BAR(BAR_IMG + 1), L_BYTES);
      mbar_expect_tx(BAR(BAR_IMG + 3), L_BYTES);
#pragma unroll
      for (int i = 0; i < 2; i++)
        bulk_g2s(sb + OFF_LA + i * (L_BYTES / 2), P.img + G0_BYTES + i * (L_BYTES / 2), L_BYTES / 2, BAR(BAR_IMG + 1));
#pragma unroll
      for (int i = 0; i < 2; i++)
        bulk_g2s(sb + OFF_LC + i * (L_BYTES / 2), P.img + G0_BYTES + 2 * L_BYTES + i * (L_BYTES / 2), L_BYTES / 2, BAR(BAR_IMG + 3));
      TLP(25);
    }
    __syncwarp();
    mbar_wait(BAR(BAR_X0), 0);
    mbar_wait(BAR(BAR_TABS), 0);
  } else if (wg < 2) {
    asm volatile("cp.async.wait_group 1;" ::: "memory");
    named_bar(1, 256);
#pragma unroll
    for (int k = 0; k < 7; k++) {
      const int p = tid + 256 * k;
      if (p < 64 * NF) {
        const uint2 v = reinterpret_cast<const uint2*>(smem + OFF_IDX)[p];
        const uint32_t o0 = v.x * 32 + ((v.x >> 2) & 1) * 16, o1 = v.y * 32 + ((v.y >> 2) & 1) * 16;
        reinterpret_cast<uint32_t*>(smem + OFF_XOFF)[p] = o0 | (o1 << 16);
      }
    }
    TL(1);
    asm volatile("cp.async.wait_all;" ::: "memory");
    mbar_arrive(BAR(BAR_X0));
    mbar_wait(BAR(BAR_X0), 0);
    TL(3);
    float acc[56];
    {
      const uint32_t xo = sb + OFF_XOFF + (wg * 64 + w4 * 16 + (lane & 15)) * 52;
      const uint32_t tb = sb + OFF_TAB, hx = (lane >> 4) << 4;
      const uint64_t db0 = P.dmn;
      uint32_t A[3][2][4];
#pragma unroll
      for (int pr = 0; pr < 2; pr++) {
        const uint32_t oa = lds_u32(xo + 4 * pr);
        ldsm_x4(tb + ((oa & 0xffff) ^ hx), A[pr][0]); ldsm_x4(tb + ((oa >> 16) ^ hx), A[pr][1]);
      }
#pragma unroll
      for (int pr = 0; pr < 13; pr++) {
        const int st = pr >> 1;
        uint32_t oa = 0;
        if (pr + 2 < 13) oa = lds_u32(xo + 4 * (pr + 2));
        if (!(pr & 1)) mbar_wait(BAR(BAR_W1FULL + st), 0);
        if (pr == 0) TL(28); if (pr == 6) TL(29);
        const uint64_t db = db0 + (uint64_t)((w1_off(st) + (pr & 1) * 4096) >> 4);
        wg_fence();
        wgmma_rs_n112_tb(acc, A[pr % 3][0][0], A[pr % 3][0][1], A[pr % 3][0][2], A[pr % 3][0][3], db, pr > 0);
        wgmma_rs_n112_tb(acc, A[pr % 3][1][0], A[pr % 3][1][1], A[pr % 3][1][2], A[pr % 3][1][3], db + (2048 >> 4), 1);
        wg_commit();
        wg_wait<1>();
        if (pr == 4 && (tid & 127) == 0) mbar_arrive(BAR(BAR_W1FREE));
        if (pr + 2 < 13) { ldsm_x4(tb + ((oa & 0xffff) ^ hx), A[(pr + 2) % 3][0]); ldsm_x4(tb + ((oa >> 16) ^ hx), A[(pr + 2) % 3][1]); }
      }
      wg_wait<0>();
      reg_fence(acc);
      if ((tid & 127) == 0) mbar_arrive(BAR(BAR_W1DONE));
    }
    TL(4);
    float dot[4];
    {
      mbar_wait(BAR(BAR_TABS), 0);
      uint32_t bb[16];
      const uint4* bp = reinterpret_cast<const uint4*>(smem + OFF_BW + q * 64);
#pragma unroll
      for (int i = 0; i < 4; i++) { const uint4 v = bp[i]; bb[4 * i] = v.x; bb[4 * i + 1] = v.y; bb[4 * i + 2] = v.z; bb[4 * i + 3] = v.w; }
      uint32_t H[14][2];
#pragma unroll
      for (int c = 0; c < 14; c++) {
        H[c][0] = gelu2_pair(acc[4 * c], acc[4 * c + 1], bb[c]);
        H[c][1] = gelu2_pair(acc[4 * c + 2], acc[4 * c + 3], bb[c]);
      }
      wg_fence();
#pragma unroll
      for (int j = 0; j < 7; j++)
        wgmma_rs_n8(dot, H[2 * j][0], H[2 * j][1], H[2 * j + 1][0], H[2 * j + 1][1], dk + (uint64_t)((OFF_W2 + j * 256) >> 4), j > 0);
      wg_commit();
      wg_wait<0>();
      reg_fence(dot);
    }
    __syncwarp();
    mbar_wait(BAR(BAR_EPOCH), 0);
    if (q == 0) {
      const unsigned epoch = lds_u32(sb + OFF_EPOCH);
#pragma unroll
      for (int r = 0; r < 2; r++) {
        const int row = wg * 64 + w4 * 16 + g + 8 * r;
        const unsigned long long pk = ((unsigned long long)epoch << 32) | (unsigned long long)__float_as_uint(dot[2 * r]);
        asm volatile("st.relaxed.gpu.global.u64 [%0], %1;" ::"l"(P.part + cta * 128 + row), "l"(pk) : "memory");
      }
    }
    __syncwarp();
  } else {
    const int t = tid - 256;
    const bool is_arr = (t == 192);
    unsigned ctr0 = 0;
    if (is_arr) asm volatile("ld.relaxed.gpu.global.u32 %0, [%1];" : "=r"(ctr0) : "l"(P.ctr) : "memory");
    {
      const int kind = role.x >> 24, w = warp - 8, rgrp = (role.y >> 24) & 15, rj = role.y >> 28;
      const unsigned char* wsb = reinterpret_cast<const unsigned char*>(P.ws);
      if (kind < 5 && elect_one()) {
        const uint32_t bytes = role.y & 0xffff;
        const uint32_t o = w * 8192;
        if (w == 0) mbar_expect_tx(BAR(BAR_Q), bytes);
        if (o < bytes) bulk_g2s(sb + OFF_G0 + o, wsb + (role.x & 0xffffff) + o, min(bytes - o, 8192u), BAR(BAR_Q));
      }
      TL(40);
      __syncwarp();
      const StaticTabs* T = reinterpret_cast<const StaticTabs*>(smem + OFF_STAB);
      uint32_t* img32 = reinterpret_cast<uint32_t*>(P.img);
      const unsigned char* raw = smem + OFF_G0 + ((role.y >> 16) & 127);
      uint32_t chk = 0;
      if (kind < 3) chk = layer_row(kind, rgrp, rj * SETUP_WARPS + w, lane, raw, T, BAR(BAR_Q), BAR(BAR_STAB), P.wout, img32);
      else if (kind == 3) chk = x1_row(rgrp, rj * SETUP_WARPS + w, lane, raw, T, BAR(BAR_Q), BAR(BAR_STAB), img32);
      if (__any_sync(0xffffffffu, chk != 0)) __trap();
      if (lane == 0) mbar_arrive(BAR(BAR_SETUP));
    }
    TL(1);
    if (is_arr) {
      asm volatile("" : "+r"(ctr0));
      *reinterpret_cast<volatile unsigned*>(smem + OFF_EPOCH) = (ctr0 >> 8) + 1;
      mbar_wait(BAR(BAR_SETUP), 0);
      TLA(30);
      asm volatile("red.relaxed.gpu.global.add.u32 [%0], 1;" ::"l"(P.ctr) : "memory");
      mbar_arrive(BAR(BAR_EPOCH));
      TLA(31);
    }
    __syncwarp();
    {
      const int c0 = (nq >> 1) * 208 + (nq & 1) * 96, nw = (nq & 1) ? 112 : 96;
      if (t < 56) {
        const int n = 2 * t;
        const uint32_t v = (n < nw) ? __ldg(reinterpret_cast<const uint32_t*>(P.b1 + c0 + n)) : 0u;
        reinterpret_cast<uint32_t*>(smem + OFF_BW)[(t & 3) * 16 + (t >> 2)] = v;
      }
      if (t >= 64 && t < 64 + 112) {
        const int k = t - 64;
        const float w = (k < nw) ? 0.5f * bf2f(__ldg(P.w2 + c0 + k)) : 0.f;
        unsigned char* base = smem + OFF_W2 + (k >> 4) * 256 + ((k >> 3) & 1) * 128;
        *reinterpret_cast<bf16*>(base + (k & 7) * 2) = __float2bfloat16(w);
        if ((k & 7) == 0) {
#pragma unroll
          for (int r = 1; r < 8; r++) *reinterpret_cast<uint4*>(base + r * 16) = make_uint4(0, 0, 0, 0);
        }
      }
      fence_proxy_async();
    }
    if (t >= 128 && t < 192) {
      int u = t - 128, l = u >> 5, qq = (u >> 3) & 3, a = u & 7;
      float wtv = 0.f;
      if (a < 6) wtv = bf2f(__ldg(P.wout + l * NF + 8 * (a >> 1) + 2 * qq + (a & 1)));
      else if (a == 6 && !(qq & 1)) wtv = bf2f(__ldg(P.wout + l * NF + 24 + (qq >> 1)));
      reinterpret_cast<float*>(smem + OFF_WTAB)[u] = wtv;
    }
    mbar_arrive(BAR(BAR_TABS));
    TL(2);
    mbar_wait(BAR(BAR_X0), 0);
    mbar_wait(BAR(BAR_TABS), 0);
  }

  TL(5);
  const uint32_t selU = (q == 0) ? 0x1010u : (q == 1) ? 0x3232u : (q == 2) ? 0x3210u : 0x7654u;
  const uint32_t selV = (q < 2) ? 0x3210u : 0x7654u;
  uint32_t bo_raw = __ldg(reinterpret_cast<const unsigned short*>(P.bout));
  mbar_wait(BAR(BAR_EPOCH), 0);
  mbar_wait(BAR(BAR_STAB), 0);
  const unsigned epoch = lds_u32(sb + OFF_EPOCH);

  uint32_t X[2][13];
  auto load_x = [&](int sl) {
    const uint4 o = *reinterpret_cast<const uint4*>(smem + OFF_LOFF + lane * 16);
    const uint32_t xo = sb + OFF_XOFF + sl * 52;
    const uint32_t tb = sb + OFF_TAB, hx = ((lane >> 3) & 1) << 4;
    const uint32_t a0 = lds_u16(xo + (o.x & 0xffff)), a1 = lds_u16(xo + (o.x >> 16));
    const uint32_t a2 = lds_u16(xo + (o.y & 0xffff)), a3 = lds_u16(xo + (o.y >> 16));
    const uint32_t a4 = lds_u16(xo + (o.z & 0xffff)), a5 = lds_u16(xo + (o.z >> 16));
    const uint32_t a6 = lds_u16(xo + (o.w & 0xffff));
    ldsm_x4_t(tb + (a0 ^ hx), X[0][0], X[1][0], X[0][1], X[1][1]);
    ldsm_x4_t(tb + (a1 ^ hx), X[0][2], X[1][2], X[0][3], X[1][3]);
    ldsm_x4_t(tb + (a2 ^ hx), X[0][4], X[1][4], X[0][5], X[1][5]);
    ldsm_x4_t(tb + (a3 ^ hx), X[0][6], X[1][6], X[0][7], X[1][7]);
    ldsm_x4_t(tb + (a4 ^ hx), X[0][8], X[1][8], X[0][9], X[1][9]);
    ldsm_x4_t(tb + (a5 ^ hx), X[0][10], X[1][10], X[0][11], X[1][11]);
    ldsm_x2_t(tb + (a6 ^ hx), X[0][12], X[1][12]);
  };
  load_x(nq * 32 + wg * 4 + w4);
#pragma unroll 1
  for (int it = 0; it < 2; it++) {
    const int sl = nq * 32 + (wg + 4 * it) * 4 + w4;
    float S = 0.f;
    uint32_t vx[2][4], vg[2][4];
    {
      float a0[28];
      if (it == 0) mbar_wait(BAR(BAR_IMG + 0), 0);
      if (it < 2) TL(6 + it * 8);
      g0_rec<0>(a0, X, selU, selV, dk, BAR(BAR_G0B), it == 0);
      wg_wait<0>();
      reg_fence(a0);
      const float4* wt = reinterpret_cast<const float4*>(smem + OFF_WTAB) + q * 2;
      float4 wa = wt[0], wb = wt[1];
#pragma unroll
      for (int r = 0; r < 2; r++) {
        S = fmaf(wa.x, a0[0 + 2 * r], S); S = fmaf(wa.y, a0[1 + 2 * r], S);
        S = fmaf(wa.z, a0[4 + 2 * r], S); S = fmaf(wa.w, a0[5 + 2 * r], S);
        S = fmaf(wb.x, a0[8 + 2 * r], S); S = fmaf(wb.y, a0[9 + 2 * r], S);
        S = fmaf(wb.z, a0[24 + 2 * r], S);
#pragma unroll
        for (int c = 0; c < 3; c++) {
          vx[r][c] = pack_bf16(a0[4 * c + 2 * r], a0[4 * c + 2 * r + 1]);
          vg[r][c] = pack_bf16(a0[12 + 4 * c + 2 * r], a0[12 + 4 * c + 2 * r + 1]);
        }
        vx[r][3] = pack_bf16(a0[24 + 2 * r], 0.f);
        vg[r][3] = pack_bf16(a0[24 + 2 * r + 1], 0.f);
      }
    }
    float g3[16], xa[16];
    if (it < 2) TL(7 + it * 8);
    if (it == 0) {
      mbar_wait(BAR(BAR_IMG + 2), 0);
      mbar_wait(BAR(BAR_IMG + 1), 0);
      mbar_wait(BAR(BAR_IMG + 3), 0);
    }
    if (it < 2) TL(8 + it * 8);
    layer_rec<0, OFF_LB>(xa, vx, X, dk);
    if (it < 2) TL(9 + it * 8);
    wg_wait<1>();
    layer_first<OFF_LA, 3>(g3, vg, X, dk);
    wg_wait<1>();
    reg_fence(xa);
    {
      const float4* wt = reinterpret_cast<const float4*>(smem + OFF_WTAB) + 8 + q * 2;
      float4 wa = wt[0], wb = wt[1];
#pragma unroll
      for (int r = 0; r < 2; r++) {
        S = fmaf(wa.x, xa[0 + 2 * r], S); S = fmaf(wa.y, xa[1 + 2 * r], S);
        S = fmaf(wa.z, xa[4 + 2 * r], S); S = fmaf(wa.w, xa[5 + 2 * r], S);
        S = fmaf(wb.x, xa[8 + 2 * r], S); S = fmaf(wb.y, xa[9 + 2 * r], S);
        S = fmaf(wb.z, xa[12 + 2 * r], S);
#pragma unroll
        for (int c = 0; c < 3; c++) vx[r][c] = pack_bf16(xa[4 * c + 2 * r], xa[4 * c + 2 * r + 1]);
        vx[r][3] = pack_bf16(xa[12 + 2 * r], 0.f);
      }
    }
    layer_rec<3, OFF_LA>(g3, vg, X, dk);
    if (it < 2) TL(10 + it * 8);
    wg_wait<1>();
    const unsigned long long* pp = P.part + (grp * 4 + (lane & 3)) * 128 + sl;
    unsigned long long pk;
    asm volatile("ld.relaxed.gpu.global.u64 %0, [%1];" : "=l"(pk) : "l"(pp) : "memory");
    float xc[16];
    layer_rec<0, OFF_LC>(xc, vx, X, dk);
    if (it == 0) load_x(sl + 16);
    wg_wait<0>();
    reg_fence(xc);
    reg_fence(g3);
    {
      float Se = 0.f;
#pragma unroll
      for (int r = 0; r < 2; r++) {
#pragma unroll
        for (int c = 0; c < 3; c++) {
          S = fmaf(g3[4 * c + 2 * r], xc[4 * c + 2 * r], S);
          S = fmaf(g3[4 * c + 2 * r + 1], xc[4 * c + 2 * r + 1], S);
        }
        Se = fmaf(g3[12 + 2 * r], xc[12 + 2 * r], Se);
      }
      if (!(q & 1)) S += Se;
    }
#pragma unroll
    for (int o = 16; o > 0; o >>= 1) S += __shfl_xor_sync(0xffffffffu, S, o);
    if (it < 2) TL(12 + it * 8);
    {
      uint32_t spin = 0;
      while (lane < 4 && (unsigned)(pk >> 32) != epoch) {
        asm volatile("ld.relaxed.gpu.global.u64 %0, [%1];" : "=l"(pk) : "l"(pp) : "memory");
        if (++spin > (1u << 24)) __trap();
      }
      __syncwarp();
      float dv = __uint_as_float((unsigned)pk);
      float d01 = dv + __shfl_xor_sync(0xffffffffu, dv, 1);
      float dsum = d01 + __shfl_xor_sync(0xffffffffu, d01, 2);
      asm volatile("" : "+r"(bo_raw));
      if (lane == 0) P.out[grp * 128 + sl] = __float2bfloat16(S + dsum + __uint_as_float(bo_raw << 16));
    }
    __syncwarp();
    if (it < 2) TL(13 + it * 8);
  }
  TL_DUMP();
}

__global__ void __launch_bounds__(128) fallback_kernel(const int* __restrict__ idx, const bf16* __restrict__ table, const bf16* __restrict__ ws,
                                                       const bf16* __restrict__ wout, const bf16* __restrict__ w1, const bf16* __restrict__ b1,
                                                       const bf16* __restrict__ w2, const bf16* __restrict__ bout, bf16* __restrict__ out) {
  __shared__ float x0[416], xa[416], xb[416], red[128];
  const int b = blockIdx.x, t = threadIdx.x;
  for (int i = t; i < 416; i += 128) { x0[i] = bf2f(table[idx[b * NF + i / 16] * 16 + (i & 15)]); xa[i] = x0[i]; }
  __syncthreads();
  float acc = 0.f;
  float* cur = xa;
  float* nxt = xb;
  for (int l = 0; l < 6; l++) {
    for (int o = t; o < 416; o += 128) {
      const int h = o >> 4, d = o & 15;
      const bf16* w = ws + (l * NF + h) * NF * NF;
      float s = 0.f;
      for (int i = 0; i < NF; i++) {
        float u = 0.f;
        for (int j = 0; j < NF; j++) u = fmaf(bf2f(w[i * NF + j]), x0[j * 16 + d], u);
        s = fmaf(u, cur[i * 16 + d], s);
      }
      nxt[o] = s;
      acc = fmaf(s, bf2f(wout[l * NF + h]), acc);
    }
    __syncthreads();
    float* tmp = cur; cur = nxt; nxt = tmp;
  }
  for (int n = t; n < 416; n += 128) {
    float h = 0.f;
    for (int k = 0; k < 416; k++) h = fmaf(x0[k], bf2f(w1[k * 416 + n]), h);
    h += bf2f(b1[n]);
    const float gl = 0.5f * h * (1.f + tanhf(0.7978845608028654f * (h + 0.044715f * h * h * h)));
    acc = fmaf(gl, bf2f(w2[n]), acc);
  }
  red[t] = acc;
  __syncthreads();
  for (int o = 64; o > 0; o >>= 1) { if (t < o) red[t] += red[t + o]; __syncthreads(); }
  if (t == 0) out[b] = __float2bfloat16(red[0] + bf2f(bout[0]));
}

typedef CUresult (*EncodeFn)(CUtensorMap*, CUtensorMapDataType, cuuint32_t, void*, const cuuint64_t*, const cuuint64_t*,
                             const cuuint32_t*, const cuuint32_t*, CUtensorMapInterleave, CUtensorMapSwizzle,
                             CUtensorMapL2promotion, CUtensorMapFloatOOBfill);

extern "C" void kernel_launch(void* const* d_in, const int* in_sizes, int n_in, void* d_out, int out_size) {
  const int* idx = (const int*)d_in[0];
  const bf16* table = (const bf16*)d_in[1];
  const bf16* ws = (const bf16*)d_in[2];
  const bf16* wout = (const bf16*)d_in[3];
  const bf16* w1 = (const bf16*)d_in[4];
  const bf16* b1 = (const bf16*)d_in[5];
  const bf16* w2 = (const bf16*)d_in[6];
  const bf16* bo = (const bf16*)d_in[7];
  bf16* out = (bf16*)d_out;

  static EncodeFn enc = nullptr;
  static Params P;
  static int n_sm = 0;
  if (!n_sm) {
    int dev = 0;
    cudaGetDevice(&dev);
    cudaDeviceGetAttribute(&n_sm, cudaDevAttrMultiProcessorCount, dev);
  }
  if (n_sm < NCTA + NHELP) {
    fallback_kernel<<<4096, 128, 0, cudaStreamPerThread>>>(idx, table, ws, wout, w1, b1, w2, bo, out);
    return;
  }
  if (!enc) {
    void* fn = nullptr;
    cudaDriverEntryPointQueryResult qr;
    cudaGetDriverEntryPoint("cuTensorMapEncodeTiled", &fn, cudaEnableDefault, &qr);
    enc = (EncodeFn)fn;
    cudaFuncSetAttribute(main_kernel, cudaFuncAttributeMaxDynamicSharedMemorySize, LAUNCH_SMEM);
    void* p;
    cudaGetSymbolAddress(&p, g_img); P.img = (unsigned char*)p;
    cudaGetSymbolAddress(&p, g_part); P.part = (unsigned long long*)p;
    cudaGetSymbolAddress(&p, g_ctr); P.ctr = (unsigned*)p;
    cudaGetSymbolAddress(&p, g_tabs); P.tabs = p;
    P.dk = make_desc(0, 128, 256, 0);
    P.dmn = make_desc(0, 8192, 1024, 1);
    for (int c = 0; c < NCTA; c++) P.role[c] = make_role(c);
  }
  P.idx = idx; P.table = table; P.ws = ws; P.wout = wout; P.b1 = b1; P.w2 = w2; P.bout = bo; P.out = out;
  TmaMaps tms;
  for (int h = 0; h < 4; h++) {
    const int c0 = (h >> 1) * 208 + (h & 1) * 96, nw = (h & 1) ? 112 : 96;
    cuuint64_t dims[2] = {(cuuint64_t)nw, 416};
    cuuint64_t strides[1] = {832};
    cuuint32_t box[2] = {64, 64};
    cuuint32_t es[2] = {1, 1};
    enc(&tms.m[h], CU_TENSOR_MAP_DATA_TYPE_BFLOAT16, 2, (void*)(w1 + c0), dims, strides, box, es,
        CU_TENSOR_MAP_INTERLEAVE_NONE, CU_TENSOR_MAP_SWIZZLE_128B, CU_TENSOR_MAP_L2_PROMOTION_L2_128B,
        CU_TENSOR_MAP_FLOAT_OOB_FILL_NONE);
  }
  main_kernel<<<NCTA + NHELP, 512, LAUNCH_SMEM, cudaStreamPerThread>>>(P, tms);
}
```

```cpp
#include <cuda_runtime.h>
#include <cuda_bf16.h>
#include <cuda.h>
#include <stdint.h>

typedef __nv_bfloat16 bf16;

constexpr int NF = 26;
constexpr int NCTA = 128;

constexpr int G0_KS = 24, G0_N = 56, G0_SLAB = G0_N * 32;
constexpr int L_KS = 43, L_SLAB = 1024;
constexpr int G0_BYTES = G0_KS * G0_SLAB;
constexpr int L_BYTES = L_KS * L_SLAB;
constexpr int IMG_BYTES = G0_BYTES + 3 * L_BYTES;

constexpr int W1_STAGES = 7;
constexpr int W1_STAGE_BYTES = 16384;
constexpr int OFF_LB = 0;
constexpr int OFF_LA = 44032;
constexpr int OFF_LC = 88064;
__host__ __device__ constexpr int w1_off(int st) { return st < 2 ? st * W1_STAGE_BYTES : OFF_LA + (st - 2) * W1_STAGE_BYTES; }
constexpr int OFF_G0 = 132096;
constexpr int OFF_IDX = 132096 + 16384;
constexpr int OFF_TAB = OFF_G0 + G0_BYTES;
constexpr int OFF_XOFF = OFF_TAB + 32000;
constexpr int OFF_BAR = OFF_XOFF + 6656;
constexpr int OFF_BW = OFF_BAR + 256;
constexpr int OFF_W2 = OFF_BW + 256;
constexpr int OFF_WTAB = OFF_W2 + 1792;
constexpr int OFF_EPOCH = OFF_WTAB + 256;
constexpr int OFF_STAB = (OFF_EPOCH + 16 + 127) / 128 * 128;
constexpr int OFF_LOFF = OFF_STAB + 3072 + 704;
constexpr int SMEM_BYTES = OFF_STAB + 4288;
static_assert(SMEM_BYTES <= 229376, "smem");
constexpr int LAUNCH_SMEM = SMEM_BYTES;

constexpr int BAR_W1FULL = 0  , BAR_W1FREE = 10  , BAR_W1DONE = 11  ,
              BAR_IMG = 14  , BAR_X0 = 18, BAR_SETUP = 19, BAR_EPOCH = 20, BAR_TABS = 21,
              BAR_Q = 22, BAR_STAB = 23, BAR_G0B = 24  , NBAR = 26;

struct TmaMaps { CUtensorMap m[4]; };
struct Params {
  const int* idx; const bf16* table; const bf16* ws; const bf16* wout; const bf16* b1; const bf16* w2; const bf16* bout;
  bf16* out;
  unsigned char* img; unsigned long long* part; unsigned* ctr; const void* tabs;
  uint64_t dk, dmn;
  uint2 role[NCTA];
};

__device__ __align__(1024) unsigned char g_img[IMG_BYTES];
__device__ unsigned long long g_part[NCTA * 128];
__device__ __align__(128) unsigned g_ctr[32 * 17];

#define GT(i) do {} while (0)
#define TL(i) do {} while (0)
#define TLP(i) do {} while (0)
#define TLA(i) do {} while (0)
#define TLW(w, i) do {} while (0)
#define TL_INIT() do {} while (0)
#define TL_START() 0
#define TL_PUT0(c) do {} while (0)
#define TL_DUMP() do {} while (0)
__device__ __forceinline__ uint32_t smem_u32(const void* p) { return (uint32_t)__cvta_generic_to_shared(p); }
__device__ __forceinline__ bool elect_one() {
  uint32_t pred;
  asm volatile("{\n.reg .pred p;\nelect.sync _|p, 0xffffffff;\nselp.u32 %0, 1, 0, p;\n}\n" : "=r"(pred));
  return pred != 0;
}
__device__ __forceinline__ void mbar_init(uint32_t bar, uint32_t cnt) {
  asm volatile("mbarrier.init.shared::cta.b64 [%0], %1;" ::"r"(bar), "r"(cnt) : "memory");
}
__device__ __forceinline__ void mbar_expect_tx(uint32_t bar, uint32_t bytes) {
  asm volatile("mbarrier.arrive.expect_tx.shared::cta.b64 _, [%0], %1;" ::"r"(bar), "r"(bytes) : "memory");
}
__device__ __forceinline__ void mbar_arrive(uint32_t bar) {
  asm volatile("mbarrier.arrive.shared::cta.b64 _, [%0];" ::"r"(bar) : "memory");
}
__device__ __forceinline__ bool mbar_try(uint32_t bar, uint32_t parity) {
  uint32_t ok;
  asm volatile("{\n.reg .pred p;\nmbarrier.try_wait.parity.shared::cta.b64 p, [%1], %2;\nselp.u32 %0, 1, 0, p;\n}\n"
               : "=r"(ok) : "r"(bar), "r"(parity) : "memory");
  return ok != 0;
}
__device__ __forceinline__ void mbar_wait(uint32_t bar, uint32_t parity) {
#pragma unroll 1
  for (uint32_t it = 0; it < (1u << 26); it++)
    if (mbar_try(bar, parity)) return;
  __trap();
}
__device__ __forceinline__ void bulk_g2s(uint32_t dst, const void* src, uint32_t bytes, uint32_t bar) {
  asm volatile("cp.async.bulk.shared::cluster.global.mbarrier::complete_tx::bytes [%0], [%1], %2, [%3];"
               ::"r"(dst), "l"(src), "r"(bytes), "r"(bar) : "memory");
}
__device__ __forceinline__ void tma_2d(uint32_t dst, const CUtensorMap* tm, int x, int y, uint32_t bar) {
  asm volatile("cp.async.bulk.tensor.2d.shared::cluster.global.mbarrier::complete_tx::bytes [%0], [%1, {%3, %4}], [%2];"
               ::"r"(dst), "l"(tm), "r"(bar), "r"(x), "r"(y) : "memory");
}
__device__ __forceinline__ void cp_async16(uint32_t dst, const void* src) {
  asm volatile("cp.async.cg.shared.global [%0], [%1], 16;" ::"r"(dst), "l"(src) : "memory");
}
__device__ __forceinline__ void fence_proxy_async() { asm volatile("fence.proxy.async.shared::cta;" ::: "memory"); }
__device__ __forceinline__ void fence_proxy_async_all() { asm volatile("fence.proxy.async;" ::: "memory"); }
template <int ID, int N> __device__ __forceinline__ void named_bar_t() { asm volatile("bar.sync %0, %1;" ::"n"(ID), "n"(N) : "memory"); }
#define named_bar(id, n) named_bar_t<id, n>()

__device__ __forceinline__ void wg_fence() { asm volatile("wgmma.fence.sync.aligned;" ::: "memory"); }
__device__ __forceinline__ void wg_commit() { asm volatile("wgmma.commit_group.sync.aligned;" ::: "memory"); }
template <int N> __device__ __forceinline__ void wg_wait() { asm volatile("wgmma.wait_group.sync.aligned %0;" ::"n"(N) : "memory"); }
template <int N> __device__ __forceinline__ void reg_fence(float (&d)[N]) {
#pragma unroll
  for (int i = 0; i < N; i++) asm volatile("" : "+f"(d[i])::"memory");
}
constexpr uint32_t SMEM_BASE = 1024;
__host__ __device__ constexpr uint64_t make_desc(uint32_t off, uint32_t lbo, uint32_t sbo, uint32_t swz) {
  return (uint64_t)(((SMEM_BASE + off) & 0x3FFFF) >> 4) | ((uint64_t)(lbo >> 4) << 16) | ((uint64_t)(sbo >> 4) << 32) | ((uint64_t)swz << 62);
}

#define ACC4(d, o) "+f"(d[o]), "+f"(d[o + 1]), "+f"(d[o + 2]), "+f"(d[o + 3])
#define ACC8(d, o) ACC4(d, o), ACC4(d, o + 4)

__device__ __forceinline__ void wgmma_rs_n32(float (&d)[16], uint32_t a0, uint32_t a1, uint32_t a2, uint32_t a3, uint64_t db, int sc) {
  asm volatile("{\n.reg .pred p;\nsetp.ne.b32 p, %21, 0;\n"
               "wgmma.mma_async.sync.aligned.m64n32k16.f32.bf16.bf16 "
               "{%0,%1,%2,%3,%4,%5,%6,%7,%8,%9,%10,%11,%12,%13,%14,%15}, {%16,%17,%18,%19}, %20, p, 1, 1, 0;\n}\n"
               : ACC8(d, 0), ACC8(d, 8)
               : "r"(a0), "r"(a1), "r"(a2), "r"(a3), "l"(db), "r"(sc));
}
__device__ __forceinline__ void wgmma_rs_n56(float (&d)[28], uint32_t a0, uint32_t a1, uint32_t a2, uint32_t a3, uint64_t db, int sc) {
  asm volatile("{\n.reg .pred p;\nsetp.ne.b32 p, %33, 0;\n"
               "wgmma.mma_async.sync.aligned.m64n56k16.f32.bf16.bf16 "
               "{%0,%1,%2,%3,%4,%5,%6,%7,%8,%9,%10,%11,%12,%13,%14,%15,%16,%17,%18,%19,%20,%21,%22,%23,%24,%25,%26,%27}, "
               "{%28,%29,%30,%31}, %32, p, 1, 1, 0;\n}\n"
               : ACC8(d, 0), ACC8(d, 8), ACC8(d, 16), ACC4(d, 24)
               : "r"(a0), "r"(a1), "r"(a2), "r"(a3), "l"(db), "r"(sc));
}
__device__ __forceinline__ void wgmma_rs_n112_tb(float (&d)[56], uint32_t a0, uint32_t a1, uint32_t a2, uint32_t a3, uint64_t db, int sc) {
  asm volatile("{\n.reg .pred p;\nsetp.ne.b32 p, %61, 0;\n"
               "wgmma.mma_async.sync.aligned.m64n112k16.f32.bf16.bf16 "
               "{%0,%1,%2,%3,%4,%5,%6,%7,%8,%9,%10,%11,%12,%13,%14,%15,%16,%17,%18,%19,%20,%21,%22,%23,%24,%25,%26,%27,%28,%29,%30,%31,%32,%33,%34,%35,%36,%37,%38,%39,%40,%41,%42,%43,%44,%45,%46,%47,%48,%49,%50,%51,%52,%53,%54,%55}, "
               "{%56,%57,%58,%59}, %60, p, 1, 1, 1;\n}\n"
               : ACC8(d, 0), ACC8(d, 8), ACC8(d, 16), ACC8(d, 24), ACC8(d, 32), ACC8(d, 40), ACC8(d, 48)
               : "r"(a0), "r"(a1), "r"(a2), "r"(a3), "l"(db), "r"(sc));
}

__device__ __forceinline__ void wgmma_rs_n8(float (&d)[4], uint32_t a0, uint32_t a1, uint32_t a2, uint32_t a3, uint64_t db, int sc) {
  asm volatile("{\n.reg .pred p;\nsetp.ne.b32 p, %9, 0;\n"
               "wgmma.mma_async.sync.aligned.m64n8k16.f32.bf16.bf16 {%0,%1,%2,%3}, {%4,%5,%6,%7}, %8, p, 1, 1, 0;\n}\n"
               : ACC4(d, 0)
               : "r"(a0), "r"(a1), "r"(a2), "r"(a3), "l"(db), "r"(sc));
}
__device__ __forceinline__ uint32_t mul_lo(uint32_t v, uint32_t r) {
  __nv_bfloat162 a = *reinterpret_cast<__nv_bfloat162*>(&v), b = *reinterpret_cast<__nv_bfloat162*>(&r);
  __nv_bfloat162 c = __hmul2(__low2bfloat162(a), b);
  return *reinterpret_cast<uint32_t*>(&c);
}
__device__ __forceinline__ uint32_t mul_hi(uint32_t v, uint32_t r) {
  __nv_bfloat162 a = *reinterpret_cast<__nv_bfloat162*>(&v), b = *reinterpret_cast<__nv_bfloat162*>(&r);
  __nv_bfloat162 c = __hmul2(__high2bfloat162(a), b);
  return *reinterpret_cast<uint32_t*>(&c);
}
__device__ __forceinline__ uint32_t mul_ew(uint32_t v, uint32_t r) {
  __nv_bfloat162 a = *reinterpret_cast<__nv_bfloat162*>(&v), b = *reinterpret_cast<__nv_bfloat162*>(&r);
  __nv_bfloat162 c = __hmul2(a, b);
  return *reinterpret_cast<uint32_t*>(&c);
}
__device__ __forceinline__ uint32_t pack_bf16(float lo, float hi) {
  uint32_t r;
  asm("cvt.rn.bf16x2.f32 %0, %1, %2;" : "=r"(r) : "f"(hi), "f"(lo));
  return r;
}
__device__ __forceinline__ float bf2f(bf16 v) { return __bfloat162float(v); }
__device__ __forceinline__ float bflo(uint32_t w) { return __uint_as_float(w << 16); }
__device__ __forceinline__ float bfhi(uint32_t w) { return __uint_as_float(w & 0xffff0000u); }

__device__ __forceinline__ void st_img(uint32_t* p, uint32_t v) {
  asm volatile("st.relaxed.gpu.global.u32 [%0], %1;" ::"l"(p), "r"(v) : "memory");
}
__device__ __forceinline__ uint32_t ld_back(const uint32_t* p) {
  uint32_t v;
  asm volatile("ld.relaxed.gpu.global.u32 %0, [%1];" : "=r"(v) : "l"(p) : "memory");
  return v;
}
__host__ __device__ constexpr int Fq(int q, int t, int e) {
  if (t == 12) return 24 + e;
  const int u = (t + 3 * q) % 12;
  const int sw = (q >= 2 && u >= 6) ? 1 : 0;
  return 2 * u + (e ^ sw);
}
constexpr int M_ONE = 26, M_NONE = 27;
struct Mono { int f1, f2; };
__host__ __device__ constexpr Mono g0_mono(int s, int q, int e) {
  if (s < 30) { const int d = s / 6 + 1, a = (s % 6) >> 1; return {Fq(q, a, s & 1), Fq(q, a + d, e)}; }
  if (s < 33) return {Fq(q, s - 30, e), Fq(q, s - 24, e)};
  if (s < 35) return {Fq(q, s - 33, e), Fq(q, s - 33, e)};
  if (s == 35) return {Fq(q, e, 0), Fq(q, e, 1)};
  if (s == 36) return {Fq(q, 2, 0), Fq(q, 2, e)};
  if (s == 37) return e ? Mono{Fq(q, 2, 1), Fq(q, 2, 1)} : Mono{M_NONE, M_NONE};
  if (s < 44) return {24 + ((s - 38) & 1), Fq(q, (s - 38) >> 1, e)};
  if (s < 47) return {Fq(q, s - 44, e), M_ONE};
  if (q == 0) return {24, 24 + e};
  if (q == 1) return e ? Mono{25, 25} : Mono{M_NONE, M_NONE};
  if (q == 2) return {24 + e, M_ONE};
  return e ? Mono{M_NONE, M_NONE} : Mono{M_ONE, M_ONE};
}
constexpr int QM_RS = 40;
constexpr int O_ZERO = 31 * QM_RS + 39, O_CONST = 30 * QM_RS + 39;
struct StaticTabs {
  uint32_t otab[48 * 8];
  uint32_t x1tab[48 * 8];
  uint16_t ltab[88 * 4];
  uint16_t loff[32 * 8];
};
constexpr StaticTabs make_tabs() {
  StaticTabs T{};
  for (int s = 0; s < 48; s++)
    for (int q = 0; q < 4; q++)
      for (int e = 0; e < 2; e++) {
        const Mono m = g0_mono(s, q, e);
        const bool none = m.f1 == M_NONE, cs = m.f1 == M_ONE, lin = m.f2 == M_ONE;
        const uint32_t o1 = none ? O_ZERO : cs ? O_CONST : m.f1 * QM_RS + (lin ? 26 : m.f2);
        const uint32_t o2 = (none || cs || lin || m.f1 == m.f2) ? O_ZERO : m.f2 * QM_RS + m.f1;
        T.otab[s * 8 + q * 2 + e] = o1 | (o2 << 16);
        const bool qd = m.f1 < NF && m.f2 < NF;
        const uint32_t y1 = qd ? m.f1 * NF + m.f2 : 0xffffu;
        const uint32_t y2 = (qd && m.f1 != m.f2) ? m.f2 * NF + m.f1 : 0xffffu;
        T.x1tab[s * 8 + q * 2 + e] = y1 | (y2 << 16);
      }
  for (int s = 0; s < 88; s++)
    for (int q = 0; q < 4; q++) {
      uint16_t v = 0;
      if (s < 85) {
        const bool ex = s >= 78;
        const int a = s / 13, k = s - 78;
        const int tt = ex ? ((k < 3) ? k : (k < 6 ? k + 3 : 12)) : s % 13;
        const int in = ex ? 24 + (q >> 1) : 8 * (a >> 1) + 2 * q + (a & 1);
        const bool valid = !(ex && tt == 12 && (q & 1));
        const int f0 = Fq(q, tt, 0);
        v = (uint16_t)((f0 >> 1) | ((f0 & 1) << 4) | ((valid ? 1 : 0) << 5) | (in << 6));
      }
      T.ltab[s * 4 + q] = v;
    }
  for (int ln = 0; ln < 32; ln++)
    for (int k = 0; k < 8; k++) {
      const int m = ln >> 3, r = ln & 7;
      const int tt = (k < 6) ? 2 * k + (m >> 1) : 12;
      T.loff[ln * 8 + k] = (uint16_t)(2 * Fq(r >> 1, tt, r & 1));
    }
  return T;
}
static_assert(sizeof(StaticTabs) == 4288, "tabs");
__device__ __align__(128) const StaticTabs g_tabs = make_tabs();

constexpr int SETUP_WARPS = 7;
constexpr int WL_BYTES = NF * NF * NF * 2;
static inline uint2 make_role(int cta) {
  int kind = 5, grp = 0, j = 0, off = 0, bytes = 0;
  const int c = cta, SL = NF * NF * 2;
  if (c < 56) { kind = 1 + c / 28; grp = (c % 28) / 7; j = c % 7; off = kind * WL_BYTES + grp * 8 * SL; bytes = (grp < 3 ? 8 : 2) * SL; }
  else if (c < 80) { kind = 0; grp = (c - 56) / 8; j = (c - 56) % 8; off = 3 * WL_BYTES + grp * 8 * SL; bytes = 8 * SL; }
  else if (c < 83) { kind = 0; grp = 3; j = c - 80; off = 3 * WL_BYTES + 24 * SL; bytes = 2 * SL; }
  else if (c < 95) { kind = 3; grp = (c - 83) / 4; j = (c - 83) % 4; off = grp * 8 * SL; bytes = 8 * SL; }
  const int delta = off & 127;
  uint2 r;
  r.x = (uint32_t)(off - delta) | ((uint32_t)kind << 24);
  r.y = (uint32_t)(bytes + delta) | ((uint32_t)delta << 16) | ((uint32_t)grp << 24) | ((uint32_t)j << 28);
  return r;
}

__device__ __forceinline__ uint32_t layer_row(int li, int grp, int r, int lane, const unsigned char* raw, const StaticTabs* T,
                                              uint32_t bar, uint32_t tbar, const bf16* __restrict__ wout, uint32_t* img32) {
  const int ks = li ? r : 13 * grp + (r >> 2), ng = li ? grp : (r & 3);
  if (ks >= 43 || (!li && grp < 3 && r >= 52)) return 0;
  const uint32_t* w32 = reinterpret_cast<const uint32_t*>(raw);
  const int n8 = lane >> 2, q = lane & 3;
  const int o = (ng < 3) ? ng * 8 + n8 : 24 + (n8 >> 2);
  const bool vo = (ng < 3) || !(n8 & 1);
  const int ob = li ? (o - 8 * grp) * 338 : o * 13 - 8 * grp * 338;
  const int si = li ? 13 : 338;
  uint32_t bias = 0;
  if (vo && ks == 42 && li == 0 && q == 0) bias = (uint32_t)__ldg(reinterpret_cast<const unsigned short*>(wout) + 2 * NF + o);
  uint32_t* dst = img32 + G0_BYTES / 4 + li * (L_BYTES / 4) + (ks * 4 + ng) * 64 + lane;
  mbar_wait(tbar, 0);
  const uint32_t e0 = T->ltab[8 * ks + q], e1 = T->ltab[8 * ks + 4 + q];
  const bool v0 = vo && (e0 & 32), v1 = vo && (e1 & 32);
  const int s0 = v0 ? ob + (e0 >> 6) * si + (e0 & 15) : 0, s1 = v1 ? ob + (e1 >> 6) * si + (e1 & 15) : 0;
  TL(33);
  mbar_wait(bar, 0);
  TL(36);
  uint32_t w0 = w32[s0], w1 = w32[s1];
  w0 = (e0 & 16) ? __funnelshift_l(w0, w0, 16) : w0;
  w1 = (e1 & 16) ? __funnelshift_l(w1, w1, 16) : w1;
  w0 = v0 ? w0 : 0u;
  w1 = v1 ? w1 : bias;
  st_img(dst, w0); st_img(dst + 32, w1);
  return (ld_back(dst) ^ w0) | (ld_back(dst + 32) ^ w1);
}
__device__ __forceinline__ float x1_val(const unsigned short* wh, uint32_t e) {
  const uint32_t a = e & 0xffff, b = e >> 16;
  const uint32_t x = wh[a == 0xffff ? 0 : a], y = wh[b == 0xffff ? 0 : b];
  return (a == 0xffff ? 0.f : __uint_as_float(x << 16)) + (b == 0xffff ? 0.f : __uint_as_float(y << 16));
}
__device__ __forceinline__ uint32_t x1_row(int ng, int ks, int lane, const unsigned char* raw, const StaticTabs* T, uint32_t bar, uint32_t tbar, uint32_t* img32) {
  if (ks >= 24) return 0;
  const int n8 = lane >> 2, q = lane & 3;
  const unsigned short* wh = reinterpret_cast<const unsigned short*>(raw) + n8 * (NF * NF);
  uint32_t* dst = img32 + ks * (G0_SLAB / 4) + ng * 64 + lane;
  mbar_wait(tbar, 0);
  const uint2 ea = *reinterpret_cast<const uint2*>(&T->x1tab[16 * ks + 2 * q]), eb = *reinterpret_cast<const uint2*>(&T->x1tab[16 * ks + 8 + 2 * q]);
  mbar_wait(bar, 0);
  const uint32_t w0 = pack_bf16(x1_val(wh, ea.x), x1_val(wh, ea.y)), w1 = pack_bf16(x1_val(wh, eb.x), x1_val(wh, eb.y));
  st_img(dst, w0); st_img(dst + 32, w1);
  return (ld_back(dst) ^ w0) | (ld_back(dst + 32) ^ w1);
}

constexpr int NHELP = 4;
constexpr int H_MS = 32 * QM_RS + 4;
constexpr int H_W5 = 0, H_W4 = 35328, H_W0 = 70656, H_TAB = 73472, H_B = 77824, H_M = 82944, H_XE = H_M + 8 * H_MS * 4, H_BAR = H_XE + 1536;
__device__ __forceinline__ int wf_off(int b, int h) { return (b >> 3) * 512 + (h >> 3) * 128 + (b & 7) * 16 + (h & 7) * 2; }
__device__ __forceinline__ void helper_role(int hk, const Params& P, unsigned char* smem, uint32_t sb) {
  const int t = threadIdx.x, warp = __shfl_sync(0xffffffffu, t >> 5, 0), lane = t & 31;
  const uint32_t d5bar = sb + H_BAR, d4bar = sb + H_BAR + 8, tbar = sb + H_BAR + 16;
  unsigned ctr0 = 0;
  if (t == 0) asm volatile("ld.relaxed.gpu.global.u32 %0, [%1];" : "=r"(ctr0) : "l"(P.ctr) : "memory");
  const unsigned char* wsb = reinterpret_cast<const unsigned char*>(P.ws);
  unsigned char* WB = smem + H_B;
  float* M = reinterpret_cast<float*>(smem + H_M);
  constexpr uint32_t W5B = WL_BYTES + ((5 * WL_BYTES) & 127), W4B = WL_BYTES + ((4 * WL_BYTES) & 127);
  if (warp < 3 && elect_one()) {
    mbar_init(sb + H_BAR + 8 * warp, 1);
    asm volatile("fence.mbarrier_init.release.cluster;" ::: "memory");
    if (warp == 0) {
      mbar_expect_tx(d5bar, W5B);
#pragma unroll
      for (int c = 0; c < 5; c++)
        bulk_g2s(sb + H_W5 + c * 8192, wsb + ((5 * WL_BYTES) & ~127) + c * 8192, c < 4 ? 8192u : W5B - 4 * 8192, d5bar);
    }
  }
  reinterpret_cast<uint32_t*>(WB)[t] = 0;
  __syncthreads();
  if (warp >= 5 && warp < 12 && elect_one()) {
    if (warp < 10) {
      const int c = warp - 5;
      if (c == 0) mbar_expect_tx(d4bar, W4B + (hk == 3 ? 2768 : 0));
      bulk_g2s(sb + H_W4 + c * 8192, wsb + ((4 * WL_BYTES) & ~127) + c * 8192, c < 4 ? 8192u : W4B - 4 * 8192, d4bar);
    } else if (warp == 10) {
      mbar_expect_tx(tbar, sizeof(StaticTabs));
      bulk_g2s(sb + H_TAB, P.tabs, sizeof(StaticTabs), tbar);
    } else if (hk == 3) {
      bulk_g2s(sb + H_W0, wsb + ((24 * NF * NF * 2) & ~127), 2768, d4bar);
    }
  }
  const unsigned short* wo16 = reinterpret_cast<const unsigned short*>(P.wout);
  uint32_t c5[13];
#pragma unroll
  for (int k = 0; k < 13; k++) c5[k] = __ldg(reinterpret_cast<const uint32_t*>(P.wout + 5 * NF) + k);
  unsigned short wv = 0;
  const int io0 = (hk < 3) ? 8 * hk : 24;
  if (t >= 352 && t < 352 + NF) wv = __ldg(wo16 + 4 * NF + t - 352);
  else if (t >= 384 && t < 392 && io0 + t - 384 < NF) wv = __ldg(wo16 + 3 * NF + io0 + t - 384);
  const StaticTabs* T = reinterpret_cast<const StaticTabs*>(smem + H_TAB);
  const int n8 = lane >> 2, q = lane & 3, g = n8;
  const int fil = (hk < 3) ? n8 : (n8 >> 2);
  const bool fx1 = (hk == 3) && !(n8 & 1);
  uint32_t* dst = reinterpret_cast<uint32_t*>(P.img) + (warp >> 1) * (G0_SLAB / 4) + (warp & 1) * 32 + (3 + hk) * 64 + lane;
  if (t >= 352 && t < 352 + NF) *reinterpret_cast<unsigned short*>(WB + wf_off(26, t - 352)) = wv;
  if (t >= 384 && t < 392) { M[(t - 384) * H_MS + O_ZERO] = 0.f; M[(t - 384) * H_MS + O_CONST] = __uint_as_float((uint32_t)wv << 16); }
  mbar_wait(d5bar, 0);
  if (t < 338) {
    const uint32_t* w5 = reinterpret_cast<const uint32_t*>(smem + H_W5 + ((5 * WL_BYTES) & 127)) + t;
    float s0 = 0.f, s1 = 0.f, s2 = 0.f, s3 = 0.f;
#pragma unroll
    for (int k = 0; k < 13; k++) {
      const uint32_t wa = w5[(2 * k) * 338], wb = w5[(2 * k + 1) * 338];
      const float ca = bflo(c5[k]), cb = bfhi(c5[k]);
      s0 = fmaf(ca, bflo(wa), s0); s1 = fmaf(ca, bfhi(wa), s1);
      s2 = fmaf(cb, bflo(wb), s2); s3 = fmaf(cb, bfhi(wb), s3);
    }
    const int h = (t * 79) >> 10, tp = t - 13 * h;
    *reinterpret_cast<bf16*>(WB + wf_off(2 * tp, h)) = __float2bfloat16(s0 + s2);
    *reinterpret_cast<bf16*>(WB + wf_off(2 * tp + 1, h)) = __float2bfloat16(s1 + s3);
  }
  fence_proxy_async();
  mbar_wait(tbar, 0);
  uint2 fot[3];
#pragma unroll
  for (int r = 0; r < 3; r++) fot[r] = *reinterpret_cast<const uint2*>(&T->otab[(warp + 16 * r) * 8 + q * 2]);
  mbar_wait(d4bar, 0);
  const int wgi = warp >> 2, il = 2 * wgi + ((warp >> 1) & 1), mt = warp & 1;
  const bool mma_wg = (hk < 3) || (wgi == 0);
  uint32_t a[2][4];
  if (mma_wg) {
    const unsigned short* A = reinterpret_cast<const unsigned short*>(smem + H_W4 + ((4 * WL_BYTES) & 127)) + (io0 + il) * NF + mt * 16 + g;
#pragma unroll
    for (int kk = 0; kk < 2; kk++) {
#pragma unroll
      for (int jj = 0; jj < 4; jj++) {
        const int k = kk * 16 + 2 * q + (jj >> 1) * 8, mo = (jj & 1) * 8;
        const int kc = (k < NF) ? k : 0;
        const uint32_t lo = A[kc * (NF * NF) + mo], hi = A[(kc + 1) * (NF * NF) + mo];
        a[kk][jj] = (k < NF) ? (lo | (hi << 16)) : 0u;
      }
    }
  }
  if (hk == 3) {
    const int u0 = (warp >= 4) ? t - 128 : -1;
    if (u0 >= 0) {
      const int sl = u0 >> 3, xl = (u0 >> 2) & 1, xq = u0 & 3;
      const uint2 xt = *reinterpret_cast<const uint2*>(&T->x1tab[sl * 8 + xq * 2]);
      const unsigned short* wh = reinterpret_cast<const unsigned short*>(smem + H_W0 + ((24 * NF * NF * 2) & 127)) + xl * (NF * NF);
      reinterpret_cast<uint32_t*>(smem + H_XE)[u0] = pack_bf16(x1_val(wh, xt.x), x1_val(wh, xt.y));
    }
  }
  __syncthreads();
  if (mma_wg) {
    float c[16];
    wg_fence();
    wgmma_rs_n32(c, a[0][0], a[0][1], a[0][2], a[0][3], make_desc(H_B, 128, 512, 0), 0);
    wgmma_rs_n32(c, a[1][0], a[1][1], a[1][2], a[1][3], make_desc(H_B + 256, 128, 512, 0), 1);
    wg_commit();
    wg_wait<0>();
    reg_fence(c);
    float* Mi = M + il * H_MS;
#pragma unroll
    for (int n = 0; n < 4; n++) {
      *reinterpret_cast<float2*>(&Mi[(mt * 16 + g) * QM_RS + n * 8 + 2 * q]) = make_float2(c[4 * n], c[4 * n + 1]);
      *reinterpret_cast<float2*>(&Mi[(mt * 16 + g + 8) * QM_RS + n * 8 + 2 * q]) = make_float2(c[4 * n + 2], c[4 * n + 3]);
    }
  }
  __syncthreads();
  uint32_t val[3], chk = 0;
#pragma unroll
  for (int r = 0; r < 3; r++) {
    const float* Mf = M + fil * H_MS;
    const float v0 = Mf[fot[r].x & 0xffff] + Mf[fot[r].x >> 16], v1 = Mf[fot[r].y & 0xffff] + Mf[fot[r].y >> 16];
    const uint32_t xe = reinterpret_cast<const uint32_t*>(smem + H_XE)[(warp + 16 * r) * 8 + (n8 >> 2) * 4 + q];
    val[r] = fx1 ? xe : pack_bf16(v0, v1);
    st_img(dst + r * 8 * (G0_SLAB / 4), val[r]);
  }
#pragma unroll
  for (int r = 0; r < 3; r++) chk |= ld_back(dst + r * 8 * (G0_SLAB / 4)) ^ val[r];
  if (__any_sync(0xffffffffu, chk != 0)) __trap();
  __syncthreads();
  if (t == 0) {
    asm volatile("" : "+r"(ctr0));
    asm volatile("red.relaxed.gpu.global.add.u32 [%0], 32;" ::"l"(P.ctr) : "memory");
    const unsigned epoch = (ctr0 >> 8) + 1, target = epoch << 8;
    unsigned v;
    uint32_t it = 0;
#pragma unroll 1
    do {
      asm volatile("ld.relaxed.gpu.global.u32 %0, [%1];" : "=r"(v) : "l"(P.ctr) : "memory");
      if (++it > (1u << 22)) __trap();
    } while ((int)(v - target) < 0);
#pragma unroll
    for (int k = 0; k < 4; k++)
      asm volatile("st.relaxed.gpu.global.u32 [%0], %1;" ::"l"(P.ctr + 32 * (1 + 4 * hk + k)), "r"(epoch) : "memory");
  }
}

template <int S>
__device__ __forceinline__ uint32_t l_prod(const uint32_t (&vp)[4], const uint32_t (&X)[13]) {
  if constexpr (S < 78) {
    constexpr int a = S / 13, t = S % 13;
    return (a & 1) ? mul_hi(vp[a >> 1], X[t]) : mul_lo(vp[a >> 1], X[t]);
  } else if constexpr (S < 85) {
    constexpr int k = S - 78;
    constexpr int t = (k < 3) ? k : (k < 6 ? k + 3 : 12);
    return mul_lo(vp[3], X[t]);
  } else {
    return 0x00003F80u;
  }
}
template <int S>
__device__ __forceinline__ uint32_t g0_prod(const uint32_t (&X)[13], uint32_t selU, uint32_t selV) {
  if constexpr (S < 30) {
    constexpr int d = S / 6 + 1, a = (S % 6) >> 1;
    return (S & 1) ? mul_hi(X[a], X[a + d]) : mul_lo(X[a], X[a + d]);
  } else if constexpr (S < 33) {
    return mul_ew(X[S - 30], X[S - 24]);
  } else if constexpr (S < 35) {
    return mul_ew(X[S - 33], X[S - 33]);
  } else if constexpr (S == 35) {
    return mul_ew(__byte_perm(X[0], X[1], 0x5410), __byte_perm(X[0], X[1], 0x7632));
  } else if constexpr (S == 36) {
    return mul_lo(X[2], X[2]);
  } else if constexpr (S == 37) {
    return mul_hi(X[2], X[2]);
  } else if constexpr (S < 44) {
    constexpr int a = (S - 38) >> 1;
    return ((S - 38) & 1) ? mul_hi(X[12], X[a]) : mul_lo(X[12], X[a]);
  } else if constexpr (S < 47) {
    return X[S - 44];
  } else {
    return mul_ew(__byte_perm(X[12], 0x3F803F80u, selU), __byte_perm(X[12], 0x3F803F80u, selV));
  }
}

constexpr int NBK = 4;

template <int KS, int KE>
__device__ __forceinline__ void l_fill(uint32_t (*A)[4], const uint32_t (&vp)[2][4], const uint32_t (&X)[2][13]) {
  A[0][0] = l_prod<2 * KS>(vp[0], X[0]);
  A[0][1] = l_prod<2 * KS>(vp[1], X[1]);
  A[0][2] = l_prod<2 * KS + 1>(vp[0], X[0]);
  A[0][3] = l_prod<2 * KS + 1>(vp[1], X[1]);
  if constexpr (KS + 1 < KE) l_fill<KS + 1, KE>(A + 1, vp, X);
}
template <int KS, int OFF>
__device__ __forceinline__ void layer_rec(float (&d)[16], const uint32_t (&vp)[2][4], const uint32_t (&X)[2][13], uint64_t dk) {
  constexpr int KE = (KS + NBK < L_KS) ? KS + NBK : L_KS;
  uint32_t A[NBK][4];
  l_fill<KS, KE>(A, vp, X);
  wg_fence();
#pragma unroll
  for (int k = 0; k < KE - KS; k++)
    wgmma_rs_n32(d, A[k][0], A[k][1], A[k][2], A[k][3], dk + (uint64_t)((OFF + (KS + k) * L_SLAB) >> 4), (KS + k) > 0);
  wg_commit();
  if constexpr (KE < L_KS) {
    wg_wait<1>();
    layer_rec<KE, OFF>(d, vp, X, dk);
  }
}
template <int OFF, int NK>
__device__ __forceinline__ void layer_first(float (&d)[16], const uint32_t (&vp)[2][4], const uint32_t (&X)[2][13], uint64_t dk) {
  uint32_t A[NK][4];
  l_fill<0, NK>(A, vp, X);
  wg_fence();
#pragma unroll
  for (int k = 0; k < NK; k++) wgmma_rs_n32(d, A[k][0], A[k][1], A[k][2], A[k][3], dk + (uint64_t)((OFF + k * L_SLAB) >> 4), k > 0);
  wg_commit();
}
template <int KS, int KE>
__device__ __forceinline__ void g0_fill(uint32_t (*A)[4], const uint32_t (&X)[2][13], uint32_t selU, uint32_t selV) {
  A[0][0] = g0_prod<2 * KS>(X[0], selU, selV);
  A[0][1] = g0_prod<2 * KS>(X[1], selU, selV);
  A[0][2] = g0_prod<2 * KS + 1>(X[0], selU, selV);
  A[0][3] = g0_prod<2 * KS + 1>(X[1], selU, selV);
  if constexpr (KS + 1 < KE) g0_fill<KS + 1, KE>(A + 1, X, selU, selV);
}
template <int B0>
__device__ __forceinline__ void g0_rec(float (&d)[28], const uint32_t (&X)[2][13], uint32_t selU, uint32_t selV, uint64_t dk, uint32_t bar2, bool first) {
  constexpr int KS = B0 * NBK;
  if constexpr (KS == 8) { if (first) mbar_wait(bar2, 0); }
  if constexpr (KS == 16) { if (first) mbar_wait(bar2 + 8, 0); }
  constexpr int KE = (KS + NBK < G0_KS) ? KS + NBK : G0_KS;
  uint32_t A[NBK][4];
  g0_fill<KS, KE>(A, X, selU, selV);
  wg_fence();
#pragma unroll
  for (int k = 0; k < KE - KS; k++)
    wgmma_rs_n56(d, A[k][0], A[k][1], A[k][2], A[k][3], dk + (uint64_t)((OFF_G0 + (KS + k) * G0_SLAB) >> 4), (KS + k) > 0);
  wg_commit();
  if constexpr (KE < G0_KS) {
    wg_wait<1>();
    g0_rec<B0 + 1>(d, X, selU, selV, dk, bar2, first);
  }
}

__device__ __forceinline__ void ldsm_x4_t(uint32_t addr, uint32_t& r0, uint32_t& r1, uint32_t& r2, uint32_t& r3) {
  asm volatile("ldmatrix.sync.aligned.m8n8.x4.trans.shared.b16 {%0,%1,%2,%3}, [%4];"
               : "=r"(r0), "=r"(r1), "=r"(r2), "=r"(r3) : "r"(addr) : "memory");
}
__device__ __forceinline__ void ldsm_x2_t(uint32_t addr, uint32_t& r0, uint32_t& r1) {
  asm volatile("ldmatrix.sync.aligned.m8n8.x2.trans.shared.b16 {%0,%1}, [%2];" : "=r"(r0), "=r"(r1) : "r"(addr) : "memory");
}
__device__ __forceinline__ float tanh_fast(float x) { float y; asm("tanh.approx.f32 %0, %1;" : "=f"(y) : "f"(x)); return y; }

__device__ __forceinline__ uint32_t gelu2_pair(float lo, float hi, uint32_t bias) {
  uint32_t x = pack_bf16(lo, hi), t, u;
  asm("add.rn.bf16x2 %0, %0, %1;" : "+r"(x) : "r"(bias));
  asm("mul.rn.bf16x2 %0, %1, %1;" : "=r"(t) : "r"(x));
  asm("fma.rn.bf16x2 %0, %0, %1, %2;" : "+r"(t) : "r"(0x3D123D12u), "r"(0x3F4C3F4Cu));
  asm("mul.rn.bf16x2 %0, %1, %2;" : "=r"(u) : "r"(x), "r"(t));
  asm("tanh.approx.bf16x2 %0, %0;" : "+r"(u));
  asm("fma.rn.bf16x2 %0, %1, %0, %1;" : "+r"(u) : "r"(x));
  return u;
}

__device__ __forceinline__ void ldsm_x4(uint32_t addr, uint32_t (&r)[4]) {
  asm volatile("ldmatrix.sync.aligned.m8n8.x4.shared.b16 {%0,%1,%2,%3}, [%4];"
               : "=r"(r[0]), "=r"(r[1]), "=r"(r[2]), "=r"(r[3]) : "r"(addr) : "memory");
}
__device__ __forceinline__ uint32_t lds_u16(uint32_t addr) {
  unsigned short v;
  asm volatile("ld.shared.u16 %0, [%1];" : "=h"(v) : "r"(addr) : "memory");
  return v;
}
__device__ __forceinline__ uint32_t lds_u32(uint32_t addr) {
  uint32_t v;
  asm volatile("ld.shared.u32 %0, [%1];" : "=r"(v) : "r"(addr) : "memory");
  return v;
}

__global__ void __launch_bounds__(512, 1)
main_kernel(const __grid_constant__ Params P, const __grid_constant__ TmaMaps tms) {
  extern __shared__ __align__(1024) unsigned char smem[];
  const uint32_t sb = smem_u32(smem);
  const int tid = threadIdx.x, warp = __shfl_sync(0xffffffffu, tid >> 5, 0), lane = tid & 31;
  if (blockIdx.x < NHELP) {
    helper_role(blockIdx.x, P, smem, sb);
    return;
  }
  const int cta = blockIdx.x - NHELP, nq = cta & 3, grp = cta >> 2;
  const uint2 role = P.role[cta];
  const uint32_t bar0 = sb + OFF_BAR;
  auto BAR = [&](int i) { return bar0 + 8 * i; };
  const int wg = warp >> 2, w4 = warp & 3, g = lane >> 2, q = lane & 3;
  const uint64_t dk = P.dk;
  const long long tl_c0 = TL_START();
  TL_INIT();
  TL_PUT0(tl_c0);

  if (tid < 256) {
    const unsigned char* isrc = reinterpret_cast<const unsigned char*>(P.idx + grp * 128 * NF);
#pragma unroll
    for (int k = 0; k < 4; k++) {
      const int c = tid + 256 * k;
      if (c < 832) cp_async16(sb + OFF_IDX + c * 16, isrc + c * 16);
    }
    asm volatile("cp.async.commit_group;" ::: "memory");
#pragma unroll
    for (int k = 0; k < 8; k++) {
      const int c = tid + 256 * k;
      if (c < 2000) cp_async16(sb + OFF_TAB + ((c ^ ((c >> 3) & 1)) << 4), reinterpret_cast<const unsigned char*>(P.table) + c * 16);
    }
    asm volatile("cp.async.commit_group;" ::: "memory");
  }
  if (elect_one()) {
    mbar_init(BAR(warp), (warp == BAR_W1FREE || warp == BAR_W1DONE) ? 2 : 1);
    if (warp < NBAR - 16)
      mbar_init(BAR(16 + warp), (16 + warp == BAR_X0) ? 256 : (16 + warp == BAR_SETUP) ? SETUP_WARPS : (16 + warp == BAR_TABS) ? 224 : 1);
    asm volatile("fence.mbarrier_init.release.cluster;" ::: "memory");
  }
  __syncthreads();
  TL(26);

  if (warp == 15) {
    if (elect_one()) {
      mbar_expect_tx(BAR(BAR_STAB), sizeof(StaticTabs));
      bulk_g2s(sb + OFF_STAB, P.tabs, sizeof(StaticTabs), BAR(BAR_STAB));
      if ((sb & 0x3FFFF) != SMEM_BASE) __trap();
      const CUtensorMap* tm0 = &tms.m[nq];
      asm volatile("prefetch.tensormap [%0];" ::"l"(tm0) : "memory");
#pragma unroll
      for (int st = 0; st < W1_STAGES; st++) {
        if (st == 1 && (role.x >> 24) < 5) mbar_wait(BAR(BAR_Q), 0);
        mbar_expect_tx(BAR(BAR_W1FULL + st), W1_STAGE_BYTES);
        tma_2d(sb + w1_off(st), tm0, 0, st * 64, BAR(BAR_W1FULL + st));
        tma_2d(sb + w1_off(st) + 8192, tm0, 64, st * 64, BAR(BAR_W1FULL + st));
      }
      TLP(22);
      mbar_wait(BAR(BAR_EPOCH), 0);
      TLP(23);
      {
        const unsigned epoch_p = lds_u32(sb + OFF_EPOCH);
        const unsigned* flag = P.ctr + 32 * (1 + (cta & 15));
        unsigned v;
        uint32_t it = 0;
#pragma unroll 1
        do {
          asm volatile("ld.relaxed.gpu.global.u32 %0, [%1];" : "=r"(v) : "l"(flag) : "memory");
          if (++it > (1u << 22)) __trap();
        } while (v != epoch_p);
        asm volatile("fence.acq_rel.cta;" ::: "memory");
      }
      fence_proxy_async_all();
      mbar_wait(BAR(BAR_X0), 0);
      TLP(24);
      mbar_expect_tx(BAR(BAR_IMG + 0), G0_BYTES / 3);
      mbar_expect_tx(BAR(BAR_G0B), G0_BYTES / 3);
      mbar_expect_tx(BAR(BAR_G0B + 1), G0_BYTES / 3);
#pragma unroll
      for (int i = 0; i < 6; i++)
        bulk_g2s(sb + OFF_G0 + i * (G0_BYTES / 6), P.img + i * (G0_BYTES / 6), G0_BYTES / 6, i < 2 ? BAR(BAR_IMG + 0) : BAR(BAR_G0B + (i - 2) / 2));
      mbar_wait(BAR(BAR_W1FREE), 0);
      mbar_expect_tx(BAR(BAR_IMG + 2), L_BYTES);
#pragma unroll
      for (int i = 0; i < 4; i++)
        bulk_g2s(sb + OFF_LB + i * (L_BYTES / 4), P.img + G0_BYTES + L_BYTES + i * (L_BYTES / 4), L_BYTES / 4, BAR(BAR_IMG + 2));
      mbar_wait(BAR(BAR_W1DONE), 0);
      mbar_expect_tx(BAR(BAR_IMG + 1), L_BYTES);
      mbar_expect_tx(BAR(BAR_IMG + 3), L_BYTES);
#pragma unroll
      for (int i = 0; i < 2; i++)
        bulk_g2s(sb + OFF_LA + i * (L_BYTES / 2), P.img + G0_BYTES + i * (L_BYTES / 2), L_BYTES / 2, BAR(BAR_IMG + 1));
#pragma unroll
      for (int i = 0; i < 2; i++)
        bulk_g2s(sb + OFF_LC + i * (L_BYTES / 2), P.img + G0_BYTES + 2 * L_BYTES + i * (L_BYTES / 2), L_BYTES / 2, BAR(BAR_IMG + 3));
      TLP(25);
    }
    __syncwarp();
    mbar_wait(BAR(BAR_X0), 0);
    mbar_wait(BAR(BAR_TABS), 0);
  } else if (wg < 2) {
    asm volatile("cp.async.wait_group 1;" ::: "memory");
    named_bar(1, 256);
#pragma unroll
    for (int k = 0; k < 7; k++) {
      const int p = tid + 256 * k;
      if (p < 64 * NF) {
        const uint2 v = reinterpret_cast<const uint2*>(smem + OFF_IDX)[p];
        const uint32_t o0 = v.x * 32 + ((v.x >> 2) & 1) * 16, o1 = v.y * 32 + ((v.y >> 2) & 1) * 16;
        reinterpret_cast<uint32_t*>(smem + OFF_XOFF)[p] = o0 | (o1 << 16);
      }
    }
    TL(1);
    asm volatile("cp.async.wait_all;" ::: "memory");
    mbar_arrive(BAR(BAR_X0));
    mbar_wait(BAR(BAR_X0), 0);
    TL(3);
    float acc[56];
    {
      const uint32_t xo = sb + OFF_XOFF + (wg * 64 + w4 * 16 + (lane & 15)) * 52;
      const uint32_t tb = sb + OFF_TAB, hx = (lane >> 4) << 4;
      const uint64_t db0 = P.dmn;
      uint32_t A[3][2][4];
#pragma unroll
      for (int pr = 0; pr < 2; pr++) {
        const uint32_t oa = lds_u32(xo + 4 * pr);
        ldsm_x4(tb + ((oa & 0xffff) ^ hx), A[pr][0]); ldsm_x4(tb + ((oa >> 16) ^ hx), A[pr][1]);
      }
#pragma unroll
      for (int pr = 0; pr < 13; pr++) {
        const int st = pr >> 1;
        uint32_t oa = 0;
        if (pr + 2 < 13) oa = lds_u32(xo + 4 * (pr + 2));
        if (!(pr & 1)) mbar_wait(BAR(BAR_W1FULL + st), 0);
        if (pr == 0) TL(28); if (pr == 6) TL(29);
        const uint64_t db = db0 + (uint64_t)((w1_off(st) + (pr & 1) * 4096) >> 4);
        wg_fence();
        wgmma_rs_n112_tb(acc, A[pr % 3][0][0], A[pr % 3][0][1], A[pr % 3][0][2], A[pr % 3][0][3], db, pr > 0);
        wgmma_rs_n112_tb(acc, A[pr % 3][1][0], A[pr % 3][1][1], A[pr % 3][1][2], A[pr % 3][1][3], db + (2048 >> 4), 1);
        wg_commit();
        wg_wait<1>();
        if (pr == 4 && (tid & 127) == 0) mbar_arrive(BAR(BAR_W1FREE));
        if (pr + 2 < 13) { ldsm_x4(tb + ((oa & 0xffff) ^ hx), A[(pr + 2) % 3][0]); ldsm_x4(tb + ((oa >> 16) ^ hx), A[(pr + 2) % 3][1]); }
      }
      wg_wait<0>();
      reg_fence(acc);
      if ((tid & 127) == 0) mbar_arrive(BAR(BAR_W1DONE));
    }
    TL(4);
    float dot[4];
    {
      mbar_wait(BAR(BAR_TABS), 0);
      uint32_t bb[16];
      const uint4* bp = reinterpret_cast<const uint4*>(smem + OFF_BW + q * 64);
#pragma unroll
      for (int i = 0; i < 4; i++) { const uint4 v = bp[i]; bb[4 * i] = v.x; bb[4 * i + 1] = v.y; bb[4 * i + 2] = v.z; bb[4 * i + 3] = v.w; }
      uint32_t H[14][2];
#pragma unroll
      for (int c = 0; c < 14; c++) {
        H[c][0] = gelu2_pair(acc[4 * c], acc[4 * c + 1], bb[c]);
        H[c][1] = gelu2_pair(acc[4 * c + 2], acc[4 * c + 3], bb[c]);
      }
      wg_fence();
#pragma unroll
      for (int j = 0; j < 7; j++)
        wgmma_rs_n8(dot, H[2 * j][0], H[2 * j][1], H[2 * j + 1][0], H[2 * j + 1][1], dk + (uint64_t)((OFF_W2 + j * 256) >> 4), j > 0);
      wg_commit();
      wg_wait<0>();
      reg_fence(dot);
    }
    __syncwarp();
    mbar_wait(BAR(BAR_EPOCH), 0);
    if (q == 0) {
      const unsigned epoch = lds_u32(sb + OFF_EPOCH);
#pragma unroll
      for (int r = 0; r < 2; r++) {
        const int row = wg * 64 + w4 * 16 + g + 8 * r;
        const unsigned long long pk = ((unsigned long long)epoch << 32) | (unsigned long long)__float_as_uint(dot[2 * r]);
        asm volatile("st.relaxed.gpu.global.u64 [%0], %1;" ::"l"(P.part + cta * 128 + row), "l"(pk) : "memory");
      }
    }
    __syncwarp();
  } else {
    const int t = tid - 256;
    const bool is_arr = (t == 192);
    unsigned ctr0 = 0;
    if (is_arr) asm volatile("ld.relaxed.gpu.global.u32 %0, [%1];" : "=r"(ctr0) : "l"(P.ctr) : "memory");
    {
      const int kind = role.x >> 24, w = warp - 8, rgrp = (role.y >> 24) & 15, rj = role.y >> 28;
      const unsigned char* wsb = reinterpret_cast<const unsigned char*>(P.ws);
      if (kind < 5 && elect_one()) {
        const uint32_t bytes = role.y & 0xffff;
        const uint32_t o = w * 8192;
        if (w == 0) mbar_expect_tx(BAR(BAR_Q), bytes);
        if (o < bytes) bulk_g2s(sb + OFF_G0 + o, wsb + (role.x & 0xffffff) + o, min(bytes - o, 8192u), BAR(BAR_Q));
      }
      TL(40);
      __syncwarp();
      const StaticTabs* T = reinterpret_cast<const StaticTabs*>(smem + OFF_STAB);
      uint32_t* img32 = reinterpret_cast<uint32_t*>(P.img);
      const unsigned char* raw = smem + OFF_G0 + ((role.y >> 16) & 127);
      uint32_t chk = 0;
      if (kind < 3) chk = layer_row(kind, rgrp, rj * SETUP_WARPS + w, lane, raw, T, BAR(BAR_Q), BAR(BAR_STAB), P.wout, img32);
      else if (kind == 3) chk = x1_row(rgrp, rj * SETUP_WARPS + w, lane, raw, T, BAR(BAR_Q), BAR(BAR_STAB), img32);
      if (__any_sync(0xffffffffu, chk != 0)) __trap();
      if (lane == 0) mbar_arrive(BAR(BAR_SETUP));
    }
    TL(1);
    if (is_arr) {
      asm volatile("" : "+r"(ctr0));
      *reinterpret_cast<volatile unsigned*>(smem + OFF_EPOCH) = (ctr0 >> 8) + 1;
      mbar_wait(BAR(BAR_SETUP), 0);
      TLA(30);
      asm volatile("red.relaxed.gpu.global.add.u32 [%0], 1;" ::"l"(P.ctr) : "memory");
      mbar_arrive(BAR(BAR_EPOCH));
      TLA(31);
    }
    __syncwarp();
    {
      const int c0 = (nq >> 1) * 208 + (nq & 1) * 96, nw = (nq & 1) ? 112 : 96;
      if (t < 56) {
        const int n = 2 * t;
        const uint32_t v = (n < nw) ? __ldg(reinterpret_cast<const uint32_t*>(P.b1 + c0 + n)) : 0u;
        reinterpret_cast<uint32_t*>(smem + OFF_BW)[(t & 3) * 16 + (t >> 2)] = v;
      }
      if (t >= 64 && t < 64 + 112) {
        const int k = t - 64;
        const float w = (k < nw) ? 0.5f * bf2f(__ldg(P.w2 + c0 + k)) : 0.f;
        unsigned char* base = smem + OFF_W2 + (k >> 4) * 256 + ((k >> 3) & 1) * 128;
        *reinterpret_cast<bf16*>(base + (k & 7) * 2) = __float2bfloat16(w);
        if ((k & 7) == 0) {
#pragma unroll
          for (int r = 1; r < 8; r++) *reinterpret_cast<uint4*>(base + r * 16) = make_uint4(0, 0, 0, 0);
        }
      }
      fence_proxy_async();
    }
    if (t >= 128 && t < 192) {
      int u = t - 128, l = u >> 5, qq = (u >> 3) & 3, a = u & 7;
      float wtv = 0.f;
      if (a < 6) wtv = bf2f(__ldg(P.wout + l * NF + 8 * (a >> 1) + 2 * qq + (a & 1)));
      else if (a == 6 && !(qq & 1)) wtv = bf2f(__ldg(P.wout + l * NF + 24 + (qq >> 1)));
      reinterpret_cast<float*>(smem + OFF_WTAB)[u] = wtv;
    }
    mbar_arrive(BAR(BAR_TABS));
    TL(2);
    mbar_wait(BAR(BAR_X0), 0);
    mbar_wait(BAR(BAR_TABS), 0);
  }

  TL(5);
  const uint32_t selU = (q == 0) ? 0x1010u : (q == 1) ? 0x3232u : (q == 2) ? 0x3210u : 0x7654u;
  const uint32_t selV = (q < 2) ? 0x3210u : 0x7654u;
  uint32_t bo_raw = __ldg(reinterpret_cast<const unsigned short*>(P.bout));
  mbar_wait(BAR(BAR_EPOCH), 0);
  mbar_wait(BAR(BAR_STAB), 0);
  const unsigned epoch = lds_u32(sb + OFF_EPOCH);

  uint32_t X[2][13];
  auto load_x = [&](int sl) {
    const uint4 o = *reinterpret_cast<const uint4*>(smem + OFF_LOFF + lane * 16);
    const uint32_t xo = sb + OFF_XOFF + sl * 52;
    const uint32_t tb = sb + OFF_TAB, hx = ((lane >> 3) & 1) << 4;
    const uint32_t a0 = lds_u16(xo + (o.x & 0xffff)), a1 = lds_u16(xo + (o.x >> 16));
    const uint32_t a2 = lds_u16(xo + (o.y & 0xffff)), a3 = lds_u16(xo + (o.y >> 16));
    const uint32_t a4 = lds_u16(xo + (o.z & 0xffff)), a5 = lds_u16(xo + (o.z >> 16));
    const uint32_t a6 = lds_u16(xo + (o.w & 0xffff));
    ldsm_x4_t(tb + (a0 ^ hx), X[0][0], X[1][0], X[0][1], X[1][1]);
    ldsm_x4_t(tb + (a1 ^ hx), X[0][2], X[1][2], X[0][3], X[1][3]);
    ldsm_x4_t(tb + (a2 ^ hx), X[0][4], X[1][4], X[0][5], X[1][5]);
    ldsm_x4_t(tb + (a3 ^ hx), X[0][6], X[1][6], X[0][7], X[1][7]);
    ldsm_x4_t(tb + (a4 ^ hx), X[0][8], X[1][8], X[0][9], X[1][9]);
    ldsm_x4_t(tb + (a5 ^ hx), X[0][10], X[1][10], X[0][11], X[1][11]);
    ldsm_x2_t(tb + (a6 ^ hx), X[0][12], X[1][12]);
  };
  load_x(nq * 32 + wg * 4 + w4);
#pragma unroll 1
  for (int it = 0; it < 2; it++) {
    const int sl = nq * 32 + (wg + 4 * it) * 4 + w4;
    float S = 0.f;
    uint32_t vx[2][4], vg[2][4];
    {
      float a0[28];
      if (it == 0) mbar_wait(BAR(BAR_IMG + 0), 0);
      if (it < 2) TL(6 + it * 8);
      g0_rec<0>(a0, X, selU, selV, dk, BAR(BAR_G0B), it == 0);
      wg_wait<0>();
      reg_fence(a0);
      const float4* wt = reinterpret_cast<const float4*>(smem + OFF_WTAB) + q * 2;
      float4 wa = wt[0], wb = wt[1];
#pragma unroll
      for (int r = 0; r < 2; r++) {
        S = fmaf(wa.x, a0[0 + 2 * r], S); S = fmaf(wa.y, a0[1 + 2 * r], S);
        S = fmaf(wa.z, a0[4 + 2 * r], S); S = fmaf(wa.w, a0[5 + 2 * r], S);
        S = fmaf(wb.x, a0[8 + 2 * r], S); S = fmaf(wb.y, a0[9 + 2 * r], S);
        S = fmaf(wb.z, a0[24 + 2 * r], S);
#pragma unroll
        for (int c = 0; c < 3; c++) {
          vx[r][c] = pack_bf16(a0[4 * c + 2 * r], a0[4 * c + 2 * r + 1]);
          vg[r][c] = pack_bf16(a0[12 + 4 * c + 2 * r], a0[12 + 4 * c + 2 * r + 1]);
        }
        vx[r][3] = pack_bf16(a0[24 + 2 * r], 0.f);
        vg[r][3] = pack_bf16(a0[24 + 2 * r + 1], 0.f);
      }
    }
    float g3[16], xa[16];
    if (it < 2) TL(7 + it * 8);
    if (it == 0) {
      mbar_wait(BAR(BAR_IMG + 2), 0);
      mbar_wait(BAR(BAR_IMG + 1), 0);
      mbar_wait(BAR(BAR_IMG + 3), 0);
    }
    if (it < 2) TL(8 + it * 8);
    layer_rec<0, OFF_LB>(xa, vx, X, dk);
    if (it < 2) TL(9 + it * 8);
    wg_wait<1>();
    layer_first<OFF_LA, 3>(g3, vg, X, dk);
    wg_wait<1>();
    reg_fence(xa);
    {
      const float4* wt = reinterpret_cast<const float4*>(smem + OFF_WTAB) + 8 + q * 2;
      float4 wa = wt[0], wb = wt[1];
#pragma unroll
      for (int r = 0; r < 2; r++) {
        S = fmaf(wa.x, xa[0 + 2 * r], S); S = fmaf(wa.y, xa[1 + 2 * r], S);
        S = fmaf(wa.z, xa[4 + 2 * r], S); S = fmaf(wa.w, xa[5 + 2 * r], S);
        S = fmaf(wb.x, xa[8 + 2 * r], S); S = fmaf(wb.y, xa[9 + 2 * r], S);
        S = fmaf(wb.z, xa[12 + 2 * r], S);
#pragma unroll
        for (int c = 0; c < 3; c++) vx[r][c] = pack_bf16(xa[4 * c + 2 * r], xa[4 * c + 2 * r + 1]);
        vx[r][3] = pack_bf16(xa[12 + 2 * r], 0.f);
      }
    }
    layer_rec<3, OFF_LA>(g3, vg, X, dk);
    if (it < 2) TL(10 + it * 8);
    wg_wait<1>();
    const unsigned long long* pp = P.part + (grp * 4 + (lane & 3)) * 128 + sl;
    unsigned long long pk;
    asm volatile("ld.relaxed.gpu.global.u64 %0, [%1];" : "=l"(pk) : "l"(pp) : "memory");
    float xc[16];
    layer_rec<0, OFF_LC>(xc, vx, X, dk);
    if (it == 0) load_x(sl + 16);
    wg_wait<0>();
    reg_fence(xc);
    reg_fence(g3);
    {
      float Se = 0.f;
#pragma unroll
      for (int r = 0; r < 2; r++) {
#pragma unroll
        for (int c = 0; c < 3; c++) {
          S = fmaf(g3[4 * c + 2 * r], xc[4 * c + 2 * r], S);
          S = fmaf(g3[4 * c + 2 * r + 1], xc[4 * c + 2 * r + 1], S);
        }
        Se = fmaf(g3[12 + 2 * r], xc[12 + 2 * r], Se);
      }
      if (!(q & 1)) S += Se;
    }
#pragma unroll
    for (int o = 16; o > 0; o >>= 1) S += __shfl_xor_sync(0xffffffffu, S, o);
    if (it < 2) TL(12 + it * 8);
    {
      uint32_t spin = 0;
      while (lane < 4 && (unsigned)(pk >> 32) != epoch) {
        asm volatile("ld.relaxed.gpu.global.u64 %0, [%1];" : "=l"(pk) : "l"(pp) : "memory");
        if (++spin > (1u << 24)) __trap();
      }
      __syncwarp();
      float dv = __uint_as_float((unsigned)pk);
      float d01 = dv + __shfl_xor_sync(0xffffffffu, dv, 1);
      float dsum = d01 + __shfl_xor_sync(0xffffffffu, d01, 2);
      asm volatile("" : "+r"(bo_raw));
      if (lane == 0) P.out[grp * 128 + sl] = __float2bfloat16(S + dsum + __uint_as_float(bo_raw << 16));
    }
    __syncwarp();
    if (it < 2) TL(13 + it * 8);
  }
  TL_DUMP();
}

__global__ void __launch_bounds__(128) fallback_kernel(const int* __restrict__ idx, const bf16* __restrict__ table, const bf16* __restrict__ ws,
                                                       const bf16* __restrict__ wout, const bf16* __restrict__ w1, const bf16* __restrict__ b1,
                                                       const bf16* __restrict__ w2, const bf16* __restrict__ bout, bf16* __restrict__ out) {
  __shared__ float x0[416], xa[416], xb[416], red[128];
  const int b = blockIdx.x, t = threadIdx.x;
  for (int i = t; i < 416; i += 128) { x0[i] = bf2f(table[idx[b * NF + i / 16] * 16 + (i & 15)]); xa[i] = x0[i]; }
  __syncthreads();
  float acc = 0.f;
  float* cur = xa;
  float* nxt = xb;
  for (int l = 0; l < 6; l++) {
    for (int o = t; o < 416; o += 128) {
      const int h = o >> 4, d = o & 15;
      const bf16* w = ws + (l * NF + h) * NF * NF;
      float s = 0.f;
      for (int i = 0; i < NF; i++) {
        float u = 0.f;
        for (int j = 0; j < NF; j++) u = fmaf(bf2f(w[i * NF + j]), x0[j * 16 + d], u);
        s = fmaf(u, cur[i * 16 + d], s);
      }
      nxt[o] = s;
      acc = fmaf(s, bf2f(wout[l * NF + h]), acc);
    }
    __syncthreads();
    float* tmp = cur; cur = nxt; nxt = tmp;
  }
  for (int n = t; n < 416; n += 128) {
    float h = 0.f;
    for (int k = 0; k < 416; k++) h = fmaf(x0[k], bf2f(w1[k * 416 + n]), h);
    h += bf2f(b1[n]);
    const float gl = 0.5f * h * (1.f + tanhf(0.7978845608028654f * (h + 0.044715f * h * h * h)));
    acc = fmaf(gl, bf2f(w2[n]), acc);
  }
  red[t] = acc;
  __syncthreads();
  for (int o = 64; o > 0; o >>= 1) { if (t < o) red[t] += red[t + o]; __syncthreads(); }
  if (t == 0) out[b] = __float2bfloat16(red[0] + bf2f(bout[0]));
}

typedef CUresult (*EncodeFn)(CUtensorMap*, CUtensorMapDataType, cuuint32_t, void*, const cuuint64_t*, const cuuint64_t*,
                             const cuuint32_t*, const cuuint32_t*, CUtensorMapInterleave, CUtensorMapSwizzle,
                             CUtensorMapL2promotion, CUtensorMapFloatOOBfill);

extern "C" void kernel_launch(void* const* d_in, const int* in_sizes, int n_in, void* d_out, int out_size) {
  const int* idx = (const int*)d_in[0];
  const bf16* table = (const bf16*)d_in[1];
  const bf16* ws = (const bf16*)d_in[2];
  const bf16* wout = (const bf16*)d_in[3];
  const bf16* w1 = (const bf16*)d_in[4];
  const bf16* b1 = (const bf16*)d_in[5];
  const bf16* w2 = (const bf16*)d_in[6];
  const bf16* bo = (const bf16*)d_in[7];
  bf16* out = (bf16*)d_out;

  static EncodeFn enc = nullptr;
  static Params P;
  static int n_sm = 0;
  if (!n_sm) {
    int dev = 0;
    cudaGetDevice(&dev);
    cudaDeviceGetAttribute(&n_sm, cudaDevAttrMultiProcessorCount, dev);
  }
  if (n_sm < NCTA + NHELP) {
    fallback_kernel<<<4096, 128, 0, cudaStreamPerThread>>>(idx, table, ws, wout, w1, b1, w2, bo, out);
    return;
  }
  if (!enc) {
    void* fn = nullptr;
    cudaDriverEntryPointQueryResult qr;
    cudaGetDriverEntryPoint("cuTensorMapEncodeTiled", &fn, cudaEnableDefault, &qr);
    enc = (EncodeFn)fn;
    cudaFuncSetAttribute(main_kernel, cudaFuncAttributeMaxDynamicSharedMemorySize, LAUNCH_SMEM);
    void* p;
    cudaGetSymbolAddress(&p, g_img); P.img = (unsigned char*)p;
    cudaGetSymbolAddress(&p, g_part); P.part = (unsigned long long*)p;
    cudaGetSymbolAddress(&p, g_ctr); P.ctr = (unsigned*)p;
    cudaGetSymbolAddress(&p, g_tabs); P.tabs = p;
    P.dk = make_desc(0, 128, 256, 0);
    P.dmn = make_desc(0, 8192, 1024, 1);
    for (int c = 0; c < NCTA; c++) P.role[c] = make_role(c);
  }
  P.idx = idx; P.table = table; P.ws = ws; P.wout = wout; P.b1 = b1; P.w2 = w2; P.bout = bo; P.out = out;
  TmaMaps tms;
  for (int h = 0; h < 4; h++) {
    const int c0 = (h >> 1) * 208 + (h & 1) * 96, nw = (h & 1) ? 112 : 96;
    cuuint64_t dims[2] = {(cuuint64_t)nw, 416};
    cuuint64_t strides[1] = {832};
    cuuint32_t box[2] = {64, 64};
    cuuint32_t es[2] = {1, 1};
    enc(&tms.m[h], CU_TENSOR_MAP_DATA_TYPE_BFLOAT16, 2, (void*)(w1 + c0), dims, strides, box, es,
        CU_TENSOR_MAP_INTERLEAVE_NONE, CU_TENSOR_MAP_SWIZZLE_128B, CU_TENSOR_MAP_L2_PROMOTION_L2_128B,
        CU_TENSOR_MAP_FLOAT_OOB_FILL_NONE);
  }
  main_kernel<<<NCTA + NHELP, 512, LAUNCH_SMEM, cudaStreamPerThread>>>(P, tms);
}
```

```cpp
#include <cuda_runtime.h>
#include <cuda_bf16.h>
#include <cuda.h>
#include <stdint.h>

typedef __nv_bfloat16 bf16;
#define WRITER_FENCE() fence_proxy_async_global()

constexpr int NF = 26;
constexpr int NCTA = 128;

constexpr int G0_KS = 24, G0_N = 56, G0_SLAB = G0_N * 32;
constexpr int L_KS = 43, L_SLAB = 1024;
constexpr int G0_BYTES = G0_KS * G0_SLAB;
constexpr int L_BYTES = L_KS * L_SLAB;
constexpr int IMG_BYTES = G0_BYTES + 3 * L_BYTES;

constexpr int W1_STAGES = 7;
constexpr int W1_STAGE_BYTES = 16384;
constexpr int OFF_LB = 0;
constexpr int OFF_LA = 44032;
constexpr int OFF_LC = 88064;
__host__ __device__ constexpr int w1_off(int st) { return st < 2 ? st * W1_STAGE_BYTES : OFF_LA + (st - 2) * W1_STAGE_BYTES; }
constexpr int OFF_G0 = 132096;
constexpr int OFF_IDX = 132096 + 16384;
constexpr int OFF_TAB = OFF_G0 + G0_BYTES;
constexpr int OFF_XOFF = OFF_TAB + 32000;
constexpr int OFF_BAR = OFF_XOFF + 6656;
constexpr int OFF_BW = OFF_BAR + 256;
constexpr int OFF_W2 = OFF_BW + 256;
constexpr int OFF_WTAB = OFF_W2 + 1792;
constexpr int OFF_EPOCH = OFF_WTAB + 256;
constexpr int OFF_STAB = (OFF_EPOCH + 16 + 127) / 128 * 128;
constexpr int OFF_LOFF = OFF_STAB + 3072 + 704;
constexpr int SMEM_BYTES = OFF_STAB + 4288;
static_assert(SMEM_BYTES <= 229376, "smem");
constexpr int LAUNCH_SMEM = SMEM_BYTES;

constexpr int BAR_W1FULL = 0  , BAR_W1FREE = 10  , BAR_W1DONE = 11  ,
              BAR_IMG = 14  , BAR_X0 = 18, BAR_SETUP = 19, BAR_EPOCH = 20, BAR_TABS = 21,
              BAR_Q = 22, BAR_STAB = 23, BAR_G0B = 24  , NBAR = 26;

struct TmaMaps { CUtensorMap m[4]; };
struct Params {
  const int* idx; const bf16* table; const bf16* ws; const bf16* wout; const bf16* b1; const bf16* w2; const bf16* bout;
  bf16* out;
  unsigned char* img; unsigned long long* part; unsigned* ctr; const void* tabs;
  uint64_t dk, dmn;
  uint2 role[NCTA];
};

__device__ __align__(1024) unsigned char g_img[IMG_BYTES];
__device__ unsigned long long g_part[NCTA * 128];
__device__ unsigned g_ctr;

#define GT(i) do {} while (0)
#define TL(i) do {} while (0)
#define TLP(i) do {} while (0)
#define TLA(i) do {} while (0)
#define TLW(w, i) do {} while (0)
#define TL_INIT() do {} while (0)
#define TL_START() 0
#define TL_PUT0(c) do {} while (0)
#define TL_DUMP() do {} while (0)
__device__ __forceinline__ uint32_t smem_u32(const void* p) { return (uint32_t)__cvta_generic_to_shared(p); }
__device__ __forceinline__ bool elect_one() {
  uint32_t pred;
  asm volatile("{\n.reg .pred p;\nelect.sync _|p, 0xffffffff;\nselp.u32 %0, 1, 0, p;\n}\n" : "=r"(pred));
  return pred != 0;
}
__device__ __forceinline__ void mbar_init(uint32_t bar, uint32_t cnt) {
  asm volatile("mbarrier.init.shared::cta.b64 [%0], %1;" ::"r"(bar), "r"(cnt) : "memory");
}
__device__ __forceinline__ void mbar_expect_tx(uint32_t bar, uint32_t bytes) {
  asm volatile("mbarrier.arrive.expect_tx.shared::cta.b64 _, [%0], %1;" ::"r"(bar), "r"(bytes) : "memory");
}
__device__ __forceinline__ void mbar_arrive(uint32_t bar) {
  asm volatile("mbarrier.arrive.shared::cta.b64 _, [%0];" ::"r"(bar) : "memory");
}
__device__ __forceinline__ bool mbar_try(uint32_t bar, uint32_t parity) {
  uint32_t ok;
  asm volatile("{\n.reg .pred p;\nmbarrier.try_wait.parity.shared::cta.b64 p, [%1], %2;\nselp.u32 %0, 1, 0, p;\n}\n"
               : "=r"(ok) : "r"(bar), "r"(parity) : "memory");
  return ok != 0;
}
__device__ __forceinline__ void mbar_wait(uint32_t bar, uint32_t parity) {
#pragma unroll 1
  for (uint32_t it = 0; it < (1u << 26); it++)
    if (mbar_try(bar, parity)) return;
  __trap();
}
__device__ __forceinline__ void bulk_g2s(uint32_t dst, const void* src, uint32_t bytes, uint32_t bar) {
  asm volatile("cp.async.bulk.shared::cluster.global.mbarrier::complete_tx::bytes [%0], [%1], %2, [%3];"
               ::"r"(dst), "l"(src), "r"(bytes), "r"(bar) : "memory");
}
__device__ __forceinline__ void tma_2d(uint32_t dst, const CUtensorMap* tm, int x, int y, uint32_t bar) {
  asm volatile("cp.async.bulk.tensor.2d.shared::cluster.global.mbarrier::complete_tx::bytes [%0], [%1, {%3, %4}], [%2];"
               ::"r"(dst), "l"(tm), "r"(bar), "r"(x), "r"(y) : "memory");
}
__device__ __forceinline__ void cp_async16(uint32_t dst, const void* src) {
  asm volatile("cp.async.cg.shared.global [%0], [%1], 16;" ::"r"(dst), "l"(src) : "memory");
}
__device__ __forceinline__ void fence_proxy_async() { asm volatile("fence.proxy.async.shared::cta;" ::: "memory"); }
__device__ __forceinline__ void fence_proxy_async_all() { asm volatile("fence.proxy.async;" ::: "memory"); }
template <int ID, int N> __device__ __forceinline__ void named_bar_t() { asm volatile("bar.sync %0, %1;" ::"n"(ID), "n"(N) : "memory"); }
#define named_bar(id, n) named_bar_t<id, n>()

__device__ __forceinline__ void wg_fence() { asm volatile("wgmma.fence.sync.aligned;" ::: "memory"); }
__device__ __forceinline__ void wg_commit() { asm volatile("wgmma.commit_group.sync.aligned;" ::: "memory"); }
template <int N> __device__ __forceinline__ void wg_wait() { asm volatile("wgmma.wait_group.sync.aligned %0;" ::"n"(N) : "memory"); }
template <int N> __device__ __forceinline__ void reg_fence(float (&d)[N]) {
#pragma unroll
  for (int i = 0; i < N; i++) asm volatile("" : "+f"(d[i])::"memory");
}
constexpr uint32_t SMEM_BASE = 1024;
__host__ __device__ constexpr uint64_t make_desc(uint32_t off, uint32_t lbo, uint32_t sbo, uint32_t swz) {
  return (uint64_t)(((SMEM_BASE + off) & 0x3FFFF) >> 4) | ((uint64_t)(lbo >> 4) << 16) | ((uint64_t)(sbo >> 4) << 32) | ((uint64_t)swz << 62);
}

#define ACC4(d, o) "+f"(d[o]), "+f"(d[o + 1]), "+f"(d[o + 2]), "+f"(d[o + 3])
#define ACC8(d, o) ACC4(d, o), ACC4(d, o + 4)

__device__ __forceinline__ void wgmma_rs_n32(float (&d)[16], uint32_t a0, uint32_t a1, uint32_t a2, uint32_t a3, uint64_t db, int sc) {
  asm volatile("{\n.reg .pred p;\nsetp.ne.b32 p, %21, 0;\n"
               "wgmma.mma_async.sync.aligned.m64n32k16.f32.bf16.bf16 "
               "{%0,%1,%2,%3,%4,%5,%6,%7,%8,%9,%10,%11,%12,%13,%14,%15}, {%16,%17,%18,%19}, %20, p, 1, 1, 0;\n}\n"
               : ACC8(d, 0), ACC8(d, 8)
               : "r"(a0), "r"(a1), "r"(a2), "r"(a3), "l"(db), "r"(sc));
}
__device__ __forceinline__ void wgmma_rs_n56(float (&d)[28], uint32_t a0, uint32_t a1, uint32_t a2, uint32_t a3, uint64_t db, int sc) {
  asm volatile("{\n.reg .pred p;\nsetp.ne.b32 p, %33, 0;\n"
               "wgmma.mma_async.sync.aligned.m64n56k16.f32.bf16.bf16 "
               "{%0,%1,%2,%3,%4,%5,%6,%7,%8,%9,%10,%11,%12,%13,%14,%15,%16,%17,%18,%19,%20,%21,%22,%23,%24,%25,%26,%27}, "
               "{%28,%29,%30,%31}, %32, p, 1, 1, 0;\n}\n"
               : ACC8(d, 0), ACC8(d, 8), ACC8(d, 16), ACC4(d, 24)
               : "r"(a0), "r"(a1), "r"(a2), "r"(a3), "l"(db), "r"(sc));
}
__device__ __forceinline__ void wgmma_rs_n112_tb(float (&d)[56], uint32_t a0, uint32_t a1, uint32_t a2, uint32_t a3, uint64_t db, int sc) {
  asm volatile("{\n.reg .pred p;\nsetp.ne.b32 p, %61, 0;\n"
               "wgmma.mma_async.sync.aligned.m64n112k16.f32.bf16.bf16 "
               "{%0,%1,%2,%3,%4,%5,%6,%7,%8,%9,%10,%11,%12,%13,%14,%15,%16,%17,%18,%19,%20,%21,%22,%23,%24,%25,%26,%27,%28,%29,%30,%31,%32,%33,%34,%35,%36,%37,%38,%39,%40,%41,%42,%43,%44,%45,%46,%47,%48,%49,%50,%51,%52,%53,%54,%55}, "
               "{%56,%57,%58,%59}, %60, p, 1, 1, 1;\n}\n"
               : ACC8(d, 0), ACC8(d, 8), ACC8(d, 16), ACC8(d, 24), ACC8(d, 32), ACC8(d, 40), ACC8(d, 48)
               : "r"(a0), "r"(a1), "r"(a2), "r"(a3), "l"(db), "r"(sc));
}

__device__ __forceinline__ void wgmma_rs_n8(float (&d)[4], uint32_t a0, uint32_t a1, uint32_t a2, uint32_t a3, uint64_t db, int sc) {
  asm volatile("{\n.reg .pred p;\nsetp.ne.b32 p, %9, 0;\n"
               "wgmma.mma_async.sync.aligned.m64n8k16.f32.bf16.bf16 {%0,%1,%2,%3}, {%4,%5,%6,%7}, %8, p, 1, 1, 0;\n}\n"
               : ACC4(d, 0)
               : "r"(a0), "r"(a1), "r"(a2), "r"(a3), "l"(db), "r"(sc));
}
__device__ __forceinline__ uint32_t mul_lo(uint32_t v, uint32_t r) {
  __nv_bfloat162 a = *reinterpret_cast<__nv_bfloat162*>(&v), b = *reinterpret_cast<__nv_bfloat162*>(&r);
  __nv_bfloat162 c = __hmul2(__low2bfloat162(a), b);
  return *reinterpret_cast<uint32_t*>(&c);
}
__device__ __forceinline__ uint32_t mul_hi(uint32_t v, uint32_t r) {
  __nv_bfloat162 a = *reinterpret_cast<__nv_bfloat162*>(&v), b = *reinterpret_cast<__nv_bfloat162*>(&r);
  __nv_bfloat162 c = __hmul2(__high2bfloat162(a), b);
  return *reinterpret_cast<uint32_t*>(&c);
}
__device__ __forceinline__ uint32_t mul_ew(uint32_t v, uint32_t r) {
  __nv_bfloat162 a = *reinterpret_cast<__nv_bfloat162*>(&v), b = *reinterpret_cast<__nv_bfloat162*>(&r);
  __nv_bfloat162 c = __hmul2(a, b);
  return *reinterpret_cast<uint32_t*>(&c);
}
__device__ __forceinline__ uint32_t pack_bf16(float lo, float hi) {
  uint32_t r;
  asm("cvt.rn.bf16x2.f32 %0, %1, %2;" : "=r"(r) : "f"(hi), "f"(lo));
  return r;
}
__device__ __forceinline__ float bf2f(bf16 v) { return __bfloat162float(v); }
__device__ __forceinline__ float bflo(uint32_t w) { return __uint_as_float(w << 16); }
__device__ __forceinline__ float bfhi(uint32_t w) { return __uint_as_float(w & 0xffff0000u); }

__device__ __forceinline__ void st_img(uint32_t* p, uint32_t v) {
  asm volatile("st.relaxed.gpu.global.u32 [%0], %1;" ::"l"(p), "r"(v) : "memory");
}
__device__ __forceinline__ void fence_proxy_async_global() { asm volatile("fence.proxy.async.global;" ::: "memory"); }
__device__ __forceinline__ uint32_t ld_back(const uint32_t* p) {
  uint32_t v;
  asm volatile("ld.relaxed.gpu.global.u32 %0, [%1];" : "=r"(v) : "l"(p) : "memory");
  return v;
}
__host__ __device__ constexpr int Fq(int q, int t, int e) {
  if (t == 12) return 24 + e;
  const int u = (t + 3 * q) % 12;
  const int sw = (q >= 2 && u >= 6) ? 1 : 0;
  return 2 * u + (e ^ sw);
}
constexpr int M_ONE = 26, M_NONE = 27;
struct Mono { int f1, f2; };
__host__ __device__ constexpr Mono g0_mono(int s, int q, int e) {
  if (s < 30) { const int d = s / 6 + 1, a = (s % 6) >> 1; return {Fq(q, a, s & 1), Fq(q, a + d, e)}; }
  if (s < 33) return {Fq(q, s - 30, e), Fq(q, s - 24, e)};
  if (s < 35) return {Fq(q, s - 33, e), Fq(q, s - 33, e)};
  if (s == 35) return {Fq(q, e, 0), Fq(q, e, 1)};
  if (s == 36) return {Fq(q, 2, 0), Fq(q, 2, e)};
  if (s == 37) return e ? Mono{Fq(q, 2, 1), Fq(q, 2, 1)} : Mono{M_NONE, M_NONE};
  if (s < 44) return {24 + ((s - 38) & 1), Fq(q, (s - 38) >> 1, e)};
  if (s < 47) return {Fq(q, s - 44, e), M_ONE};
  if (q == 0) return {24, 24 + e};
  if (q == 1) return e ? Mono{25, 25} : Mono{M_NONE, M_NONE};
  if (q == 2) return {24 + e, M_ONE};
  return e ? Mono{M_NONE, M_NONE} : Mono{M_ONE, M_ONE};
}
constexpr int QM_RS = 40;
constexpr int O_ZERO = 31 * QM_RS + 39, O_CONST = 30 * QM_RS + 39;
struct StaticTabs {
  uint32_t otab[48 * 8];
  uint32_t x1tab[48 * 8];
  uint16_t ltab[88 * 4];
  uint16_t loff[32 * 8];
};
constexpr StaticTabs make_tabs() {
  StaticTabs T{};
  for (int s = 0; s < 48; s++)
    for (int q = 0; q < 4; q++)
      for (int e = 0; e < 2; e++) {
        const Mono m = g0_mono(s, q, e);
        const bool none = m.f1 == M_NONE, cs = m.f1 == M_ONE, lin = m.f2 == M_ONE;
        const uint32_t o1 = none ? O_ZERO : cs ? O_CONST : m.f1 * QM_RS + (lin ? 26 : m.f2);
        const uint32_t o2 = (none || cs || lin || m.f1 == m.f2) ? O_ZERO : m.f2 * QM_RS + m.f1;
        T.otab[s * 8 + q * 2 + e] = o1 | (o2 << 16);
        const bool qd = m.f1 < NF && m.f2 < NF;
        const uint32_t y1 = qd ? m.f1 * NF + m.f2 : 0xffffu;
        const uint32_t y2 = (qd && m.f1 != m.f2) ? m.f2 * NF + m.f1 : 0xffffu;
        T.x1tab[s * 8 + q * 2 + e] = y1 | (y2 << 16);
      }
  for (int s = 0; s < 88; s++)
    for (int q = 0; q < 4; q++) {
      uint16_t v = 0;
      if (s < 85) {
        const bool ex = s >= 78;
        const int a = s / 13, k = s - 78;
        const int tt = ex ? ((k < 3) ? k : (k < 6 ? k + 3 : 12)) : s % 13;
        const int in = ex ? 24 + (q >> 1) : 8 * (a >> 1) + 2 * q + (a & 1);
        const bool valid = !(ex && tt == 12 && (q & 1));
        const int f0 = Fq(q, tt, 0);
        v = (uint16_t)((f0 >> 1) | ((f0 & 1) << 4) | ((valid ? 1 : 0) << 5) | (in << 6));
      }
      T.ltab[s * 4 + q] = v;
    }
  for (int ln = 0; ln < 32; ln++)
    for (int k = 0; k < 8; k++) {
      const int m = ln >> 3, r = ln & 7;
      const int tt = (k < 6) ? 2 * k + (m >> 1) : 12;
      T.loff[ln * 8 + k] = (uint16_t)(2 * Fq(r >> 1, tt, r & 1));
    }
  return T;
}
static_assert(sizeof(StaticTabs) == 4288, "tabs");
__device__ __align__(128) const StaticTabs g_tabs = make_tabs();

constexpr int SETUP_WARPS = 7;
constexpr int WL_BYTES = NF * NF * NF * 2;
static inline uint2 make_role(int cta) {
  int kind = 5, grp = 0, j = 0, off = 0, bytes = 0;
  const int c = cta, SL = NF * NF * 2;
  if (c < 56) { kind = 1 + c / 28; grp = (c % 28) / 7; j = c % 7; off = kind * WL_BYTES + grp * 8 * SL; bytes = (grp < 3 ? 8 : 2) * SL; }
  else if (c < 80) { kind = 0; grp = (c - 56) / 8; j = (c - 56) % 8; off = 3 * WL_BYTES + grp * 8 * SL; bytes = 8 * SL; }
  else if (c < 83) { kind = 0; grp = 3; j = c - 80; off = 3 * WL_BYTES + 24 * SL; bytes = 2 * SL; }
  else if (c < 95) { kind = 3; grp = (c - 83) / 4; j = (c - 83) % 4; off = grp * 8 * SL; bytes = 8 * SL; }
  const int delta = off & 127;
  uint2 r;
  r.x = (uint32_t)(off - delta) | ((uint32_t)kind << 24);
  r.y = (uint32_t)(bytes + delta) | ((uint32_t)delta << 16) | ((uint32_t)grp << 24) | ((uint32_t)j << 28);
  return r;
}

__device__ __forceinline__ uint32_t layer_row(int li, int grp, int r, int lane, const unsigned char* raw, const StaticTabs* T,
                                              uint32_t bar, uint32_t tbar, const bf16* __restrict__ wout, uint32_t* img32) {
  const int ks = li ? r : 13 * grp + (r >> 2), ng = li ? grp : (r & 3);
  if (ks >= 43 || (!li && grp < 3 && r >= 52)) return 0;
  const uint32_t* w32 = reinterpret_cast<const uint32_t*>(raw);
  const int n8 = lane >> 2, q = lane & 3;
  const int o = (ng < 3) ? ng * 8 + n8 : 24 + (n8 >> 2);
  const bool vo = (ng < 3) || !(n8 & 1);
  const int ob = li ? (o - 8 * grp) * 338 : o * 13 - 8 * grp * 338;
  const int si = li ? 13 : 338;
  uint32_t bias = 0;
  if (vo && ks == 42 && li == 0 && q == 0) bias = (uint32_t)__ldg(reinterpret_cast<const unsigned short*>(wout) + 2 * NF + o);
  uint32_t* dst = img32 + G0_BYTES / 4 + li * (L_BYTES / 4) + (ks * 4 + ng) * 64 + lane;
  mbar_wait(tbar, 0);
  const uint32_t e0 = T->ltab[8 * ks + q], e1 = T->ltab[8 * ks + 4 + q];
  const bool v0 = vo && (e0 & 32), v1 = vo && (e1 & 32);
  const int s0 = v0 ? ob + (e0 >> 6) * si + (e0 & 15) : 0, s1 = v1 ? ob + (e1 >> 6) * si + (e1 & 15) : 0;
  TL(33);
  mbar_wait(bar, 0);
  TL(36);
  uint32_t w0 = w32[s0], w1 = w32[s1];
  w0 = (e0 & 16) ? __funnelshift_l(w0, w0, 16) : w0;
  w1 = (e1 & 16) ? __funnelshift_l(w1, w1, 16) : w1;
  w0 = v0 ? w0 : 0u;
  w1 = v1 ? w1 : bias;
  st_img(dst, w0); st_img(dst + 32, w1);
  const uint32_t chk = (ld_back(dst) ^ w0) | (ld_back(dst + 32) ^ w1);
  WRITER_FENCE();
  return chk;
}
__device__ __forceinline__ float x1_val(const unsigned short* wh, uint32_t e) {
  const uint32_t a = e & 0xffff, b = e >> 16;
  const uint32_t x = wh[a == 0xffff ? 0 : a], y = wh[b == 0xffff ? 0 : b];
  return (a == 0xffff ? 0.f : __uint_as_float(x << 16)) + (b == 0xffff ? 0.f : __uint_as_float(y << 16));
}
__device__ __forceinline__ uint32_t x1_row(int ng, int ks, int lane, const unsigned char* raw, const StaticTabs* T, uint32_t bar, uint32_t tbar, uint32_t* img32) {
  if (ks >= 24) return 0;
  const int n8 = lane >> 2, q = lane & 3;
  const unsigned short* wh = reinterpret_cast<const unsigned short*>(raw) + n8 * (NF * NF);
  uint32_t* dst = img32 + ks * (G0_SLAB / 4) + ng * 64 + lane;
  mbar_wait(tbar, 0);
  const uint2 ea = *reinterpret_cast<const uint2*>(&T->x1tab[16 * ks + 2 * q]), eb = *reinterpret_cast<const uint2*>(&T->x1tab[16 * ks + 8 + 2 * q]);
  mbar_wait(bar, 0);
  const uint32_t w0 = pack_bf16(x1_val(wh, ea.x), x1_val(wh, ea.y)), w1 = pack_bf16(x1_val(wh, eb.x), x1_val(wh, eb.y));
  st_img(dst, w0); st_img(dst + 32, w1);
  const uint32_t chk = (ld_back(dst) ^ w0) | (ld_back(dst + 32) ^ w1);
  WRITER_FENCE();
  return chk;
}

constexpr int NHELP = 4;
constexpr int H_MS = 32 * QM_RS + 4;
constexpr int H_W5 = 0, H_W4 = 35328, H_W0 = 70656, H_TAB = 73472, H_B = 77824, H_M = 82944, H_XE = H_M + 8 * H_MS * 4, H_BAR = H_XE + 1536;
__device__ __forceinline__ int wf_off(int b, int h) { return (b >> 3) * 512 + (h >> 3) * 128 + (b & 7) * 16 + (h & 7) * 2; }
__device__ __forceinline__ void helper_role(int hk, const Params& P, unsigned char* smem, uint32_t sb) {
  const int t = threadIdx.x, warp = __shfl_sync(0xffffffffu, t >> 5, 0), lane = t & 31;
  const uint32_t d5bar = sb + H_BAR, d4bar = sb + H_BAR + 8, tbar = sb + H_BAR + 16;
  const unsigned char* wsb = reinterpret_cast<const unsigned char*>(P.ws);
  unsigned char* WB = smem + H_B;
  float* M = reinterpret_cast<float*>(smem + H_M);
  constexpr uint32_t W5B = WL_BYTES + ((5 * WL_BYTES) & 127), W4B = WL_BYTES + ((4 * WL_BYTES) & 127);
  if (warp < 3 && elect_one()) {
    mbar_init(sb + H_BAR + 8 * warp, 1);
    asm volatile("fence.mbarrier_init.release.cluster;" ::: "memory");
    if (warp == 0) {
      mbar_expect_tx(d5bar, W5B);
#pragma unroll
      for (int c = 0; c < 5; c++)
        bulk_g2s(sb + H_W5 + c * 8192, wsb + ((5 * WL_BYTES) & ~127) + c * 8192, c < 4 ? 8192u : W5B - 4 * 8192, d5bar);
    }
  }
  reinterpret_cast<uint32_t*>(WB)[t] = 0;
  __syncthreads();
  if (warp >= 5 && warp < 12 && elect_one()) {
    if (warp < 10) {
      const int c = warp - 5;
      if (c == 0) mbar_expect_tx(d4bar, W4B + (hk == 3 ? 2768 : 0));
      bulk_g2s(sb + H_W4 + c * 8192, wsb + ((4 * WL_BYTES) & ~127) + c * 8192, c < 4 ? 8192u : W4B - 4 * 8192, d4bar);
    } else if (warp == 10) {
      mbar_expect_tx(tbar, sizeof(StaticTabs));
      bulk_g2s(sb + H_TAB, P.tabs, sizeof(StaticTabs), tbar);
    } else if (hk == 3) {
      bulk_g2s(sb + H_W0, wsb + ((24 * NF * NF * 2) & ~127), 2768, d4bar);
    }
  }
  const unsigned short* wo16 = reinterpret_cast<const unsigned short*>(P.wout);
  uint32_t c5[13];
#pragma unroll
  for (int k = 0; k < 13; k++) c5[k] = __ldg(reinterpret_cast<const uint32_t*>(P.wout + 5 * NF) + k);
  unsigned short wv = 0;
  const int io0 = (hk < 3) ? 8 * hk : 24;
  if (t >= 352 && t < 352 + NF) wv = __ldg(wo16 + 4 * NF + t - 352);
  else if (t >= 384 && t < 392 && io0 + t - 384 < NF) wv = __ldg(wo16 + 3 * NF + io0 + t - 384);
  const StaticTabs* T = reinterpret_cast<const StaticTabs*>(smem + H_TAB);
  const int n8 = lane >> 2, q = lane & 3, g = n8;
  const int fil = (hk < 3) ? n8 : (n8 >> 2);
  const bool fx1 = (hk == 3) && !(n8 & 1);
  uint32_t* dst = reinterpret_cast<uint32_t*>(P.img) + (warp >> 1) * (G0_SLAB / 4) + (warp & 1) * 32 + (3 + hk) * 64 + lane;
  if (t >= 352 && t < 352 + NF) *reinterpret_cast<unsigned short*>(WB + wf_off(26, t - 352)) = wv;
  if (t >= 384 && t < 392) { M[(t - 384) * H_MS + O_ZERO] = 0.f; M[(t - 384) * H_MS + O_CONST] = __uint_as_float((uint32_t)wv << 16); }
  mbar_wait(d5bar, 0);
  if (t < 338) {
    const uint32_t* w5 = reinterpret_cast<const uint32_t*>(smem + H_W5 + ((5 * WL_BYTES) & 127)) + t;
    float s0 = 0.f, s1 = 0.f, s2 = 0.f, s3 = 0.f;
#pragma unroll
    for (int k = 0; k < 13; k++) {
      const uint32_t wa = w5[(2 * k) * 338], wb = w5[(2 * k + 1) * 338];
      const float ca = bflo(c5[k]), cb = bfhi(c5[k]);
      s0 = fmaf(ca, bflo(wa), s0); s1 = fmaf(ca, bfhi(wa), s1);
      s2 = fmaf(cb, bflo(wb), s2); s3 = fmaf(cb, bfhi(wb), s3);
    }
    const int h = (t * 79) >> 10, tp = t - 13 * h;
    *reinterpret_cast<bf16*>(WB + wf_off(2 * tp, h)) = __float2bfloat16(s0 + s2);
    *reinterpret_cast<bf16*>(WB + wf_off(2 * tp + 1, h)) = __float2bfloat16(s1 + s3);
  }
  fence_proxy_async();
  mbar_wait(tbar, 0);
  uint2 fot[3];
#pragma unroll
  for (int r = 0; r < 3; r++) fot[r] = *reinterpret_cast<const uint2*>(&T->otab[(warp + 16 * r) * 8 + q * 2]);
  mbar_wait(d4bar, 0);
  const int wgi = warp >> 2, il = 2 * wgi + ((warp >> 1) & 1), mt = warp & 1;
  const bool mma_wg = (hk < 3) || (wgi == 0);
  uint32_t a[2][4];
  if (mma_wg) {
    const unsigned short* A = reinterpret_cast<const unsigned short*>(smem + H_W4 + ((4 * WL_BYTES) & 127)) + (io0 + il) * NF + mt * 16 + g;
#pragma unroll
    for (int kk = 0; kk < 2; kk++) {
#pragma unroll
      for (int jj = 0; jj < 4; jj++) {
        const int k = kk * 16 + 2 * q + (jj >> 1) * 8, mo = (jj & 1) * 8;
        const int kc = (k < NF) ? k : 0;
        const uint32_t lo = A[kc * (NF * NF) + mo], hi = A[(kc + 1) * (NF * NF) + mo];
        a[kk][jj] = (k < NF) ? (lo | (hi << 16)) : 0u;
      }
    }
  }
  if (hk == 3) {
    const int u0 = (warp >= 4) ? t - 128 : -1;
    if (u0 >= 0) {
      const int sl = u0 >> 3, xl = (u0 >> 2) & 1, xq = u0 & 3;
      const uint2 xt = *reinterpret_cast<const uint2*>(&T->x1tab[sl * 8 + xq * 2]);
      const unsigned short* wh = reinterpret_cast<const unsigned short*>(smem + H_W0 + ((24 * NF * NF * 2) & 127)) + xl * (NF * NF);
      reinterpret_cast<uint32_t*>(smem + H_XE)[u0] = pack_bf16(x1_val(wh, xt.x), x1_val(wh, xt.y));
    }
  }
  __syncthreads();
  if (mma_wg) {
    float c[16];
    wg_fence();
    wgmma_rs_n32(c, a[0][0], a[0][1], a[0][2], a[0][3], make_desc(H_B, 128, 512, 0), 0);
    wgmma_rs_n32(c, a[1][0], a[1][1], a[1][2], a[1][3], make_desc(H_B + 256, 128, 512, 0), 1);
    wg_commit();
    wg_wait<0>();
    reg_fence(c);
    float* Mi = M + il * H_MS;
#pragma unroll
    for (int n = 0; n < 4; n++) {
      *reinterpret_cast<float2*>(&Mi[(mt * 16 + g) * QM_RS + n * 8 + 2 * q]) = make_float2(c[4 * n], c[4 * n + 1]);
      *reinterpret_cast<float2*>(&Mi[(mt * 16 + g + 8) * QM_RS + n * 8 + 2 * q]) = make_float2(c[4 * n + 2], c[4 * n + 3]);
    }
  }
  __syncthreads();
  uint32_t val[3], chk = 0;
#pragma unroll
  for (int r = 0; r < 3; r++) {
    const float* Mf = M + fil * H_MS;
    const float v0 = Mf[fot[r].x & 0xffff] + Mf[fot[r].x >> 16], v1 = Mf[fot[r].y & 0xffff] + Mf[fot[r].y >> 16];
    const uint32_t xe = reinterpret_cast<const uint32_t*>(smem + H_XE)[(warp + 16 * r) * 8 + (n8 >> 2) * 4 + q];
    val[r] = fx1 ? xe : pack_bf16(v0, v1);
    st_img(dst + r * 8 * (G0_SLAB / 4), val[r]);
  }
#pragma unroll
  for (int r = 0; r < 3; r++) chk |= ld_back(dst + r * 8 * (G0_SLAB / 4)) ^ val[r];
  WRITER_FENCE();
  if (__any_sync(0xffffffffu, chk != 0)) __trap();
  __syncthreads();
  if (t == 0) asm volatile("red.relaxed.gpu.global.add.u32 [%0], 32;" ::"l"(P.ctr) : "memory");
}

template <int S>
__device__ __forceinline__ uint32_t l_prod(const uint32_t (&vp)[4], const uint32_t (&X)[13]) {
  if constexpr (S < 78) {
    constexpr int a = S / 13, t = S % 13;
    return (a & 1) ? mul_hi(vp[a >> 1], X[t]) : mul_lo(vp[a >> 1], X[t]);
  } else if constexpr (S < 85) {
    constexpr int k = S - 78;
    constexpr int t = (k < 3) ? k : (k < 6 ? k + 3 : 12);
    return mul_lo(vp[3], X[t]);
  } else {
    return 0x00003F80u;
  }
}
template <int S>
__device__ __forceinline__ uint32_t g0_prod(const uint32_t (&X)[13], uint32_t selU, uint32_t selV) {
  if constexpr (S < 30) {
    constexpr int d = S / 6 + 1, a = (S % 6) >> 1;
    return (S & 1) ? mul_hi(X[a], X[a + d]) : mul_lo(X[a], X[a + d]);
  } else if constexpr (S < 33) {
    return mul_ew(X[S - 30], X[S - 24]);
  } else if constexpr (S < 35) {
    return mul_ew(X[S - 33], X[S - 33]);
  } else if constexpr (S == 35) {
    return mul_ew(__byte_perm(X[0], X[1], 0x5410), __byte_perm(X[0], X[1], 0x7632));
  } else if constexpr (S == 36) {
    return mul_lo(X[2], X[2]);
  } else if constexpr (S == 37) {
    return mul_hi(X[2], X[2]);
  } else if constexpr (S < 44) {
    constexpr int a = (S - 38) >> 1;
    return ((S - 38) & 1) ? mul_hi(X[12], X[a]) : mul_lo(X[12], X[a]);
  } else if constexpr (S < 47) {
    return X[S - 44];
  } else {
    return mul_ew(__byte_perm(X[12], 0x3F803F80u, selU), __byte_perm(X[12], 0x3F803F80u, selV));
  }
}

constexpr int NBK = 4;

template <int KS, int KE>
__device__ __forceinline__ void l_fill(uint32_t (*A)[4], const uint32_t (&vp)[2][4], const uint32_t (&X)[2][13]) {
  A[0][0] = l_prod<2 * KS>(vp[0], X[0]);
  A[0][1] = l_prod<2 * KS>(vp[1], X[1]);
  A[0][2] = l_prod<2 * KS + 1>(vp[0], X[0]);
  A[0][3] = l_prod<2 * KS + 1>(vp[1], X[1]);
  if constexpr (KS + 1 < KE) l_fill<KS + 1, KE>(A + 1, vp, X);
}
template <int KS, int OFF>
__device__ __forceinline__ void layer_rec(float (&d)[16], const uint32_t (&vp)[2][4], const uint32_t (&X)[2][13], uint64_t dk) {
  constexpr int KE = (KS + NBK < L_KS) ? KS + NBK : L_KS;
  uint32_t A[NBK][4];
  l_fill<KS, KE>(A, vp, X);
  wg_fence();
#pragma unroll
  for (int k = 0; k < KE - KS; k++)
    wgmma_rs_n32(d, A[k][0], A[k][1], A[k][2], A[k][3], dk + (uint64_t)((OFF + (KS + k) * L_SLAB) >> 4), (KS + k) > 0);
  wg_commit();
  if constexpr (KE < L_KS) {
    wg_wait<1>();
    layer_rec<KE, OFF>(d, vp, X, dk);
  }
}
template <int OFF, int NK>
__device__ __forceinline__ void layer_first(float (&d)[16], const uint32_t (&vp)[2][4], const uint32_t (&X)[2][13], uint64_t dk) {
  uint32_t A[NK][4];
  l_fill<0, NK>(A, vp, X);
  wg_fence();
#pragma unroll
  for (int k = 0; k < NK; k++) wgmma_rs_n32(d, A[k][0], A[k][1], A[k][2], A[k][3], dk + (uint64_t)((OFF + k * L_SLAB) >> 4), k > 0);
  wg_commit();
}
template <int KS, int KE>
__device__ __forceinline__ void g0_fill(uint32_t (*A)[4], const uint32_t (&X)[2][13], uint32_t selU, uint32_t selV) {
  A[0][0] = g0_prod<2 * KS>(X[0], selU, selV);
  A[0][1] = g0_prod<2 * KS>(X[1], selU, selV);
  A[0][2] = g0_prod<2 * KS + 1>(X[0], selU, selV);
  A[0][3] = g0_prod<2 * KS + 1>(X[1], selU, selV);
  if constexpr (KS + 1 < KE) g0_fill<KS + 1, KE>(A + 1, X, selU, selV);
}
template <int B0>
__device__ __forceinline__ void g0_rec(float (&d)[28], const uint32_t (&X)[2][13], uint32_t selU, uint32_t selV, uint64_t dk, uint32_t bar2, bool first) {
  constexpr int KS = B0 * NBK;
  if constexpr (KS == 8) { if (first) mbar_wait(bar2, 0); }
  if constexpr (KS == 16) { if (first) mbar_wait(bar2 + 8, 0); }
  constexpr int KE = (KS + NBK < G0_KS) ? KS + NBK : G0_KS;
  uint32_t A[NBK][4];
  g0_fill<KS, KE>(A, X, selU, selV);
  wg_fence();
#pragma unroll
  for (int k = 0; k < KE - KS; k++)
    wgmma_rs_n56(d, A[k][0], A[k][1], A[k][2], A[k][3], dk + (uint64_t)((OFF_G0 + (KS + k) * G0_SLAB) >> 4), (KS + k) > 0);
  wg_commit();
  if constexpr (KE < G0_KS) {
    wg_wait<1>();
    g0_rec<B0 + 1>(d, X, selU, selV, dk, bar2, first);
  }
}

__device__ __forceinline__ void ldsm_x4_t(uint32_t addr, uint32_t& r0, uint32_t& r1, uint32_t& r2, uint32_t& r3) {
  asm volatile("ldmatrix.sync.aligned.m8n8.x4.trans.shared.b16 {%0,%1,%2,%3}, [%4];"
               : "=r"(r0), "=r"(r1), "=r"(r2), "=r"(r3) : "r"(addr) : "memory");
}
__device__ __forceinline__ void ldsm_x2_t(uint32_t addr, uint32_t& r0, uint32_t& r1) {
  asm volatile("ldmatrix.sync.aligned.m8n8.x2.trans.shared.b16 {%0,%1}, [%2];" : "=r"(r0), "=r"(r1) : "r"(addr) : "memory");
}
__device__ __forceinline__ float tanh_fast(float x) { float y; asm("tanh.approx.f32 %0, %1;" : "=f"(y) : "f"(x)); return y; }

__device__ __forceinline__ uint32_t gelu2_pair(float lo, float hi, uint32_t bias) {
  uint32_t x = pack_bf16(lo, hi), t, u;
  asm("add.rn.bf16x2 %0, %0, %1;" : "+r"(x) : "r"(bias));
  asm("mul.rn.bf16x2 %0, %1, %1;" : "=r"(t) : "r"(x));
  asm("fma.rn.bf16x2 %0, %0, %1, %2;" : "+r"(t) : "r"(0x3D123D12u), "r"(0x3F4C3F4Cu));
  asm("mul.rn.bf16x2 %0, %1, %2;" : "=r"(u) : "r"(x), "r"(t));
  asm("tanh.approx.bf16x2 %0, %0;" : "+r"(u));
  asm("fma.rn.bf16x2 %0, %1, %0, %1;" : "+r"(u) : "r"(x));
  return u;
}

__device__ __forceinline__ void ldsm_x4(uint32_t addr, uint32_t (&r)[4]) {
  asm volatile("ldmatrix.sync.aligned.m8n8.x4.shared.b16 {%0,%1,%2,%3}, [%4];"
               : "=r"(r[0]), "=r"(r[1]), "=r"(r[2]), "=r"(r[3]) : "r"(addr) : "memory");
}
__device__ __forceinline__ uint32_t lds_u16(uint32_t addr) {
  unsigned short v;
  asm volatile("ld.shared.u16 %0, [%1];" : "=h"(v) : "r"(addr) : "memory");
  return v;
}
__device__ __forceinline__ uint32_t lds_u32(uint32_t addr) {
  uint32_t v;
  asm volatile("ld.shared.u32 %0, [%1];" : "=r"(v) : "r"(addr) : "memory");
  return v;
}

__global__ void __launch_bounds__(512, 1)
main_kernel(const __grid_constant__ Params P, const __grid_constant__ TmaMaps tms) {
  extern __shared__ __align__(1024) unsigned char smem[];
  const uint32_t sb = smem_u32(smem);
  const int tid = threadIdx.x, warp = __shfl_sync(0xffffffffu, tid >> 5, 0), lane = tid & 31;
  if (blockIdx.x < NHELP) {
    helper_role(blockIdx.x, P, smem, sb);
    return;
  }
  const int cta = blockIdx.x - NHELP, nq = cta & 3, grp = cta >> 2;
  const uint2 role = P.role[cta];
  const uint32_t bar0 = sb + OFF_BAR;
  auto BAR = [&](int i) { return bar0 + 8 * i; };
  const int wg = warp >> 2, w4 = warp & 3, g = lane >> 2, q = lane & 3;
  const uint64_t dk = P.dk;
  const long long tl_c0 = TL_START();
  TL_INIT();
  TL_PUT0(tl_c0);

  if (tid < 256) {
    const unsigned char* isrc = reinterpret_cast<const unsigned char*>(P.idx + grp * 128 * NF);
#pragma unroll
    for (int k = 0; k < 4; k++) {
      const int c = tid + 256 * k;
      if (c < 832) cp_async16(sb + OFF_IDX + c * 16, isrc + c * 16);
    }
    asm volatile("cp.async.commit_group;" ::: "memory");
#pragma unroll
    for (int k = 0; k < 8; k++) {
      const int c = tid + 256 * k;
      if (c < 2000) cp_async16(sb + OFF_TAB + ((c ^ ((c >> 3) & 1)) << 4), reinterpret_cast<const unsigned char*>(P.table) + c * 16);
    }
    asm volatile("cp.async.commit_group;" ::: "memory");
  }
  if (elect_one()) {
    mbar_init(BAR(warp), (warp == BAR_W1FREE || warp == BAR_W1DONE) ? 2 : 1);
    if (warp < NBAR - 16)
      mbar_init(BAR(16 + warp), (16 + warp == BAR_X0) ? 256 : (16 + warp == BAR_SETUP) ? SETUP_WARPS : (16 + warp == BAR_TABS) ? 224 : 1);
    asm volatile("fence.mbarrier_init.release.cluster;" ::: "memory");
  }
  __syncthreads();
  TL(26);

  if (warp == 15) {
    if (elect_one()) {
      mbar_expect_tx(BAR(BAR_STAB), sizeof(StaticTabs));
      bulk_g2s(sb + OFF_STAB, P.tabs, sizeof(StaticTabs), BAR(BAR_STAB));
      if ((sb & 0x3FFFF) != SMEM_BASE) __trap();
      const CUtensorMap* tm0 = &tms.m[nq];
      asm volatile("prefetch.tensormap [%0];" ::"l"(tm0) : "memory");
#pragma unroll
      for (int st = 0; st < W1_STAGES; st++) {
        if (st == 1 && (role.x >> 24) < 5) mbar_wait(BAR(BAR_Q), 0);
        mbar_expect_tx(BAR(BAR_W1FULL + st), W1_STAGE_BYTES);
        tma_2d(sb + w1_off(st), tm0, 0, st * 64, BAR(BAR_W1FULL + st));
        tma_2d(sb + w1_off(st) + 8192, tm0, 64, st * 64, BAR(BAR_W1FULL + st));
      }
      TLP(22);
      mbar_wait(BAR(BAR_EPOCH), 0);
      TLP(23);
      const unsigned target = lds_u32(sb + OFF_EPOCH) << 8;
      {
        unsigned v;
        uint32_t it = 0;
#pragma unroll 1
        do {
          asm volatile("ld.relaxed.gpu.global.u32 %0, [%1];" : "=r"(v) : "l"(P.ctr) : "memory");
          if (++it > (1u << 22)) __trap();
        } while ((int)(v - target) < 0);
      }
      mbar_wait(BAR(BAR_X0), 0);
      TLP(24);
      mbar_expect_tx(BAR(BAR_IMG + 0), G0_BYTES / 3);
      mbar_expect_tx(BAR(BAR_G0B), G0_BYTES / 3);
      mbar_expect_tx(BAR(BAR_G0B + 1), G0_BYTES / 3);
#pragma unroll
      for (int i = 0; i < 6; i++)
        bulk_g2s(sb + OFF_G0 + i * (G0_BYTES / 6), P.img + i * (G0_BYTES / 6), G0_BYTES / 6, i < 2 ? BAR(BAR_IMG + 0) : BAR(BAR_G0B + (i - 2) / 2));
      mbar_wait(BAR(BAR_W1FREE), 0);
      mbar_expect_tx(BAR(BAR_IMG + 2), L_BYTES);
#pragma unroll
      for (int i = 0; i < 4; i++)
        bulk_g2s(sb + OFF_LB + i * (L_BYTES / 4), P.img + G0_BYTES + L_BYTES + i * (L_BYTES / 4), L_BYTES / 4, BAR(BAR_IMG + 2));
      mbar_wait(BAR(BAR_W1DONE), 0);
      mbar_expect_tx(BAR(BAR_IMG + 1), L_BYTES);
      mbar_expect_tx(BAR(BAR_IMG + 3), L_BYTES);
#pragma unroll
      for (int i = 0; i < 2; i++)
        bulk_g2s(sb + OFF_LA + i * (L_BYTES / 2), P.img + G0_BYTES + i * (L_BYTES / 2), L_BYTES / 2, BAR(BAR_IMG + 1));
#pragma unroll
      for (int i = 0; i < 2; i++)
        bulk_g2s(sb + OFF_LC + i * (L_BYTES / 2), P.img + G0_BYTES + 2 * L_BYTES + i * (L_BYTES / 2), L_BYTES / 2, BAR(BAR_IMG + 3));
      TLP(25);
    }
    __syncwarp();
    mbar_wait(BAR(BAR_X0), 0);
    mbar_wait(BAR(BAR_TABS), 0);
  } else if (wg < 2) {
    asm volatile("cp.async.wait_group 1;" ::: "memory");
    named_bar(1, 256);
#pragma unroll
    for (int k = 0; k < 7; k++) {
      const int p = tid + 256 * k;
      if (p < 64 * NF) {
        const uint2 v = reinterpret_cast<const uint2*>(smem + OFF_IDX)[p];
        const uint32_t o0 = v.x * 32 + ((v.x >> 2) & 1) * 16, o1 = v.y * 32 + ((v.y >> 2) & 1) * 16;
        reinterpret_cast<uint32_t*>(smem + OFF_XOFF)[p] = o0 | (o1 << 16);
      }
    }
    TL(1);
    asm volatile("cp.async.wait_all;" ::: "memory");
    mbar_arrive(BAR(BAR_X0));
    mbar_wait(BAR(BAR_X0), 0);
    TL(3);
    float acc[56];
    {
      const uint32_t xo = sb + OFF_XOFF + (wg * 64 + w4 * 16 + (lane & 15)) * 52;
      const uint32_t tb = sb + OFF_TAB, hx = (lane >> 4) << 4;
      const uint64_t db0 = P.dmn;
      uint32_t A[3][2][4];
#pragma unroll
      for (int pr = 0; pr < 2; pr++) {
        const uint32_t oa = lds_u32(xo + 4 * pr);
        ldsm_x4(tb + ((oa & 0xffff) ^ hx), A[pr][0]); ldsm_x4(tb + ((oa >> 16) ^ hx), A[pr][1]);
      }
#pragma unroll
      for (int pr = 0; pr < 13; pr++) {
        const int st = pr >> 1;
        uint32_t oa = 0;
        if (pr + 2 < 13) oa = lds_u32(xo + 4 * (pr + 2));
        if (!(pr & 1)) mbar_wait(BAR(BAR_W1FULL + st), 0);
        if (pr == 0) TL(28); if (pr == 6) TL(29);
        const uint64_t db = db0 + (uint64_t)((w1_off(st) + (pr & 1) * 4096) >> 4);
        wg_fence();
        wgmma_rs_n112_tb(acc, A[pr % 3][0][0], A[pr % 3][0][1], A[pr % 3][0][2], A[pr % 3][0][3], db, pr > 0);
        wgmma_rs_n112_tb(acc, A[pr % 3][1][0], A[pr % 3][1][1], A[pr % 3][1][2], A[pr % 3][1][3], db + (2048 >> 4), 1);
        wg_commit();
        wg_wait<1>();
        if (pr == 4 && (tid & 127) == 0) mbar_arrive(BAR(BAR_W1FREE));
        if (pr + 2 < 13) { ldsm_x4(tb + ((oa & 0xffff) ^ hx), A[(pr + 2) % 3][0]); ldsm_x4(tb + ((oa >> 16) ^ hx), A[(pr + 2) % 3][1]); }
      }
      wg_wait<0>();
      reg_fence(acc);
      if ((tid & 127) == 0) mbar_arrive(BAR(BAR_W1DONE));
    }
    TL(4);
    float dot[4];
    {
      mbar_wait(BAR(BAR_TABS), 0);
      uint32_t bb[16];
      const uint4* bp = reinterpret_cast<const uint4*>(smem + OFF_BW + q * 64);
#pragma unroll
      for (int i = 0; i < 4; i++) { const uint4 v = bp[i]; bb[4 * i] = v.x; bb[4 * i + 1] = v.y; bb[4 * i + 2] = v.z; bb[4 * i + 3] = v.w; }
      uint32_t H[14][2];
#pragma unroll
      for (int c = 0; c < 14; c++) {
        H[c][0] = gelu2_pair(acc[4 * c], acc[4 * c + 1], bb[c]);
        H[c][1] = gelu2_pair(acc[4 * c + 2], acc[4 * c + 3], bb[c]);
      }
      wg_fence();
#pragma unroll
      for (int j = 0; j < 7; j++)
        wgmma_rs_n8(dot, H[2 * j][0], H[2 * j][1], H[2 * j + 1][0], H[2 * j + 1][1], dk + (uint64_t)((OFF_W2 + j * 256) >> 4), j > 0);
      wg_commit();
      wg_wait<0>();
      reg_fence(dot);
    }
    __syncwarp();
    mbar_wait(BAR(BAR_EPOCH), 0);
    if (q == 0) {
      const unsigned epoch = lds_u32(sb + OFF_EPOCH);
#pragma unroll
      for (int r = 0; r < 2; r++) {
        const int row = wg * 64 + w4 * 16 + g + 8 * r;
        const unsigned long long pk = ((unsigned long long)epoch << 32) | (unsigned long long)__float_as_uint(dot[2 * r]);
        asm volatile("st.relaxed.gpu.global.u64 [%0], %1;" ::"l"(P.part + cta * 128 + row), "l"(pk) : "memory");
      }
    }
    __syncwarp();
  } else {
    const int t = tid - 256;
    const bool is_arr = (t == 192);
    unsigned ctr0 = 0;
    if (is_arr) asm volatile("ld.relaxed.gpu.global.u32 %0, [%1];" : "=r"(ctr0) : "l"(P.ctr) : "memory");
    {
      const int kind = role.x >> 24, w = warp - 8, rgrp = (role.y >> 24) & 15, rj = role.y >> 28;
      const unsigned char* wsb = reinterpret_cast<const unsigned char*>(P.ws);
      if (kind < 5 && elect_one()) {
        const uint32_t bytes = role.y & 0xffff;
        const uint32_t o = w * 8192;
        if (w == 0) mbar_expect_tx(BAR(BAR_Q), bytes);
        if (o < bytes) bulk_g2s(sb + OFF_G0 + o, wsb + (role.x & 0xffffff) + o, min(bytes - o, 8192u), BAR(BAR_Q));
      }
      TL(40);
      __syncwarp();
      const StaticTabs* T = reinterpret_cast<const StaticTabs*>(smem + OFF_STAB);
      uint32_t* img32 = reinterpret_cast<uint32_t*>(P.img);
      const unsigned char* raw = smem + OFF_G0 + ((role.y >> 16) & 127);
      uint32_t chk = 0;
      if (kind < 3) chk = layer_row(kind, rgrp, rj * SETUP_WARPS + w, lane, raw, T, BAR(BAR_Q), BAR(BAR_STAB), P.wout, img32);
      else if (kind == 3) chk = x1_row(rgrp, rj * SETUP_WARPS + w, lane, raw, T, BAR(BAR_Q), BAR(BAR_STAB), img32);
      if (__any_sync(0xffffffffu, chk != 0)) __trap();
      if (lane == 0) mbar_arrive(BAR(BAR_SETUP));
    }
    TL(1);
    if (is_arr) {
      asm volatile("" : "+r"(ctr0));
      *reinterpret_cast<volatile unsigned*>(smem + OFF_EPOCH) = (ctr0 >> 8) + 1;
      mbar_wait(BAR(BAR_SETUP), 0);
      TLA(30);
      asm volatile("red.relaxed.gpu.global.add.u32 [%0], 1;" ::"l"(P.ctr) : "memory");
      mbar_arrive(BAR(BAR_EPOCH));
      TLA(31);
    }
    __syncwarp();
    {
      const int c0 = (nq >> 1) * 208 + (nq & 1) * 96, nw = (nq & 1) ? 112 : 96;
      if (t < 56) {
        const int n = 2 * t;
        const uint32_t v = (n < nw) ? __ldg(reinterpret_cast<const uint32_t*>(P.b1 + c0 + n)) : 0u;
        reinterpret_cast<uint32_t*>(smem + OFF_BW)[(t & 3) * 16 + (t >> 2)] = v;
      }
      if (t >= 64 && t < 64 + 112) {
        const int k = t - 64;
        const float w = (k < nw) ? 0.5f * bf2f(__ldg(P.w2 + c0 + k)) : 0.f;
        unsigned char* base = smem + OFF_W2 + (k >> 4) * 256 + ((k >> 3) & 1) * 128;
        *reinterpret_cast<bf16*>(base + (k & 7) * 2) = __float2bfloat16(w);
        if ((k & 7) == 0) {
#pragma unroll
          for (int r = 1; r < 8; r++) *reinterpret_cast<uint4*>(base + r * 16) = make_uint4(0, 0, 0, 0);
        }
      }
      fence_proxy_async();
    }
    if (t >= 128 && t < 192) {
      int u = t - 128, l = u >> 5, qq = (u >> 3) & 3, a = u & 7;
      float wtv = 0.f;
      if (a < 6) wtv = bf2f(__ldg(P.wout + l * NF + 8 * (a >> 1) + 2 * qq + (a & 1)));
      else if (a == 6 && !(qq & 1)) wtv = bf2f(__ldg(P.wout + l * NF + 24 + (qq >> 1)));
      reinterpret_cast<float*>(smem + OFF_WTAB)[u] = wtv;
    }
    mbar_arrive(BAR(BAR_TABS));
    TL(2);
    mbar_wait(BAR(BAR_X0), 0);
    mbar_wait(BAR(BAR_TABS), 0);
  }

  TL(5);
  const uint32_t selU = (q == 0) ? 0x1010u : (q == 1) ? 0x3232u : (q == 2) ? 0x3210u : 0x7654u;
  const uint32_t selV = (q < 2) ? 0x3210u : 0x7654u;
  uint32_t bo_raw = __ldg(reinterpret_cast<const unsigned short*>(P.bout));
  mbar_wait(BAR(BAR_EPOCH), 0);
  mbar_wait(BAR(BAR_STAB), 0);
  const unsigned epoch = lds_u32(sb + OFF_EPOCH);

  uint32_t X[2][13];
  auto load_x = [&](int sl) {
    const uint4 o = *reinterpret_cast<const uint4*>(smem + OFF_LOFF + lane * 16);
    const uint32_t xo = sb + OFF_XOFF + sl * 52;
    const uint32_t tb = sb + OFF_TAB, hx = ((lane >> 3) & 1) << 4;
    const uint32_t a0 = lds_u16(xo + (o.x & 0xffff)), a1 = lds_u16(xo + (o.x >> 16));
    const uint32_t a2 = lds_u16(xo + (o.y & 0xffff)), a3 = lds_u16(xo + (o.y >> 16));
    const uint32_t a4 = lds_u16(xo + (o.z & 0xffff)), a5 = lds_u16(xo + (o.z >> 16));
    const uint32_t a6 = lds_u16(xo + (o.w & 0xffff));
    ldsm_x4_t(tb + (a0 ^ hx), X[0][0], X[1][0], X[0][1], X[1][1]);
    ldsm_x4_t(tb + (a1 ^ hx), X[0][2], X[1][2], X[0][3], X[1][3]);
    ldsm_x4_t(tb + (a2 ^ hx), X[0][4], X[1][4], X[0][5], X[1][5]);
    ldsm_x4_t(tb + (a3 ^ hx), X[0][6], X[1][6], X[0][7], X[1][7]);
    ldsm_x4_t(tb + (a4 ^ hx), X[0][8], X[1][8], X[0][9], X[1][9]);
    ldsm_x4_t(tb + (a5 ^ hx), X[0][10], X[1][10], X[0][11], X[1][11]);
    ldsm_x2_t(tb + (a6 ^ hx), X[0][12], X[1][12]);
  };
  load_x(nq * 32 + wg * 4 + w4);
#pragma unroll 1
  for (int it = 0; it < 2; it++) {
    const int sl = nq * 32 + (wg + 4 * it) * 4 + w4;
    float S = 0.f;
    uint32_t vx[2][4], vg[2][4];
    {
      float a0[28];
      if (it == 0) mbar_wait(BAR(BAR_IMG + 0), 0);
      if (it < 2) TL(6 + it * 8);
      g0_rec<0>(a0, X, selU, selV, dk, BAR(BAR_G0B), it == 0);
      wg_wait<0>();
      reg_fence(a0);
      const float4* wt = reinterpret_cast<const float4*>(smem + OFF_WTAB) + q * 2;
      float4 wa = wt[0], wb = wt[1];
#pragma unroll
      for (int r = 0; r < 2; r++) {
        S = fmaf(wa.x, a0[0 + 2 * r], S); S = fmaf(wa.y, a0[1 + 2 * r], S);
        S = fmaf(wa.z, a0[4 + 2 * r], S); S = fmaf(wa.w, a0[5 + 2 * r], S);
        S = fmaf(wb.x, a0[8 + 2 * r], S); S = fmaf(wb.y, a0[9 + 2 * r], S);
        S = fmaf(wb.z, a0[24 + 2 * r], S);
#pragma unroll
        for (int c = 0; c < 3; c++) {
          vx[r][c] = pack_bf16(a0[4 * c + 2 * r], a0[4 * c + 2 * r + 1]);
          vg[r][c] = pack_bf16(a0[12 + 4 * c + 2 * r], a0[12 + 4 * c + 2 * r + 1]);
        }
        vx[r][3] = pack_bf16(a0[24 + 2 * r], 0.f);
        vg[r][3] = pack_bf16(a0[24 + 2 * r + 1], 0.f);
      }
    }
    float g3[16], xa[16];
    if (it < 2) TL(7 + it * 8);
    if (it == 0) {
      mbar_wait(BAR(BAR_IMG + 2), 0);
      mbar_wait(BAR(BAR_IMG + 1), 0);
      mbar_wait(BAR(BAR_IMG + 3), 0);
    }
    if (it < 2) TL(8 + it * 8);
    layer_rec<0, OFF_LB>(xa, vx, X, dk);
    if (it < 2) TL(9 + it * 8);
    wg_wait<1>();
    layer_first<OFF_LA, 3>(g3, vg, X, dk);
    wg_wait<1>();
    reg_fence(xa);
    {
      const float4* wt = reinterpret_cast<const float4*>(smem + OFF_WTAB) + 8 + q * 2;
      float4 wa = wt[0], wb = wt[1];
#pragma unroll
      for (int r = 0; r < 2; r++) {
        S = fmaf(wa.x, xa[0 + 2 * r], S); S = fmaf(wa.y, xa[1 + 2 * r], S);
        S = fmaf(wa.z, xa[4 + 2 * r], S); S = fmaf(wa.w, xa[5 + 2 * r], S);
        S = fmaf(wb.x, xa[8 + 2 * r], S); S = fmaf(wb.y, xa[9 + 2 * r], S);
        S = fmaf(wb.z, xa[12 + 2 * r], S);
#pragma unroll
        for (int c = 0; c < 3; c++) vx[r][c] = pack_bf16(xa[4 * c + 2 * r], xa[4 * c + 2 * r + 1]);
        vx[r][3] = pack_bf16(xa[12 + 2 * r], 0.f);
      }
    }
    layer_rec<3, OFF_LA>(g3, vg, X, dk);
    if (it < 2) TL(10 + it * 8);
    wg_wait<1>();
    const unsigned long long* pp = P.part + (grp * 4 + (lane & 3)) * 128 + sl;
    unsigned long long pk;
    asm volatile("ld.relaxed.gpu.global.u64 %0, [%1];" : "=l"(pk) : "l"(pp) : "memory");
    float xc[16];
    layer_rec<0, OFF_LC>(xc, vx, X, dk);
    if (it == 0) load_x(sl + 16);
    wg_wait<0>();
    reg_fence(xc);
    reg_fence(g3);
    {
      float Se = 0.f;
#pragma unroll
      for (int r = 0; r < 2; r++) {
#pragma unroll
        for (int c = 0; c < 3; c++) {
          S = fmaf(g3[4 * c + 2 * r], xc[4 * c + 2 * r], S);
          S = fmaf(g3[4 * c + 2 * r + 1], xc[4 * c + 2 * r + 1], S);
        }
        Se = fmaf(g3[12 + 2 * r], xc[12 + 2 * r], Se);
      }
      if (!(q & 1)) S += Se;
    }
#pragma unroll
    for (int o = 16; o > 0; o >>= 1) S += __shfl_xor_sync(0xffffffffu, S, o);
    if (it < 2) TL(12 + it * 8);
    {
      uint32_t spin = 0;
      while (lane < 4 && (unsigned)(pk >> 32) != epoch) {
        asm volatile("ld.relaxed.gpu.global.u64 %0, [%1];" : "=l"(pk) : "l"(pp) : "memory");
        if (++spin > (1u << 24)) __trap();
      }
      __syncwarp();
      float dv = __uint_as_float((unsigned)pk);
      float d01 = dv + __shfl_xor_sync(0xffffffffu, dv, 1);
      float dsum = d01 + __shfl_xor_sync(0xffffffffu, d01, 2);
      asm volatile("" : "+r"(bo_raw));
      if (lane == 0) P.out[grp * 128 + sl] = __float2bfloat16(S + dsum + __uint_as_float(bo_raw << 16));
    }
    __syncwarp();
    if (it < 2) TL(13 + it * 8);
  }
  TL_DUMP();
}

__global__ void __launch_bounds__(128) fallback_kernel(const int* __restrict__ idx, const bf16* __restrict__ table, const bf16* __restrict__ ws,
                                                       const bf16* __restrict__ wout, const bf16* __restrict__ w1, const bf16* __restrict__ b1,
                                                       const bf16* __restrict__ w2, const bf16* __restrict__ bout, bf16* __restrict__ out) {
  __shared__ float x0[416], xa[416], xb[416], red[128];
  const int b = blockIdx.x, t = threadIdx.x;
  for (int i = t; i < 416; i += 128) { x0[i] = bf2f(table[idx[b * NF + i / 16] * 16 + (i & 15)]); xa[i] = x0[i]; }
  __syncthreads();
  float acc = 0.f;
  float* cur = xa;
  float* nxt = xb;
  for (int l = 0; l < 6; l++) {
    for (int o = t; o < 416; o += 128) {
      const int h = o >> 4, d = o & 15;
      const bf16* w = ws + (l * NF + h) * NF * NF;
      float s = 0.f;
      for (int i = 0; i < NF; i++) {
        float u = 0.f;
        for (int j = 0; j < NF; j++) u = fmaf(bf2f(w[i * NF + j]), x0[j * 16 + d], u);
        s = fmaf(u, cur[i * 16 + d], s);
      }
      nxt[o] = s;
      acc = fmaf(s, bf2f(wout[l * NF + h]), acc);
    }
    __syncthreads();
    float* tmp = cur; cur = nxt; nxt = tmp;
  }
  for (int n = t; n < 416; n += 128) {
    float h = 0.f;
    for (int k = 0; k < 416; k++) h = fmaf(x0[k], bf2f(w1[k * 416 + n]), h);
    h += bf2f(b1[n]);
    const float gl = 0.5f * h * (1.f + tanhf(0.7978845608028654f * (h + 0.044715f * h * h * h)));
    acc = fmaf(gl, bf2f(w2[n]), acc);
  }
  red[t] = acc;
  __syncthreads();
  for (int o = 64; o > 0; o >>= 1) { if (t < o) red[t] += red[t + o]; __syncthreads(); }
  if (t == 0) out[b] = __float2bfloat16(red[0] + bf2f(bout[0]));
}

typedef CUresult (*EncodeFn)(CUtensorMap*, CUtensorMapDataType, cuuint32_t, void*, const cuuint64_t*, const cuuint64_t*,
                             const cuuint32_t*, const cuuint32_t*, CUtensorMapInterleave, CUtensorMapSwizzle,
                             CUtensorMapL2promotion, CUtensorMapFloatOOBfill);

extern "C" void kernel_launch(void* const* d_in, const int* in_sizes, int n_in, void* d_out, int out_size) {
  const int* idx = (const int*)d_in[0];
  const bf16* table = (const bf16*)d_in[1];
  const bf16* ws = (const bf16*)d_in[2];
  const bf16* wout = (const bf16*)d_in[3];
  const bf16* w1 = (const bf16*)d_in[4];
  const bf16* b1 = (const bf16*)d_in[5];
  const bf16* w2 = (const bf16*)d_in[6];
  const bf16* bo = (const bf16*)d_in[7];
  bf16* out = (bf16*)d_out;

  static EncodeFn enc = nullptr;
  static Params P;
  static int n_sm = 0;
  if (!n_sm) {
    int dev = 0;
    cudaGetDevice(&dev);
    cudaDeviceGetAttribute(&n_sm, cudaDevAttrMultiProcessorCount, dev);
  }
  if (n_sm < NCTA + NHELP) {
    fallback_kernel<<<4096, 128, 0, cudaStreamPerThread>>>(idx, table, ws, wout, w1, b1, w2, bo, out);
    return;
  }
  if (!enc) {
    void* fn = nullptr;
    cudaDriverEntryPointQueryResult qr;
    cudaGetDriverEntryPoint("cuTensorMapEncodeTiled", &fn, cudaEnableDefault, &qr);
    enc = (EncodeFn)fn;
    cudaFuncSetAttribute(main_kernel, cudaFuncAttributeMaxDynamicSharedMemorySize, LAUNCH_SMEM);
    void* p;
    cudaGetSymbolAddress(&p, g_img); P.img = (unsigned char*)p;
    cudaGetSymbolAddress(&p, g_part); P.part = (unsigned long long*)p;
    cudaGetSymbolAddress(&p, g_ctr); P.ctr = (unsigned*)p;
    cudaGetSymbolAddress(&p, g_tabs); P.tabs = p;
    P.dk = make_desc(0, 128, 256, 0);
    P.dmn = make_desc(0, 8192, 1024, 1);
    for (int c = 0; c < NCTA; c++) P.role[c] = make_role(c);
  }
  P.idx = idx; P.table = table; P.ws = ws; P.wout = wout; P.b1 = b1; P.w2 = w2; P.bout = bo; P.out = out;
  TmaMaps tms;
  for (int h = 0; h < 4; h++) {
    const int c0 = (h >> 1) * 208 + (h & 1) * 96, nw = (h & 1) ? 112 : 96;
    cuuint64_t dims[2] = {(cuuint64_t)nw, 416};
    cuuint64_t strides[1] = {832};
    cuuint32_t box[2] = {64, 64};
    cuuint32_t es[2] = {1, 1};
    enc(&tms.m[h], CU_TENSOR_MAP_DATA_TYPE_BFLOAT16, 2, (void*)(w1 + c0), dims, strides, box, es,
        CU_TENSOR_MAP_INTERLEAVE_NONE, CU_TENSOR_MAP_SWIZZLE_128B, CU_TENSOR_MAP_L2_PROMOTION_L2_128B,
        CU_TENSOR_MAP_FLOAT_OOB_FILL_NONE);
  }
  main_kernel<<<NCTA + NHELP, 512, LAUNCH_SMEM, cudaStreamPerThread>>>(P, tms);
}
```

```cpp
#include <cuda_runtime.h>
#include <cuda_bf16.h>
#include <cuda.h>
#include <stdint.h>

typedef __nv_bfloat16 bf16;
#define WRITER_FENCE() fence_proxy_async_global()

constexpr int NF = 26;
constexpr int NCTA = 128;

constexpr int G0_KS = 24, G0_N = 56, G0_SLAB = G0_N * 32;
constexpr int L_KS = 43, L_SLAB = 1024;
constexpr int G0_BYTES = G0_KS * G0_SLAB;
constexpr int L_BYTES = L_KS * L_SLAB;
constexpr int IMG_BYTES = G0_BYTES + 3 * L_BYTES;

constexpr int W1_STAGES = 7;
constexpr int W1_STAGE_BYTES = 16384;
constexpr int OFF_LB = 0;
constexpr int OFF_LA = 44032;
constexpr int OFF_LC = 88064;
__host__ __device__ constexpr int w1_off(int st) { return st < 2 ? st * W1_STAGE_BYTES : OFF_LA + (st - 2) * W1_STAGE_BYTES; }
constexpr int OFF_G0 = 132096;
constexpr int OFF_IDX = 132096 + 16384;
constexpr int OFF_TAB = OFF_G0 + G0_BYTES;
constexpr int OFF_XOFF = OFF_TAB + 32000;
constexpr int OFF_BAR = OFF_XOFF + 6656;
constexpr int OFF_BW = OFF_BAR + 256;
constexpr int OFF_W2 = OFF_BW + 256;
constexpr int OFF_WTAB = OFF_W2 + 1792;
constexpr int OFF_EPOCH = OFF_WTAB + 256;
constexpr int OFF_STAB = (OFF_EPOCH + 16 + 127) / 128 * 128;
constexpr int OFF_LOFF = OFF_STAB + 3072 + 704;
constexpr int SMEM_BYTES = OFF_STAB + 4288;
static_assert(SMEM_BYTES <= 229376, "smem");
constexpr int LAUNCH_SMEM = SMEM_BYTES;

constexpr int BAR_W1FULL = 0  , BAR_W1FREE = 10  , BAR_W1DONE = 11  ,
              BAR_IMG = 14  , BAR_X0 = 18, BAR_SETUP = 19, BAR_EPOCH = 20, BAR_TABS = 21,
              BAR_Q = 22, BAR_STAB = 23, BAR_G0B = 24  , NBAR = 26;

struct TmaMaps { CUtensorMap m[4]; };
struct Params {
  const int* idx; const bf16* table; const bf16* ws; const bf16* wout; const bf16* b1; const bf16* w2; const bf16* bout;
  bf16* out;
  unsigned char* img; unsigned long long* part; unsigned* ctr; const void* tabs;
  uint64_t dk, dmn;
  uint2 role[NCTA];
};

__device__ __align__(1024) unsigned char g_img[IMG_BYTES];
__device__ unsigned long long g_part[NCTA * 128];
__device__ __align__(128) unsigned g_ctr[64];

#define GT(i) do {} while (0)
#define TL(i) do {} while (0)
#define TLP(i) do {} while (0)
#define TLA(i) do {} while (0)
#define TLW(w, i) do {} while (0)
#define TL_INIT() do {} while (0)
#define TL_START() 0
#define TL_PUT0(c) do {} while (0)
#define TL_DUMP() do {} while (0)
__device__ __forceinline__ uint32_t smem_u32(const void* p) { return (uint32_t)__cvta_generic_to_shared(p); }
__device__ __forceinline__ bool elect_one() {
  uint32_t pred;
  asm volatile("{\n.reg .pred p;\nelect.sync _|p, 0xffffffff;\nselp.u32 %0, 1, 0, p;\n}\n" : "=r"(pred));
  return pred != 0;
}
__device__ __forceinline__ void mbar_init(uint32_t bar, uint32_t cnt) {
  asm volatile("mbarrier.init.shared::cta.b64 [%0], %1;" ::"r"(bar), "r"(cnt) : "memory");
}
__device__ __forceinline__ void mbar_expect_tx(uint32_t bar, uint32_t bytes) {
  asm volatile("mbarrier.arrive.expect_tx.shared::cta.b64 _, [%0], %1;" ::"r"(bar), "r"(bytes) : "memory");
}
__device__ __forceinline__ void mbar_arrive(uint32_t bar) {
  asm volatile("mbarrier.arrive.shared::cta.b64 _, [%0];" ::"r"(bar) : "memory");
}
__device__ __forceinline__ bool mbar_try(uint32_t bar, uint32_t parity) {
  uint32_t ok;
  asm volatile("{\n.reg .pred p;\nmbarrier.try_wait.parity.shared::cta.b64 p, [%1], %2;\nselp.u32 %0, 1, 0, p;\n}\n"
               : "=r"(ok) : "r"(bar), "r"(parity) : "memory");
  return ok != 0;
}
__device__ __forceinline__ void mbar_wait(uint32_t bar, uint32_t parity) {
#pragma unroll 1
  for (uint32_t it = 0; it < (1u << 26); it++)
    if (mbar_try(bar, parity)) return;
  __trap();
}
__device__ __forceinline__ void bulk_g2s(uint32_t dst, const void* src, uint32_t bytes, uint32_t bar) {
  asm volatile("cp.async.bulk.shared::cluster.global.mbarrier::complete_tx::bytes [%0], [%1], %2, [%3];"
               ::"r"(dst), "l"(src), "r"(bytes), "r"(bar) : "memory");
}
__device__ __forceinline__ void tma_2d(uint32_t dst, const CUtensorMap* tm, int x, int y, uint32_t bar) {
  asm volatile("cp.async.bulk.tensor.2d.shared::cluster.global.mbarrier::complete_tx::bytes [%0], [%1, {%3, %4}], [%2];"
               ::"r"(dst), "l"(tm), "r"(bar), "r"(x), "r"(y) : "memory");
}
__device__ __forceinline__ void cp_async16(uint32_t dst, const void* src) {
  asm volatile("cp.async.cg.shared.global [%0], [%1], 16;" ::"r"(dst), "l"(src) : "memory");
}
__device__ __forceinline__ void fence_proxy_async() { asm volatile("fence.proxy.async.shared::cta;" ::: "memory"); }
__device__ __forceinline__ void fence_proxy_async_all() { asm volatile("fence.proxy.async;" ::: "memory"); }
template <int ID, int N> __device__ __forceinline__ void named_bar_t() { asm volatile("bar.sync %0, %1;" ::"n"(ID), "n"(N) : "memory"); }
#define named_bar(id, n) named_bar_t<id, n>()

__device__ __forceinline__ void wg_fence() { asm volatile("wgmma.fence.sync.aligned;" ::: "memory"); }
__device__ __forceinline__ void wg_commit() { asm volatile("wgmma.commit_group.sync.aligned;" ::: "memory"); }
template <int N> __device__ __forceinline__ void wg_wait() { asm volatile("wgmma.wait_group.sync.aligned %0;" ::"n"(N) : "memory"); }
template <int N> __device__ __forceinline__ void reg_fence(float (&d)[N]) {
#pragma unroll
  for (int i = 0; i < N; i++) asm volatile("" : "+f"(d[i])::"memory");
}
constexpr uint32_t SMEM_BASE = 1024;
__host__ __device__ constexpr uint64_t make_desc(uint32_t off, uint32_t lbo, uint32_t sbo, uint32_t swz) {
  return (uint64_t)(((SMEM_BASE + off) & 0x3FFFF) >> 4) | ((uint64_t)(lbo >> 4) << 16) | ((uint64_t)(sbo >> 4) << 32) | ((uint64_t)swz << 62);
}

#define ACC4(d, o) "+f"(d[o]), "+f"(d[o + 1]), "+f"(d[o + 2]), "+f"(d[o + 3])
#define ACC8(d, o) ACC4(d, o), ACC4(d, o + 4)

__device__ __forceinline__ void wgmma_rs_n32(float (&d)[16], uint32_t a0, uint32_t a1, uint32_t a2, uint32_t a3, uint64_t db, int sc) {
  asm volatile("{\n.reg .pred p;\nsetp.ne.b32 p, %21, 0;\n"
               "wgmma.mma_async.sync.aligned.m64n32k16.f32.bf16.bf16 "
               "{%0,%1,%2,%3,%4,%5,%6,%7,%8,%9,%10,%11,%12,%13,%14,%15}, {%16,%17,%18,%19}, %20, p, 1, 1, 0;\n}\n"
               : ACC8(d, 0), ACC8(d, 8)
               : "r"(a0), "r"(a1), "r"(a2), "r"(a3), "l"(db), "r"(sc));
}
__device__ __forceinline__ void wgmma_rs_n56(float (&d)[28], uint32_t a0, uint32_t a1, uint32_t a2, uint32_t a3, uint64_t db, int sc) {
  asm volatile("{\n.reg .pred p;\nsetp.ne.b32 p, %33, 0;\n"
               "wgmma.mma_async.sync.aligned.m64n56k16.f32.bf16.bf16 "
               "{%0,%1,%2,%3,%4,%5,%6,%7,%8,%9,%10,%11,%12,%13,%14,%15,%16,%17,%18,%19,%20,%21,%22,%23,%24,%25,%26,%27}, "
               "{%28,%29,%30,%31}, %32, p, 1, 1, 0;\n}\n"
               : ACC8(d, 0), ACC8(d, 8), ACC8(d, 16), ACC4(d, 24)
               : "r"(a0), "r"(a1), "r"(a2), "r"(a3), "l"(db), "r"(sc));
}
__device__ __forceinline__ void wgmma_rs_n112_tb(float (&d)[56], uint32_t a0, uint32_t a1, uint32_t a2, uint32_t a3, uint64_t db, int sc) {
  asm volatile("{\n.reg .pred p;\nsetp.ne.b32 p, %61, 0;\n"
               "wgmma.mma_async.sync.aligned.m64n112k16.f32.bf16.bf16 "
               "{%0,%1,%2,%3,%4,%5,%6,%7,%8,%9,%10,%11,%12,%13,%14,%15,%16,%17,%18,%19,%20,%21,%22,%23,%24,%25,%26,%27,%28,%29,%30,%31,%32,%33,%34,%35,%36,%37,%38,%39,%40,%41,%42,%43,%44,%45,%46,%47,%48,%49,%50,%51,%52,%53,%54,%55}, "
               "{%56,%57,%58,%59}, %60, p, 1, 1, 1;\n}\n"
               : ACC8(d, 0), ACC8(d, 8), ACC8(d, 16), ACC8(d, 24), ACC8(d, 32), ACC8(d, 40), ACC8(d, 48)
               : "r"(a0), "r"(a1), "r"(a2), "r"(a3), "l"(db), "r"(sc));
}

__device__ __forceinline__ void wgmma_rs_n8(float (&d)[4], uint32_t a0, uint32_t a1, uint32_t a2, uint32_t a3, uint64_t db, int sc) {
  asm volatile("{\n.reg .pred p;\nsetp.ne.b32 p, %9, 0;\n"
               "wgmma.mma_async.sync.aligned.m64n8k16.f32.bf16.bf16 {%0,%1,%2,%3}, {%4,%5,%6,%7}, %8, p, 1, 1, 0;\n}\n"
               : ACC4(d, 0)
               : "r"(a0), "r"(a1), "r"(a2), "r"(a3), "l"(db), "r"(sc));
}
__device__ __forceinline__ uint32_t mul_lo(uint32_t v, uint32_t r) {
  __nv_bfloat162 a = *reinterpret_cast<__nv_bfloat162*>(&v), b = *reinterpret_cast<__nv_bfloat162*>(&r);
  __nv_bfloat162 c = __hmul2(__low2bfloat162(a), b);
  return *reinterpret_cast<uint32_t*>(&c);
}
__device__ __forceinline__ uint32_t mul_hi(uint32_t v, uint32_t r) {
  __nv_bfloat162 a = *reinterpret_cast<__nv_bfloat162*>(&v), b = *reinterpret_cast<__nv_bfloat162*>(&r);
  __nv_bfloat162 c = __hmul2(__high2bfloat162(a), b);
  return *reinterpret_cast<uint32_t*>(&c);
}
__device__ __forceinline__ uint32_t mul_ew(uint32_t v, uint32_t r) {
  __nv_bfloat162 a = *reinterpret_cast<__nv_bfloat162*>(&v), b = *reinterpret_cast<__nv_bfloat162*>(&r);
  __nv_bfloat162 c = __hmul2(a, b);
  return *reinterpret_cast<uint32_t*>(&c);
}
__device__ __forceinline__ uint32_t pack_bf16(float lo, float hi) {
  uint32_t r;
  asm("cvt.rn.bf16x2.f32 %0, %1, %2;" : "=r"(r) : "f"(hi), "f"(lo));
  return r;
}
__device__ __forceinline__ float bf2f(bf16 v) { return __bfloat162float(v); }
__device__ __forceinline__ float bflo(uint32_t w) { return __uint_as_float(w << 16); }
__device__ __forceinline__ float bfhi(uint32_t w) { return __uint_as_float(w & 0xffff0000u); }

__device__ __forceinline__ void st_img(uint32_t* p, uint32_t v) {
  asm volatile("st.relaxed.gpu.global.u32 [%0], %1;" ::"l"(p), "r"(v) : "memory");
}
__device__ __forceinline__ void fence_proxy_async_global() { asm volatile("fence.proxy.async.global;" ::: "memory"); }
__device__ __forceinline__ uint32_t ld_back(const uint32_t* p) {
  uint32_t v;
  asm volatile("ld.relaxed.gpu.global.u32 %0, [%1];" : "=r"(v) : "l"(p) : "memory");
  return v;
}
__host__ __device__ constexpr int Fq(int q, int t, int e) {
  if (t == 12) return 24 + e;
  const int u = (t + 3 * q) % 12;
  const int sw = (q >= 2 && u >= 6) ? 1 : 0;
  return 2 * u + (e ^ sw);
}
constexpr int M_ONE = 26, M_NONE = 27;
struct Mono { int f1, f2; };
__host__ __device__ constexpr Mono g0_mono(int s, int q, int e) {
  if (s < 30) { const int d = s / 6 + 1, a = (s % 6) >> 1; return {Fq(q, a, s & 1), Fq(q, a + d, e)}; }
  if (s < 33) return {Fq(q, s - 30, e), Fq(q, s - 24, e)};
  if (s < 35) return {Fq(q, s - 33, e), Fq(q, s - 33, e)};
  if (s == 35) return {Fq(q, e, 0), Fq(q, e, 1)};
  if (s == 36) return {Fq(q, 2, 0), Fq(q, 2, e)};
  if (s == 37) return e ? Mono{Fq(q, 2, 1), Fq(q, 2, 1)} : Mono{M_NONE, M_NONE};
  if (s < 44) return {24 + ((s - 38) & 1), Fq(q, (s - 38) >> 1, e)};
  if (s < 47) return {Fq(q, s - 44, e), M_ONE};
  if (q == 0) return {24, 24 + e};
  if (q == 1) return e ? Mono{25, 25} : Mono{M_NONE, M_NONE};
  if (q == 2) return {24 + e, M_ONE};
  return e ? Mono{M_NONE, M_NONE} : Mono{M_ONE, M_ONE};
}
constexpr int QM_RS = 40;
constexpr int O_ZERO = 31 * QM_RS + 39, O_CONST = 30 * QM_RS + 39;
struct StaticTabs {
  uint32_t otab[48 * 8];
  uint32_t x1tab[48 * 8];
  uint16_t ltab[88 * 4];
  uint16_t loff[32 * 8];
};
constexpr StaticTabs make_tabs() {
  StaticTabs T{};
  for (int s = 0; s < 48; s++)
    for (int q = 0; q < 4; q++)
      for (int e = 0; e < 2; e++) {
        const Mono m = g0_mono(s, q, e);
        const bool none = m.f1 == M_NONE, cs = m.f1 == M_ONE, lin = m.f2 == M_ONE;
        const uint32_t o1 = none ? O_ZERO : cs ? O_CONST : m.f1 * QM_RS + (lin ? 26 : m.f2);
        const uint32_t o2 = (none || cs || lin || m.f1 == m.f2) ? O_ZERO : m.f2 * QM_RS + m.f1;
        T.otab[s * 8 + q * 2 + e] = o1 | (o2 << 16);
        const bool qd = m.f1 < NF && m.f2 < NF;
        const uint32_t y1 = qd ? m.f1 * NF + m.f2 : 0xffffu;
        const uint32_t y2 = (qd && m.f1 != m.f2) ? m.f2 * NF + m.f1 : 0xffffu;
        T.x1tab[s * 8 + q * 2 + e] = y1 | (y2 << 16);
      }
  for (int s = 0; s < 88; s++)
    for (int q = 0; q < 4; q++) {
      uint16_t v = 0;
      if (s < 85) {
        const bool ex = s >= 78;
        const int a = s / 13, k = s - 78;
        const int tt = ex ? ((k < 3) ? k : (k < 6 ? k + 3 : 12)) : s % 13;
        const int in = ex ? 24 + (q >> 1) : 8 * (a >> 1) + 2 * q + (a & 1);
        const bool valid = !(ex && tt == 12 && (q & 1));
        const int f0 = Fq(q, tt, 0);
        v = (uint16_t)((f0 >> 1) | ((f0 & 1) << 4) | ((valid ? 1 : 0) << 5) | (in << 6));
      }
      T.ltab[s * 4 + q] = v;
    }
  for (int ln = 0; ln < 32; ln++)
    for (int k = 0; k < 8; k++) {
      const int m = ln >> 3, r = ln & 7;
      const int tt = (k < 6) ? 2 * k + (m >> 1) : 12;
      T.loff[ln * 8 + k] = (uint16_t)(2 * Fq(r >> 1, tt, r & 1));
    }
  return T;
}
static_assert(sizeof(StaticTabs) == 4288, "tabs");
__device__ __align__(128) const StaticTabs g_tabs = make_tabs();

constexpr int SETUP_WARPS = 7;
constexpr int WL_BYTES = NF * NF * NF * 2;
static inline uint2 make_role(int cta) {
  int kind = 5, grp = 0, j = 0, off = 0, bytes = 0;
  const int c = cta, SL = NF * NF * 2;
  if (c < 56) { kind = 1 + c / 28; grp = (c % 28) / 7; j = c % 7; off = kind * WL_BYTES + grp * 8 * SL; bytes = (grp < 3 ? 8 : 2) * SL; }
  else if (c < 80) { kind = 0; grp = (c - 56) / 8; j = (c - 56) % 8; off = 3 * WL_BYTES + grp * 8 * SL; bytes = 8 * SL; }
  else if (c < 83) { kind = 0; grp = 3; j = c - 80; off = 3 * WL_BYTES + 24 * SL; bytes = 2 * SL; }
  else if (c < 95) { kind = 3; grp = (c - 83) / 4; j = (c - 83) % 4; off = grp * 8 * SL; bytes = 8 * SL; }
  const int delta = off & 127;
  uint2 r;
  r.x = (uint32_t)(off - delta) | ((uint32_t)kind << 24);
  r.y = (uint32_t)(bytes + delta) | ((uint32_t)delta << 16) | ((uint32_t)grp << 24) | ((uint32_t)j << 28);
  return r;
}

__device__ __forceinline__ uint32_t layer_row(int li, int grp, int r, int lane, const unsigned char* raw, const StaticTabs* T,
                                              uint32_t bar, uint32_t tbar, const bf16* __restrict__ wout, uint32_t* img32) {
  const int ks = li ? r : 13 * grp + (r >> 2), ng = li ? grp : (r & 3);
  if (ks >= 43 || (!li && grp < 3 && r >= 52)) return 0;
  const uint32_t* w32 = reinterpret_cast<const uint32_t*>(raw);
  const int n8 = lane >> 2, q = lane & 3;
  const int o = (ng < 3) ? ng * 8 + n8 : 24 + (n8 >> 2);
  const bool vo = (ng < 3) || !(n8 & 1);
  const int ob = li ? (o - 8 * grp) * 338 : o * 13 - 8 * grp * 338;
  const int si = li ? 13 : 338;
  uint32_t bias = 0;
  if (vo && ks == 42 && li == 0 && q == 0) bias = (uint32_t)__ldg(reinterpret_cast<const unsigned short*>(wout) + 2 * NF + o);
  uint32_t* dst = img32 + G0_BYTES / 4 + li * (L_BYTES / 4) + (ks * 4 + ng) * 64 + lane;
  mbar_wait(tbar, 0);
  const uint32_t e0 = T->ltab[8 * ks + q], e1 = T->ltab[8 * ks + 4 + q];
  const bool v0 = vo && (e0 & 32), v1 = vo && (e1 & 32);
  const int s0 = v0 ? ob + (e0 >> 6) * si + (e0 & 15) : 0, s1 = v1 ? ob + (e1 >> 6) * si + (e1 & 15) : 0;
  TL(33);
  mbar_wait(bar, 0);
  TL(36);
  uint32_t w0 = w32[s0], w1 = w32[s1];
  w0 = (e0 & 16) ? __funnelshift_l(w0, w0, 16) : w0;
  w1 = (e1 & 16) ? __funnelshift_l(w1, w1, 16) : w1;
  w0 = v0 ? w0 : 0u;
  w1 = v1 ? w1 : bias;
  st_img(dst, w0); st_img(dst + 32, w1);
  const uint32_t chk = (ld_back(dst) ^ w0) | (ld_back(dst + 32) ^ w1);
  WRITER_FENCE();
  return chk;
}
__device__ __forceinline__ float x1_val(const unsigned short* wh, uint32_t e) {
  const uint32_t a = e & 0xffff, b = e >> 16;
  const uint32_t x = wh[a == 0xffff ? 0 : a], y = wh[b == 0xffff ? 0 : b];
  return (a == 0xffff ? 0.f : __uint_as_float(x << 16)) + (b == 0xffff ? 0.f : __uint_as_float(y << 16));
}
__device__ __forceinline__ uint32_t x1_row(int ng, int ks, int lane, const unsigned char* raw, const StaticTabs* T, uint32_t bar, uint32_t tbar, uint32_t* img32) {
  if (ks >= 24) return 0;
  const int n8 = lane >> 2, q = lane & 3;
  const unsigned short* wh = reinterpret_cast<const unsigned short*>(raw) + n8 * (NF * NF);
  uint32_t* dst = img32 + ks * (G0_SLAB / 4) + ng * 64 + lane;
  mbar_wait(tbar, 0);
  const uint2 ea = *reinterpret_cast<const uint2*>(&T->x1tab[16 * ks + 2 * q]), eb = *reinterpret_cast<const uint2*>(&T->x1tab[16 * ks + 8 + 2 * q]);
  mbar_wait(bar, 0);
  const uint32_t w0 = pack_bf16(x1_val(wh, ea.x), x1_val(wh, ea.y)), w1 = pack_bf16(x1_val(wh, eb.x), x1_val(wh, eb.y));
  st_img(dst, w0); st_img(dst + 32, w1);
  const uint32_t chk = (ld_back(dst) ^ w0) | (ld_back(dst + 32) ^ w1);
  WRITER_FENCE();
  return chk;
}

constexpr int NHELP = 4;
constexpr int H_MS = 32 * QM_RS + 4;
constexpr int H_W5 = 0, H_W4 = 35328, H_W0 = 70656, H_TAB = 73472, H_B = 77824, H_M = 82944, H_XE = H_M + 8 * H_MS * 4, H_BAR = H_XE + 1536;
__device__ __forceinline__ int wf_off(int b, int h) { return (b >> 3) * 512 + (h >> 3) * 128 + (b & 7) * 16 + (h & 7) * 2; }
__device__ __forceinline__ void helper_role(int hk, const Params& P, unsigned char* smem, uint32_t sb) {
  const int t = threadIdx.x, warp = __shfl_sync(0xffffffffu, t >> 5, 0), lane = t & 31;
  const uint32_t d5bar = sb + H_BAR, d4bar = sb + H_BAR + 8, tbar = sb + H_BAR + 16;
  const unsigned char* wsb = reinterpret_cast<const unsigned char*>(P.ws);
  unsigned char* WB = smem + H_B;
  float* M = reinterpret_cast<float*>(smem + H_M);
  constexpr uint32_t W5B = WL_BYTES + ((5 * WL_BYTES) & 127), W4B = WL_BYTES + ((4 * WL_BYTES) & 127);
  if (warp < 3 && elect_one()) {
    mbar_init(sb + H_BAR + 8 * warp, 1);
    asm volatile("fence.mbarrier_init.release.cluster;" ::: "memory");
    if (warp == 0) {
      mbar_expect_tx(d5bar, W5B);
#pragma unroll
      for (int c = 0; c < 5; c++)
        bulk_g2s(sb + H_W5 + c * 8192, wsb + ((5 * WL_BYTES) & ~127) + c * 8192, c < 4 ? 8192u : W5B - 4 * 8192, d5bar);
    }
  }
  reinterpret_cast<uint32_t*>(WB)[t] = 0;
  __syncthreads();
  if (warp >= 5 && warp < 12 && elect_one()) {
    if (warp < 10) {
      const int c = warp - 5;
      if (c == 0) mbar_expect_tx(d4bar, W4B + (hk == 3 ? 2768 : 0));
      bulk_g2s(sb + H_W4 + c * 8192, wsb + ((4 * WL_BYTES) & ~127) + c * 8192, c < 4 ? 8192u : W4B - 4 * 8192, d4bar);
    } else if (warp == 10) {
      mbar_expect_tx(tbar, sizeof(StaticTabs));
      bulk_g2s(sb + H_TAB, P.tabs, sizeof(StaticTabs), tbar);
    } else if (hk == 3) {
      bulk_g2s(sb + H_W0, wsb + ((24 * NF * NF * 2) & ~127), 2768, d4bar);
    }
  }
  const unsigned short* wo16 = reinterpret_cast<const unsigned short*>(P.wout);
  uint32_t c5[13];
#pragma unroll
  for (int k = 0; k < 13; k++) c5[k] = __ldg(reinterpret_cast<const uint32_t*>(P.wout + 5 * NF) + k);
  unsigned short wv = 0;
  const int io0 = (hk < 3) ? 8 * hk : 24;
  if (t >= 352 && t < 352 + NF) wv = __ldg(wo16 + 4 * NF + t - 352);
  else if (t >= 384 && t < 392 && io0 + t - 384 < NF) wv = __ldg(wo16 + 3 * NF + io0 + t - 384);
  const StaticTabs* T = reinterpret_cast<const StaticTabs*>(smem + H_TAB);
  const int n8 = lane >> 2, q = lane & 3, g = n8;
  const int fil = (hk < 3) ? n8 : (n8 >> 2);
  const bool fx1 = (hk == 3) && !(n8 & 1);
  uint32_t* dst = reinterpret_cast<uint32_t*>(P.img) + (warp >> 1) * (G0_SLAB / 4) + (warp & 1) * 32 + (3 + hk) * 64 + lane;
  if (t >= 352 && t < 352 + NF) *reinterpret_cast<unsigned short*>(WB + wf_off(26, t - 352)) = wv;
  if (t >= 384 && t < 392) { M[(t - 384) * H_MS + O_ZERO] = 0.f; M[(t - 384) * H_MS + O_CONST] = __uint_as_float((uint32_t)wv << 16); }
  mbar_wait(d5bar, 0);
  if (t < 338) {
    const uint32_t* w5 = reinterpret_cast<const uint32_t*>(smem + H_W5 + ((5 * WL_BYTES) & 127)) + t;
    float s0 = 0.f, s1 = 0.f, s2 = 0.f, s3 = 0.f;
#pragma unroll
    for (int k = 0; k < 13; k++) {
      const uint32_t wa = w5[(2 * k) * 338], wb = w5[(2 * k + 1) * 338];
      const float ca = bflo(c5[k]), cb = bfhi(c5[k]);
      s0 = fmaf(ca, bflo(wa), s0); s1 = fmaf(ca, bfhi(wa), s1);
      s2 = fmaf(cb, bflo(wb), s2); s3 = fmaf(cb, bfhi(wb), s3);
    }
    const int h = (t * 79) >> 10, tp = t - 13 * h;
    *reinterpret_cast<bf16*>(WB + wf_off(2 * tp, h)) = __float2bfloat16(s0 + s2);
    *reinterpret_cast<bf16*>(WB + wf_off(2 * tp + 1, h)) = __float2bfloat16(s1 + s3);
  }
  fence_proxy_async();
  mbar_wait(tbar, 0);
  uint2 fot[3];
#pragma unroll
  for (int r = 0; r < 3; r++) fot[r] = *reinterpret_cast<const uint2*>(&T->otab[(warp + 16 * r) * 8 + q * 2]);
  mbar_wait(d4bar, 0);
  const int wgi = warp >> 2, il = 2 * wgi + ((warp >> 1) & 1), mt = warp & 1;
  const bool mma_wg = (hk < 3) || (wgi == 0);
  uint32_t a[2][4];
  if (mma_wg) {
    const unsigned short* A = reinterpret_cast<const unsigned short*>(smem + H_W4 + ((4 * WL_BYTES) & 127)) + (io0 + il) * NF + mt * 16 + g;
#pragma unroll
    for (int kk = 0; kk < 2; kk++) {
#pragma unroll
      for (int jj = 0; jj < 4; jj++) {
        const int k = kk * 16 + 2 * q + (jj >> 1) * 8, mo = (jj & 1) * 8;
        const int kc = (k < NF) ? k : 0;
        const uint32_t lo = A[kc * (NF * NF) + mo], hi = A[(kc + 1) * (NF * NF) + mo];
        a[kk][jj] = (k < NF) ? (lo | (hi << 16)) : 0u;
      }
    }
  }
  if (hk == 3) {
    const int u0 = (warp >= 4) ? t - 128 : -1;
    if (u0 >= 0) {
      const int sl = u0 >> 3, xl = (u0 >> 2) & 1, xq = u0 & 3;
      const uint2 xt = *reinterpret_cast<const uint2*>(&T->x1tab[sl * 8 + xq * 2]);
      const unsigned short* wh = reinterpret_cast<const unsigned short*>(smem + H_W0 + ((24 * NF * NF * 2) & 127)) + xl * (NF * NF);
      reinterpret_cast<uint32_t*>(smem + H_XE)[u0] = pack_bf16(x1_val(wh, xt.x), x1_val(wh, xt.y));
    }
  }
  __syncthreads();
  if (mma_wg) {
    float c[16];
    wg_fence();
    wgmma_rs_n32(c, a[0][0], a[0][1], a[0][2], a[0][3], make_desc(H_B, 128, 512, 0), 0);
    wgmma_rs_n32(c, a[1][0], a[1][1], a[1][2], a[1][3], make_desc(H_B + 256, 128, 512, 0), 1);
    wg_commit();
    wg_wait<0>();
    reg_fence(c);
    float* Mi = M + il * H_MS;
#pragma unroll
    for (int n = 0; n < 4; n++) {
      *reinterpret_cast<float2*>(&Mi[(mt * 16 + g) * QM_RS + n * 8 + 2 * q]) = make_float2(c[4 * n], c[4 * n + 1]);
      *reinterpret_cast<float2*>(&Mi[(mt * 16 + g + 8) * QM_RS + n * 8 + 2 * q]) = make_float2(c[4 * n + 2], c[4 * n + 3]);
    }
  }
  __syncthreads();
  uint32_t val[3], chk = 0;
#pragma unroll
  for (int r = 0; r < 3; r++) {
    const float* Mf = M + fil * H_MS;
    const float v0 = Mf[fot[r].x & 0xffff] + Mf[fot[r].x >> 16], v1 = Mf[fot[r].y & 0xffff] + Mf[fot[r].y >> 16];
    const uint32_t xe = reinterpret_cast<const uint32_t*>(smem + H_XE)[(warp + 16 * r) * 8 + (n8 >> 2) * 4 + q];
    val[r] = fx1 ? xe : pack_bf16(v0, v1);
    st_img(dst + r * 8 * (G0_SLAB / 4), val[r]);
  }
#pragma unroll
  for (int r = 0; r < 3; r++) chk |= ld_back(dst + r * 8 * (G0_SLAB / 4)) ^ val[r];
  WRITER_FENCE();
  if (__any_sync(0xffffffffu, chk != 0)) __trap();
  __syncthreads();
  if (t == 0) asm volatile("red.relaxed.gpu.global.add.u32 [%0], 1;" ::"l"(P.ctr + 32) : "memory");
}

template <int S>
__device__ __forceinline__ uint32_t l_prod(const uint32_t (&vp)[4], const uint32_t (&X)[13]) {
  if constexpr (S < 78) {
    constexpr int a = S / 13, t = S % 13;
    return (a & 1) ? mul_hi(vp[a >> 1], X[t]) : mul_lo(vp[a >> 1], X[t]);
  } else if constexpr (S < 85) {
    constexpr int k = S - 78;
    constexpr int t = (k < 3) ? k : (k < 6 ? k + 3 : 12);
    return mul_lo(vp[3], X[t]);
  } else {
    return 0x00003F80u;
  }
}
template <int S>
__device__ __forceinline__ uint32_t g0_prod(const uint32_t (&X)[13], uint32_t selU, uint32_t selV) {
  if constexpr (S < 30) {
    constexpr int d = S / 6 + 1, a = (S % 6) >> 1;
    return (S & 1) ? mul_hi(X[a], X[a + d]) : mul_lo(X[a], X[a + d]);
  } else if constexpr (S < 33) {
    return mul_ew(X[S - 30], X[S - 24]);
  } else if constexpr (S < 35) {
    return mul_ew(X[S - 33], X[S - 33]);
  } else if constexpr (S == 35) {
    return mul_ew(__byte_perm(X[0], X[1], 0x5410), __byte_perm(X[0], X[1], 0x7632));
  } else if constexpr (S == 36) {
    return mul_lo(X[2], X[2]);
  } else if constexpr (S == 37) {
    return mul_hi(X[2], X[2]);
  } else if constexpr (S < 44) {
    constexpr int a = (S - 38) >> 1;
    return ((S - 38) & 1) ? mul_hi(X[12], X[a]) : mul_lo(X[12], X[a]);
  } else if constexpr (S < 47) {
    return X[S - 44];
  } else {
    return mul_ew(__byte_perm(X[12], 0x3F803F80u, selU), __byte_perm(X[12], 0x3F803F80u, selV));
  }
}

constexpr int NBK = 4;

template <int KS, int KE>
__device__ __forceinline__ void l_fill(uint32_t (*A)[4], const uint32_t (&vp)[2][4], const uint32_t (&X)[2][13]) {
  A[0][0] = l_prod<2 * KS>(vp[0], X[0]);
  A[0][1] = l_prod<2 * KS>(vp[1], X[1]);
  A[0][2] = l_prod<2 * KS + 1>(vp[0], X[0]);
  A[0][3] = l_prod<2 * KS + 1>(vp[1], X[1]);
  if constexpr (KS + 1 < KE) l_fill<KS + 1, KE>(A + 1, vp, X);
}
template <int KS, int OFF>
__device__ __forceinline__ void layer_rec(float (&d)[16], const uint32_t (&vp)[2][4], const uint32_t (&X)[2][13], uint64_t dk) {
  constexpr int KE = (KS + NBK < L_KS) ? KS + NBK : L_KS;
  uint32_t A[NBK][4];
  l_fill<KS, KE>(A, vp, X);
  wg_fence();
#pragma unroll
  for (int k = 0; k < KE - KS; k++)
    wgmma_rs_n32(d, A[k][0], A[k][1], A[k][2], A[k][3], dk + (uint64_t)((OFF + (KS + k) * L_SLAB) >> 4), (KS + k) > 0);
  wg_commit();
  if constexpr (KE < L_KS) {
    wg_wait<1>();
    layer_rec<KE, OFF>(d, vp, X, dk);
  }
}
template <int OFF, int NK>
__device__ __forceinline__ void layer_first(float (&d)[16], const uint32_t (&vp)[2][4], const uint32_t (&X)[2][13], uint64_t dk) {
  uint32_t A[NK][4];
  l_fill<0, NK>(A, vp, X);
  wg_fence();
#pragma unroll
  for (int k = 0; k < NK; k++) wgmma_rs_n32(d, A[k][0], A[k][1], A[k][2], A[k][3], dk + (uint64_t)((OFF + k * L_SLAB) >> 4), k > 0);
  wg_commit();
}
template <int KS, int KE>
__device__ __forceinline__ void g0_fill(uint32_t (*A)[4], const uint32_t (&X)[2][13], uint32_t selU, uint32_t selV) {
  A[0][0] = g0_prod<2 * KS>(X[0], selU, selV);
  A[0][1] = g0_prod<2 * KS>(X[1], selU, selV);
  A[0][2] = g0_prod<2 * KS + 1>(X[0], selU, selV);
  A[0][3] = g0_prod<2 * KS + 1>(X[1], selU, selV);
  if constexpr (KS + 1 < KE) g0_fill<KS + 1, KE>(A + 1, X, selU, selV);
}
template <int B0>
__device__ __forceinline__ void g0_rec(float (&d)[28], const uint32_t (&X)[2][13], uint32_t selU, uint32_t selV, uint64_t dk, uint32_t bar2, bool first) {
  constexpr int KS = B0 * NBK;
  if constexpr (KS == 8) { if (first) mbar_wait(bar2, 0); }
  if constexpr (KS == 16) { if (first) mbar_wait(bar2 + 8, 0); }
  constexpr int KE = (KS + NBK < G0_KS) ? KS + NBK : G0_KS;
  uint32_t A[NBK][4];
  g0_fill<KS, KE>(A, X, selU, selV);
  wg_fence();
#pragma unroll
  for (int k = 0; k < KE - KS; k++)
    wgmma_rs_n56(d, A[k][0], A[k][1], A[k][2], A[k][3], dk + (uint64_t)((OFF_G0 + (KS + k) * G0_SLAB) >> 4), (KS + k) > 0);
  wg_commit();
  if constexpr (KE < G0_KS) {
    wg_wait<1>();
    g0_rec<B0 + 1>(d, X, selU, selV, dk, bar2, first);
  }
}

__device__ __forceinline__ void ldsm_x4_t(uint32_t addr, uint32_t& r0, uint32_t& r1, uint32_t& r2, uint32_t& r3) {
  asm volatile("ldmatrix.sync.aligned.m8n8.x4.trans.shared.b16 {%0,%1,%2,%3}, [%4];"
               : "=r"(r0), "=r"(r1), "=r"(r2), "=r"(r3) : "r"(addr) : "memory");
}
__device__ __forceinline__ void ldsm_x2_t(uint32_t addr, uint32_t& r0, uint32_t& r1) {
  asm volatile("ldmatrix.sync.aligned.m8n8.x2.trans.shared.b16 {%0,%1}, [%2];" : "=r"(r0), "=r"(r1) : "r"(addr) : "memory");
}
__device__ __forceinline__ float tanh_fast(float x) { float y; asm("tanh.approx.f32 %0, %1;" : "=f"(y) : "f"(x)); return y; }

__device__ __forceinline__ uint32_t gelu2_pair(float lo, float hi, uint32_t bias) {
  uint32_t x = pack_bf16(lo, hi), t, u;
  asm("add.rn.bf16x2 %0, %0, %1;" : "+r"(x) : "r"(bias));
  asm("mul.rn.bf16x2 %0, %1, %1;" : "=r"(t) : "r"(x));
  asm("fma.rn.bf16x2 %0, %0, %1, %2;" : "+r"(t) : "r"(0x3D123D12u), "r"(0x3F4C3F4Cu));
  asm("mul.rn.bf16x2 %0, %1, %2;" : "=r"(u) : "r"(x), "r"(t));
  asm("tanh.approx.bf16x2 %0, %0;" : "+r"(u));
  asm("fma.rn.bf16x2 %0, %1, %0, %1;" : "+r"(u) : "r"(x));
  return u;
}

__device__ __forceinline__ void ldsm_x4(uint32_t addr, uint32_t (&r)[4]) {
  asm volatile("ldmatrix.sync.aligned.m8n8.x4.shared.b16 {%0,%1,%2,%3}, [%4];"
               : "=r"(r[0]), "=r"(r[1]), "=r"(r[2]), "=r"(r[3]) : "r"(addr) : "memory");
}
__device__ __forceinline__ uint32_t lds_u16(uint32_t addr) {
  unsigned short v;
  asm volatile("ld.shared.u16 %0, [%1];" : "=h"(v) : "r"(addr) : "memory");
  return v;
}
__device__ __forceinline__ uint32_t lds_u32(uint32_t addr) {
  uint32_t v;
  asm volatile("ld.shared.u32 %0, [%1];" : "=r"(v) : "r"(addr) : "memory");
  return v;
}

__global__ void __launch_bounds__(512, 1)
main_kernel(const __grid_constant__ Params P, const __grid_constant__ TmaMaps tms) {
  extern __shared__ __align__(1024) unsigned char smem[];
  const uint32_t sb = smem_u32(smem);
  const int tid = threadIdx.x, warp = __shfl_sync(0xffffffffu, tid >> 5, 0), lane = tid & 31;
  if (blockIdx.x < NHELP) {
    helper_role(blockIdx.x, P, smem, sb);
    return;
  }
  const int cta = blockIdx.x - NHELP, nq = cta & 3, grp = cta >> 2;
  const uint2 role = P.role[cta];
  const uint32_t bar0 = sb + OFF_BAR;
  auto BAR = [&](int i) { return bar0 + 8 * i; };
  const int wg = warp >> 2, w4 = warp & 3, g = lane >> 2, q = lane & 3;
  const uint64_t dk = P.dk;
  const long long tl_c0 = TL_START();
  TL_INIT();
  TL_PUT0(tl_c0);

  if (tid < 256) {
    const unsigned char* isrc = reinterpret_cast<const unsigned char*>(P.idx + grp * 128 * NF);
#pragma unroll
    for (int k = 0; k < 4; k++) {
      const int c = tid + 256 * k;
      if (c < 832) cp_async16(sb + OFF_IDX + c * 16, isrc + c * 16);
    }
    asm volatile("cp.async.commit_group;" ::: "memory");
#pragma unroll
    for (int k = 0; k < 8; k++) {
      const int c = tid + 256 * k;
      if (c < 2000) cp_async16(sb + OFF_TAB + ((c ^ ((c >> 3) & 1)) << 4), reinterpret_cast<const unsigned char*>(P.table) + c * 16);
    }
    asm volatile("cp.async.commit_group;" ::: "memory");
  }
  if (elect_one()) {
    mbar_init(BAR(warp), (warp == BAR_W1FREE || warp == BAR_W1DONE) ? 2 : 1);
    if (warp < NBAR - 16)
      mbar_init(BAR(16 + warp), (16 + warp == BAR_X0) ? 256 : (16 + warp == BAR_SETUP) ? SETUP_WARPS : (16 + warp == BAR_TABS) ? 224 : 1);
    asm volatile("fence.mbarrier_init.release.cluster;" ::: "memory");
  }
  __syncthreads();
  TL(26);

  if (warp == 15) {
    if (elect_one()) {
      mbar_expect_tx(BAR(BAR_STAB), sizeof(StaticTabs));
      bulk_g2s(sb + OFF_STAB, P.tabs, sizeof(StaticTabs), BAR(BAR_STAB));
      if ((sb & 0x3FFFF) != SMEM_BASE) __trap();
      const CUtensorMap* tm0 = &tms.m[nq];
      asm volatile("prefetch.tensormap [%0];" ::"l"(tm0) : "memory");
#pragma unroll
      for (int st = 0; st < W1_STAGES; st++) {
        if (st == 1 && (role.x >> 24) < 5) mbar_wait(BAR(BAR_Q), 0);
        mbar_expect_tx(BAR(BAR_W1FULL + st), W1_STAGE_BYTES);
        tma_2d(sb + w1_off(st), tm0, 0, st * 64, BAR(BAR_W1FULL + st));
        tma_2d(sb + w1_off(st) + 8192, tm0, 64, st * 64, BAR(BAR_W1FULL + st));
      }
      TLP(22);
      mbar_wait(BAR(BAR_EPOCH), 0);
      TLP(23);
      const unsigned epoch_p = lds_u32(sb + OFF_EPOCH);
      auto wait_ctr = [&](const unsigned* ctr, unsigned target) {
        unsigned v;
        uint32_t it = 0;
#pragma unroll 1
        do {
          asm volatile("ld.relaxed.gpu.global.u32 %0, [%1];" : "=r"(v) : "l"(ctr) : "memory");
          if (++it > (1u << 22)) __trap();
        } while ((int)(v - target) < 0);
      };
      wait_ctr(P.ctr + 32, epoch_p << 4);
      mbar_wait(BAR(BAR_X0), 0);
      TLP(24);
#pragma unroll
      for (int i = 0; i < 6; i++) {
        const uint32_t bar = i < 2 ? BAR(BAR_IMG + 0) : BAR(BAR_G0B + (i - 2) / 2);
        if (!(i & 1)) mbar_expect_tx(bar, G0_BYTES / 3);
        bulk_g2s(sb + OFF_G0 + i * (G0_BYTES / 6), P.img + i * (G0_BYTES / 6), G0_BYTES / 6, bar);
      }
      wait_ctr(P.ctr, epoch_p << 7);
      mbar_wait(BAR(BAR_W1FREE), 0);
      mbar_expect_tx(BAR(BAR_IMG + 2), L_BYTES);
#pragma unroll
      for (int i = 0; i < 4; i++)
        bulk_g2s(sb + OFF_LB + i * (L_BYTES / 4), P.img + G0_BYTES + L_BYTES + i * (L_BYTES / 4), L_BYTES / 4, BAR(BAR_IMG + 2));
      mbar_wait(BAR(BAR_W1DONE), 0);
      mbar_expect_tx(BAR(BAR_IMG + 1), L_BYTES);
      mbar_expect_tx(BAR(BAR_IMG + 3), L_BYTES);
#pragma unroll
      for (int i = 0; i < 2; i++)
        bulk_g2s(sb + OFF_LA + i * (L_BYTES / 2), P.img + G0_BYTES + i * (L_BYTES / 2), L_BYTES / 2, BAR(BAR_IMG + 1));
#pragma unroll
      for (int i = 0; i < 2; i++)
        bulk_g2s(sb + OFF_LC + i * (L_BYTES / 2), P.img + G0_BYTES + 2 * L_BYTES + i * (L_BYTES / 2), L_BYTES / 2, BAR(BAR_IMG + 3));
      TLP(25);
    }
    __syncwarp();
    mbar_wait(BAR(BAR_X0), 0);
    mbar_wait(BAR(BAR_TABS), 0);
  } else if (wg < 2) {
    asm volatile("cp.async.wait_group 1;" ::: "memory");
    named_bar(1, 256);
#pragma unroll
    for (int k = 0; k < 7; k++) {
      const int p = tid + 256 * k;
      if (p < 64 * NF) {
        const uint2 v = reinterpret_cast<const uint2*>(smem + OFF_IDX)[p];
        const uint32_t o0 = v.x * 32 + ((v.x >> 2) & 1) * 16, o1 = v.y * 32 + ((v.y >> 2) & 1) * 16;
        reinterpret_cast<uint32_t*>(smem + OFF_XOFF)[p] = o0 | (o1 << 16);
      }
    }
    TL(1);
    asm volatile("cp.async.wait_all;" ::: "memory");
    mbar_arrive(BAR(BAR_X0));
    mbar_wait(BAR(BAR_X0), 0);
    TL(3);
    float acc[56];
    {
      const uint32_t xo = sb + OFF_XOFF + (wg * 64 + w4 * 16 + (lane & 15)) * 52;
      const uint32_t tb = sb + OFF_TAB, hx = (lane >> 4) << 4;
      const uint64_t db0 = P.dmn;
      uint32_t A[3][2][4];
#pragma unroll
      for (int pr = 0; pr < 2; pr++) {
        const uint32_t oa = lds_u32(xo + 4 * pr);
        ldsm_x4(tb + ((oa & 0xffff) ^ hx), A[pr][0]); ldsm_x4(tb + ((oa >> 16) ^ hx), A[pr][1]);
      }
#pragma unroll
      for (int pr = 0; pr < 13; pr++) {
        const int st = pr >> 1;
        uint32_t oa = 0;
        if (pr + 2 < 13) oa = lds_u32(xo + 4 * (pr + 2));
        if (!(pr & 1)) mbar_wait(BAR(BAR_W1FULL + st), 0);
        if (pr == 0) TL(28); if (pr == 6) TL(29);
        const uint64_t db = db0 + (uint64_t)((w1_off(st) + (pr & 1) * 4096) >> 4);
        wg_fence();
        wgmma_rs_n112_tb(acc, A[pr % 3][0][0], A[pr % 3][0][1], A[pr % 3][0][2], A[pr % 3][0][3], db, pr > 0);
        wgmma_rs_n112_tb(acc, A[pr % 3][1][0], A[pr % 3][1][1], A[pr % 3][1][2], A[pr % 3][1][3], db + (2048 >> 4), 1);
        wg_commit();
        wg_wait<1>();
        if (pr == 4 && (tid & 127) == 0) mbar_arrive(BAR(BAR_W1FREE));
        if (pr + 2 < 13) { ldsm_x4(tb + ((oa & 0xffff) ^ hx), A[(pr + 2) % 3][0]); ldsm_x4(tb + ((oa >> 16) ^ hx), A[(pr + 2) % 3][1]); }
      }
      wg_wait<0>();
      reg_fence(acc);
      if ((tid & 127) == 0) mbar_arrive(BAR(BAR_W1DONE));
    }
    TL(4);
    float dot[4];
    {
      mbar_wait(BAR(BAR_TABS), 0);
      uint32_t bb[16];
      const uint4* bp = reinterpret_cast<const uint4*>(smem + OFF_BW + q * 64);
#pragma unroll
      for (int i = 0; i < 4; i++) { const uint4 v = bp[i]; bb[4 * i] = v.x; bb[4 * i + 1] = v.y; bb[4 * i + 2] = v.z; bb[4 * i + 3] = v.w; }
      uint32_t H[14][2];
#pragma unroll
      for (int c = 0; c < 14; c++) {
        H[c][0] = gelu2_pair(acc[4 * c], acc[4 * c + 1], bb[c]);
        H[c][1] = gelu2_pair(acc[4 * c + 2], acc[4 * c + 3], bb[c]);
      }
      wg_fence();
#pragma unroll
      for (int j = 0; j < 7; j++)
        wgmma_rs_n8(dot, H[2 * j][0], H[2 * j][1], H[2 * j + 1][0], H[2 * j + 1][1], dk + (uint64_t)((OFF_W2 + j * 256) >> 4), j > 0);
      wg_commit();
      wg_wait<0>();
      reg_fence(dot);
    }
    __syncwarp();
    mbar_wait(BAR(BAR_EPOCH), 0);
    if (q == 0) {
      const unsigned epoch = lds_u32(sb + OFF_EPOCH);
#pragma unroll
      for (int r = 0; r < 2; r++) {
        const int row = wg * 64 + w4 * 16 + g + 8 * r;
        const unsigned long long pk = ((unsigned long long)epoch << 32) | (unsigned long long)__float_as_uint(dot[2 * r]);
        asm volatile("st.relaxed.gpu.global.u64 [%0], %1;" ::"l"(P.part + cta * 128 + row), "l"(pk) : "memory");
      }
    }
    __syncwarp();
  } else {
    const int t = tid - 256;
    const bool is_arr = (t == 192);
    unsigned ctr0 = 0;
    if (is_arr) asm volatile("ld.relaxed.gpu.global.u32 %0, [%1];" : "=r"(ctr0) : "l"(P.ctr) : "memory");
    {
      const int kind = role.x >> 24, w = warp - 8, rgrp = (role.y >> 24) & 15, rj = role.y >> 28;
      const unsigned char* wsb = reinterpret_cast<const unsigned char*>(P.ws);
      if (kind < 5 && elect_one()) {
        const uint32_t bytes = role.y & 0xffff;
        const uint32_t o = w * 8192;
        if (w == 0) mbar_expect_tx(BAR(BAR_Q), bytes);
        if (o < bytes) bulk_g2s(sb + OFF_G0 + o, wsb + (role.x & 0xffffff) + o, min(bytes - o, 8192u), BAR(BAR_Q));
      }
      TL(40);
      __syncwarp();
      const StaticTabs* T = reinterpret_cast<const StaticTabs*>(smem + OFF_STAB);
      uint32_t* img32 = reinterpret_cast<uint32_t*>(P.img);
      const unsigned char* raw = smem + OFF_G0 + ((role.y >> 16) & 127);
      uint32_t chk = 0;
      if (kind < 3) chk = layer_row(kind, rgrp, rj * SETUP_WARPS + w, lane, raw, T, BAR(BAR_Q), BAR(BAR_STAB), P.wout, img32);
      else if (kind == 3) chk = x1_row(rgrp, rj * SETUP_WARPS + w, lane, raw, T, BAR(BAR_Q), BAR(BAR_STAB), img32);
      if (__any_sync(0xffffffffu, chk != 0)) __trap();
      if (lane == 0) mbar_arrive(BAR(BAR_SETUP));
    }
    TL(1);
    if (is_arr) {
      asm volatile("" : "+r"(ctr0));
      *reinterpret_cast<volatile unsigned*>(smem + OFF_EPOCH) = (ctr0 >> 7) + 1;
      mbar_wait(BAR(BAR_SETUP), 0);
      TLA(30);
      if ((role.x >> 24) == 3) asm volatile("red.relaxed.gpu.global.add.u32 [%0], 1;" ::"l"(P.ctr + 32) : "memory");
      asm volatile("red.relaxed.gpu.global.add.u32 [%0], 1;" ::"l"(P.ctr) : "memory");
      mbar_arrive(BAR(BAR_EPOCH));
      TLA(31);
    }
    __syncwarp();
    {
      const int c0 = (nq >> 1) * 208 + (nq & 1) * 96, nw = (nq & 1) ? 112 : 96;
      if (t < 56) {
        const int n = 2 * t;
        const uint32_t v = (n < nw) ? __ldg(reinterpret_cast<const uint32_t*>(P.b1 + c0 + n)) : 0u;
        reinterpret_cast<uint32_t*>(smem + OFF_BW)[(t & 3) * 16 + (t >> 2)] = v;
      }
      if (t >= 64 && t < 64 + 112) {
        const int k = t - 64;
        const float w = (k < nw) ? 0.5f * bf2f(__ldg(P.w2 + c0 + k)) : 0.f;
        unsigned char* base = smem + OFF_W2 + (k >> 4) * 256 + ((k >> 3) & 1) * 128;
        *reinterpret_cast<bf16*>(base + (k & 7) * 2) = __float2bfloat16(w);
        if ((k & 7) == 0) {
#pragma unroll
          for (int r = 1; r < 8; r++) *reinterpret_cast<uint4*>(base + r * 16) = make_uint4(0, 0, 0, 0);
        }
      }
      fence_proxy_async();
    }
    if (t >= 128 && t < 192) {
      int u = t - 128, l = u >> 5, qq = (u >> 3) & 3, a = u & 7;
      float wtv = 0.f;
      if (a < 6) wtv = bf2f(__ldg(P.wout + l * NF + 8 * (a >> 1) + 2 * qq + (a & 1)));
      else if (a == 6 && !(qq & 1)) wtv = bf2f(__ldg(P.wout + l * NF + 24 + (qq >> 1)));
      reinterpret_cast<float*>(smem + OFF_WTAB)[u] = wtv;
    }
    mbar_arrive(BAR(BAR_TABS));
    TL(2);
    mbar_wait(BAR(BAR_X0), 0);
    mbar_wait(BAR(BAR_TABS), 0);
  }

  TL(5);
  const uint32_t selU = (q == 0) ? 0x1010u : (q == 1) ? 0x3232u : (q == 2) ? 0x3210u : 0x7654u;
  const uint32_t selV = (q < 2) ? 0x3210u : 0x7654u;
  uint32_t bo_raw = __ldg(reinterpret_cast<const unsigned short*>(P.bout));
  mbar_wait(BAR(BAR_EPOCH), 0);
  mbar_wait(BAR(BAR_STAB), 0);
  const unsigned epoch = lds_u32(sb + OFF_EPOCH);

  uint32_t X[2][13];
  auto load_x = [&](int sl) {
    const uint4 o = *reinterpret_cast<const uint4*>(smem + OFF_LOFF + lane * 16);
    const uint32_t xo = sb + OFF_XOFF + sl * 52;
    const uint32_t tb = sb + OFF_TAB, hx = ((lane >> 3) & 1) << 4;
    const uint32_t a0 = lds_u16(xo + (o.x & 0xffff)), a1 = lds_u16(xo + (o.x >> 16));
    const uint32_t a2 = lds_u16(xo + (o.y & 0xffff)), a3 = lds_u16(xo + (o.y >> 16));
    const uint32_t a4 = lds_u16(xo + (o.z & 0xffff)), a5 = lds_u16(xo + (o.z >> 16));
    const uint32_t a6 = lds_u16(xo + (o.w & 0xffff));
    ldsm_x4_t(tb + (a0 ^ hx), X[0][0], X[1][0], X[0][1], X[1][1]);
    ldsm_x4_t(tb + (a1 ^ hx), X[0][2], X[1][2], X[0][3], X[1][3]);
    ldsm_x4_t(tb + (a2 ^ hx), X[0][4], X[1][4], X[0][5], X[1][5]);
    ldsm_x4_t(tb + (a3 ^ hx), X[0][6], X[1][6], X[0][7], X[1][7]);
    ldsm_x4_t(tb + (a4 ^ hx), X[0][8], X[1][8], X[0][9], X[1][9]);
    ldsm_x4_t(tb + (a5 ^ hx), X[0][10], X[1][10], X[0][11], X[1][11]);
    ldsm_x2_t(tb + (a6 ^ hx), X[0][12], X[1][12]);
  };
  load_x(nq * 32 + wg * 4 + w4);
#pragma unroll 1
  for (int it = 0; it < 2; it++) {
    const int sl = nq * 32 + (wg + 4 * it) * 4 + w4;
    float S = 0.f;
    uint32_t vx[2][4], vg[2][4];
    {
      float a0[28];
      if (it == 0) mbar_wait(BAR(BAR_IMG + 0), 0);
      if (it < 2) TL(6 + it * 8);
      g0_rec<0>(a0, X, selU, selV, dk, BAR(BAR_G0B), it == 0);
      wg_wait<0>();
      reg_fence(a0);
      const float4* wt = reinterpret_cast<const float4*>(smem + OFF_WTAB) + q * 2;
      float4 wa = wt[0], wb = wt[1];
#pragma unroll
      for (int r = 0; r < 2; r++) {
        S = fmaf(wa.x, a0[0 + 2 * r], S); S = fmaf(wa.y, a0[1 + 2 * r], S);
        S = fmaf(wa.z, a0[4 + 2 * r], S); S = fmaf(wa.w, a0[5 + 2 * r], S);
        S = fmaf(wb.x, a0[8 + 2 * r], S); S = fmaf(wb.y, a0[9 + 2 * r], S);
        S = fmaf(wb.z, a0[24 + 2 * r], S);
#pragma unroll
        for (int c = 0; c < 3; c++) {
          vx[r][c] = pack_bf16(a0[4 * c + 2 * r], a0[4 * c + 2 * r + 1]);
          vg[r][c] = pack_bf16(a0[12 + 4 * c + 2 * r], a0[12 + 4 * c + 2 * r + 1]);
        }
        vx[r][3] = pack_bf16(a0[24 + 2 * r], 0.f);
        vg[r][3] = pack_bf16(a0[24 + 2 * r + 1], 0.f);
      }
    }
    float g3[16], xa[16];
    if (it < 2) TL(7 + it * 8);
    if (it == 0) {
      mbar_wait(BAR(BAR_IMG + 2), 0);
      mbar_wait(BAR(BAR_IMG + 1), 0);
      mbar_wait(BAR(BAR_IMG + 3), 0);
    }
    if (it < 2) TL(8 + it * 8);
    layer_rec<0, OFF_LB>(xa, vx, X, dk);
    if (it < 2) TL(9 + it * 8);
    wg_wait<1>();
    layer_first<OFF_LA, 3>(g3, vg, X, dk);
    wg_wait<1>();
    reg_fence(xa);
    {
      const float4* wt = reinterpret_cast<const float4*>(smem + OFF_WTAB) + 8 + q * 2;
      float4 wa = wt[0], wb = wt[1];
#pragma unroll
      for (int r = 0; r < 2; r++) {
        S = fmaf(wa.x, xa[0 + 2 * r], S); S = fmaf(wa.y, xa[1 + 2 * r], S);
        S = fmaf(wa.z, xa[4 + 2 * r], S); S = fmaf(wa.w, xa[5 + 2 * r], S);
        S = fmaf(wb.x, xa[8 + 2 * r], S); S = fmaf(wb.y, xa[9 + 2 * r], S);
        S = fmaf(wb.z, xa[12 + 2 * r], S);
#pragma unroll
        for (int c = 0; c < 3; c++) vx[r][c] = pack_bf16(xa[4 * c + 2 * r], xa[4 * c + 2 * r + 1]);
        vx[r][3] = pack_bf16(xa[12 + 2 * r], 0.f);
      }
    }
    layer_rec<3, OFF_LA>(g3, vg, X, dk);
    if (it < 2) TL(10 + it * 8);
    wg_wait<1>();
    const unsigned long long* pp = P.part + (grp * 4 + (lane & 3)) * 128 + sl;
    unsigned long long pk;
    asm volatile("ld.relaxed.gpu.global.u64 %0, [%1];" : "=l"(pk) : "l"(pp) : "memory");
    float xc[16];
    layer_rec<0, OFF_LC>(xc, vx, X, dk);
    if (it == 0) load_x(sl + 16);
    wg_wait<0>();
    reg_fence(xc);
    reg_fence(g3);
    {
      float Se = 0.f;
#pragma unroll
      for (int r = 0; r < 2; r++) {
#pragma unroll
        for (int c = 0; c < 3; c++) {
          S = fmaf(g3[4 * c + 2 * r], xc[4 * c + 2 * r], S);
          S = fmaf(g3[4 * c + 2 * r + 1], xc[4 * c + 2 * r + 1], S);
        }
        Se = fmaf(g3[12 + 2 * r], xc[12 + 2 * r], Se);
      }
      if (!(q & 1)) S += Se;
    }
#pragma unroll
    for (int o = 16; o > 0; o >>= 1) S += __shfl_xor_sync(0xffffffffu, S, o);
    if (it < 2) TL(12 + it * 8);
    {
      uint32_t spin = 0;
      while (lane < 4 && (unsigned)(pk >> 32) != epoch) {
        asm volatile("ld.relaxed.gpu.global.u64 %0, [%1];" : "=l"(pk) : "l"(pp) : "memory");
        if (++spin > (1u << 24)) __trap();
      }
      __syncwarp();
      float dv = __uint_as_float((unsigned)pk);
      float d01 = dv + __shfl_xor_sync(0xffffffffu, dv, 1);
      float dsum = d01 + __shfl_xor_sync(0xffffffffu, d01, 2);
      asm volatile("" : "+r"(bo_raw));
      if (lane == 0) P.out[grp * 128 + sl] = __float2bfloat16(S + dsum + __uint_as_float(bo_raw << 16));
    }
    __syncwarp();
    if (it < 2) TL(13 + it * 8);
  }
  TL_DUMP();
}

__global__ void __launch_bounds__(128) fallback_kernel(const int* __restrict__ idx, const bf16* __restrict__ table, const bf16* __restrict__ ws,
                                                       const bf16* __restrict__ wout, const bf16* __restrict__ w1, const bf16* __restrict__ b1,
                                                       const bf16* __restrict__ w2, const bf16* __restrict__ bout, bf16* __restrict__ out) {
  __shared__ float x0[416], xa[416], xb[416], red[128];
  const int b = blockIdx.x, t = threadIdx.x;
  for (int i = t; i < 416; i += 128) { x0[i] = bf2f(table[idx[b * NF + i / 16] * 16 + (i & 15)]); xa[i] = x0[i]; }
  __syncthreads();
  float acc = 0.f;
  float* cur = xa;
  float* nxt = xb;
  for (int l = 0; l < 6; l++) {
    for (int o = t; o < 416; o += 128) {
      const int h = o >> 4, d = o & 15;
      const bf16* w = ws + (l * NF + h) * NF * NF;
      float s = 0.f;
      for (int i = 0; i < NF; i++) {
        float u = 0.f;
        for (int j = 0; j < NF; j++) u = fmaf(bf2f(w[i * NF + j]), x0[j * 16 + d], u);
        s = fmaf(u, cur[i * 16 + d], s);
      }
      nxt[o] = s;
      acc = fmaf(s, bf2f(wout[l * NF + h]), acc);
    }
    __syncthreads();
    float* tmp = cur; cur = nxt; nxt = tmp;
  }
  for (int n = t; n < 416; n += 128) {
    float h = 0.f;
    for (int k = 0; k < 416; k++) h = fmaf(x0[k], bf2f(w1[k * 416 + n]), h);
    h += bf2f(b1[n]);
    const float gl = 0.5f * h * (1.f + tanhf(0.7978845608028654f * (h + 0.044715f * h * h * h)));
    acc = fmaf(gl, bf2f(w2[n]), acc);
  }
  red[t] = acc;
  __syncthreads();
  for (int o = 64; o > 0; o >>= 1) { if (t < o) red[t] += red[t + o]; __syncthreads(); }
  if (t == 0) out[b] = __float2bfloat16(red[0] + bf2f(bout[0]));
}

typedef CUresult (*EncodeFn)(CUtensorMap*, CUtensorMapDataType, cuuint32_t, void*, const cuuint64_t*, const cuuint64_t*,
                             const cuuint32_t*, const cuuint32_t*, CUtensorMapInterleave, CUtensorMapSwizzle,
                             CUtensorMapL2promotion, CUtensorMapFloatOOBfill);

extern "C" void kernel_launch(void* const* d_in, const int* in_sizes, int n_in, void* d_out, int out_size) {
  const int* idx = (const int*)d_in[0];
  const bf16* table = (const bf16*)d_in[1];
  const bf16* ws = (const bf16*)d_in[2];
  const bf16* wout = (const bf16*)d_in[3];
  const bf16* w1 = (const bf16*)d_in[4];
  const bf16* b1 = (const bf16*)d_in[5];
  const bf16* w2 = (const bf16*)d_in[6];
  const bf16* bo = (const bf16*)d_in[7];
  bf16* out = (bf16*)d_out;

  static EncodeFn enc = nullptr;
  static Params P;
  static int n_sm = 0;
  if (!n_sm) {
    int dev = 0;
    cudaGetDevice(&dev);
    cudaDeviceGetAttribute(&n_sm, cudaDevAttrMultiProcessorCount, dev);
  }
  if (n_sm < NCTA + NHELP) {
    fallback_kernel<<<4096, 128, 0, cudaStreamPerThread>>>(idx, table, ws, wout, w1, b1, w2, bo, out);
    return;
  }
  if (!enc) {
    void* fn = nullptr;
    cudaDriverEntryPointQueryResult qr;
    cudaGetDriverEntryPoint("cuTensorMapEncodeTiled", &fn, cudaEnableDefault, &qr);
    enc = (EncodeFn)fn;
    cudaFuncSetAttribute(main_kernel, cudaFuncAttributeMaxDynamicSharedMemorySize, LAUNCH_SMEM);
    void* p;
    cudaGetSymbolAddress(&p, g_img); P.img = (unsigned char*)p;
    cudaGetSymbolAddress(&p, g_part); P.part = (unsigned long long*)p;
    cudaGetSymbolAddress(&p, g_ctr); P.ctr = (unsigned*)p;
    cudaGetSymbolAddress(&p, g_tabs); P.tabs = p;
    P.dk = make_desc(0, 128, 256, 0);
    P.dmn = make_desc(0, 8192, 1024, 1);
    for (int c = 0; c < NCTA; c++) P.role[c] = make_role(c);
  }
  P.idx = idx; P.table = table; P.ws = ws; P.wout = wout; P.b1 = b1; P.w2 = w2; P.bout = bo; P.out = out;
  TmaMaps tms;
  for (int h = 0; h < 4; h++) {
    const int c0 = (h >> 1) * 208 + (h & 1) * 96, nw = (h & 1) ? 112 : 96;
    cuuint64_t dims[2] = {(cuuint64_t)nw, 416};
    cuuint64_t strides[1] = {832};
    cuuint32_t box[2] = {64, 64};
    cuuint32_t es[2] = {1, 1};
    enc(&tms.m[h], CU_TENSOR_MAP_DATA_TYPE_BFLOAT16, 2, (void*)(w1 + c0), dims, strides, box, es,
        CU_TENSOR_MAP_INTERLEAVE_NONE, CU_TENSOR_MAP_SWIZZLE_128B, CU_TENSOR_MAP_L2_PROMOTION_L2_128B,
        CU_TENSOR_MAP_FLOAT_OOB_FILL_NONE);
  }
  main_kernel<<<NCTA + NHELP, 512, LAUNCH_SMEM, cudaStreamPerThread>>>(P, tms);
}
```

```cpp
#include <cuda_runtime.h>
#include <cuda_bf16.h>
#include <cuda.h>
#include <stdint.h>

typedef __nv_bfloat16 bf16;
#define WRITER_FENCE() fence_proxy_async_global()

constexpr int NF = 26;
constexpr int NCTA = 128;

constexpr int G0_KS = 24, G0_N = 56, G0_SLAB = G0_N * 32;
constexpr int L_KS = 43, L_SLAB = 1024;
constexpr int G0_BYTES = G0_KS * G0_SLAB;
constexpr int L_BYTES = L_KS * L_SLAB;
constexpr int IMG_BYTES = G0_BYTES + 3 * L_BYTES;

constexpr int W1_STAGES = 7;
constexpr int W1_STAGE_BYTES = 16384;
constexpr int OFF_LB = 0;
constexpr int OFF_LA = 44032;
constexpr int OFF_LC = 88064;
__host__ __device__ constexpr int w1_off(int st) { return st < 2 ? st * W1_STAGE_BYTES : OFF_LA + (st - 2) * W1_STAGE_BYTES; }
constexpr int OFF_G0 = 132096;
constexpr int OFF_IDX = 132096 + 16384;
constexpr int OFF_TAB = OFF_G0 + G0_BYTES;
constexpr int OFF_XOFF = OFF_TAB + 32000;
constexpr int OFF_BAR = OFF_XOFF + 6656;
constexpr int OFF_BW = OFF_BAR + 256;
constexpr int OFF_W2 = OFF_BW + 256;
constexpr int OFF_WTAB = OFF_W2 + 1792;
constexpr int OFF_EPOCH = OFF_WTAB + 256;
constexpr int OFF_STAB = (OFF_EPOCH + 16 + 127) / 128 * 128;
constexpr int OFF_LOFF = OFF_STAB + 3072 + 704;
constexpr int SMEM_BYTES = OFF_STAB + 4288;
static_assert(SMEM_BYTES <= 229376, "smem");
constexpr int LAUNCH_SMEM = SMEM_BYTES;

constexpr int BAR_W1FULL = 0  , BAR_W1FREE = 10  , BAR_W1DONE = 11  , BAR_G0OK = 12,
              BAR_IMG = 14  , BAR_X0 = 18, BAR_SETUP = 19, BAR_EPOCH = 20, BAR_TABS = 21,
              BAR_Q = 22, BAR_STAB = 23, BAR_G0B = 24  , NBAR = 26;

struct TmaMaps { CUtensorMap m[4]; };
struct Params {
  const int* idx; const bf16* table; const bf16* ws; const bf16* wout; const bf16* b1; const bf16* w2; const bf16* bout;
  bf16* out;
  unsigned char* img; unsigned long long* part; unsigned* ctr; const void* tabs;
  uint64_t dk, dmn;
  uint2 role[NCTA];
};

__device__ __align__(1024) unsigned char g_img[IMG_BYTES];
__device__ unsigned long long g_part[NCTA * 128];
__device__ __align__(128) unsigned g_ctr[64];

#define GT(i) do {} while (0)
#define TL(i) do {} while (0)
#define TLP(i) do {} while (0)
#define TLA(i) do {} while (0)
#define TLW(w, i) do {} while (0)
#define TL_INIT() do {} while (0)
#define TL_START() 0
#define TL_PUT0(c) do {} while (0)
#define TL_DUMP() do {} while (0)
__device__ __forceinline__ uint32_t smem_u32(const void* p) { return (uint32_t)__cvta_generic_to_shared(p); }
__device__ __forceinline__ bool elect_one() {
  uint32_t pred;
  asm volatile("{\n.reg .pred p;\nelect.sync _|p, 0xffffffff;\nselp.u32 %0, 1, 0, p;\n}\n" : "=r"(pred));
  return pred != 0;
}
__device__ __forceinline__ void mbar_init(uint32_t bar, uint32_t cnt) {
  asm volatile("mbarrier.init.shared::cta.b64 [%0], %1;" ::"r"(bar), "r"(cnt) : "memory");
}
__device__ __forceinline__ void mbar_expect_tx(uint32_t bar, uint32_t bytes) {
  asm volatile("mbarrier.arrive.expect_tx.shared::cta.b64 _, [%0], %1;" ::"r"(bar), "r"(bytes) : "memory");
}
__device__ __forceinline__ void mbar_arrive(uint32_t bar) {
  asm volatile("mbarrier.arrive.shared::cta.b64 _, [%0];" ::"r"(bar) : "memory");
}
__device__ __forceinline__ bool mbar_try(uint32_t bar, uint32_t parity) {
  uint32_t ok;
  asm volatile("{\n.reg .pred p;\nmbarrier.try_wait.parity.shared::cta.b64 p, [%1], %2;\nselp.u32 %0, 1, 0, p;\n}\n"
               : "=r"(ok) : "r"(bar), "r"(parity) : "memory");
  return ok != 0;
}
__device__ __forceinline__ void mbar_wait(uint32_t bar, uint32_t parity) {
#pragma unroll 1
  for (uint32_t it = 0; it < (1u << 26); it++)
    if (mbar_try(bar, parity)) return;
  __trap();
}
__device__ __forceinline__ void bulk_g2s(uint32_t dst, const void* src, uint32_t bytes, uint32_t bar) {
  asm volatile("cp.async.bulk.shared::cluster.global.mbarrier::complete_tx::bytes [%0], [%1], %2, [%3];"
               ::"r"(dst), "l"(src), "r"(bytes), "r"(bar) : "memory");
}
__device__ __forceinline__ void tma_2d(uint32_t dst, const CUtensorMap* tm, int x, int y, uint32_t bar) {
  asm volatile("cp.async.bulk.tensor.2d.shared::cluster.global.mbarrier::complete_tx::bytes [%0], [%1, {%3, %4}], [%2];"
               ::"r"(dst), "l"(tm), "r"(bar), "r"(x), "r"(y) : "memory");
}
__device__ __forceinline__ void cp_async16(uint32_t dst, const void* src) {
  asm volatile("cp.async.cg.shared.global [%0], [%1], 16;" ::"r"(dst), "l"(src) : "memory");
}
__device__ __forceinline__ void fence_proxy_async() { asm volatile("fence.proxy.async.shared::cta;" ::: "memory"); }
__device__ __forceinline__ void fence_proxy_async_all() { asm volatile("fence.proxy.async;" ::: "memory"); }
template <int ID, int N> __device__ __forceinline__ void named_bar_t() { asm volatile("bar.sync %0, %1;" ::"n"(ID), "n"(N) : "memory"); }
#define named_bar(id, n) named_bar_t<id, n>()

__device__ __forceinline__ void wg_fence() { asm volatile("wgmma.fence.sync.aligned;" ::: "memory"); }
__device__ __forceinline__ void wg_commit() { asm volatile("wgmma.commit_group.sync.aligned;" ::: "memory"); }
template <int N> __device__ __forceinline__ void wg_wait() { asm volatile("wgmma.wait_group.sync.aligned %0;" ::"n"(N) : "memory"); }
template <int N> __device__ __forceinline__ void reg_fence(float (&d)[N]) {
#pragma unroll
  for (int i = 0; i < N; i++) asm volatile("" : "+f"(d[i])::"memory");
}
constexpr uint32_t SMEM_BASE = 1024;
__host__ __device__ constexpr uint64_t make_desc(uint32_t off, uint32_t lbo, uint32_t sbo, uint32_t swz) {
  return (uint64_t)(((SMEM_BASE + off) & 0x3FFFF) >> 4) | ((uint64_t)(lbo >> 4) << 16) | ((uint64_t)(sbo >> 4) << 32) | ((uint64_t)swz << 62);
}

#define ACC4(d, o) "+f"(d[o]), "+f"(d[o + 1]), "+f"(d[o + 2]), "+f"(d[o + 3])
#define ACC8(d, o) ACC4(d, o), ACC4(d, o + 4)

__device__ __forceinline__ void wgmma_rs_n32(float (&d)[16], uint32_t a0, uint32_t a1, uint32_t a2, uint32_t a3, uint64_t db, int sc) {
  asm volatile("{\n.reg .pred p;\nsetp.ne.b32 p, %21, 0;\n"
               "wgmma.mma_async.sync.aligned.m64n32k16.f32.bf16.bf16 "
               "{%0,%1,%2,%3,%4,%5,%6,%7,%8,%9,%10,%11,%12,%13,%14,%15}, {%16,%17,%18,%19}, %20, p, 1, 1, 0;\n}\n"
               : ACC8(d, 0), ACC8(d, 8)
               : "r"(a0), "r"(a1), "r"(a2), "r"(a3), "l"(db), "r"(sc));
}
__device__ __forceinline__ void wgmma_rs_n56(float (&d)[28], uint32_t a0, uint32_t a1, uint32_t a2, uint32_t a3, uint64_t db, int sc) {
  asm volatile("{\n.reg .pred p;\nsetp.ne.b32 p, %33, 0;\n"
               "wgmma.mma_async.sync.aligned.m64n56k16.f32.bf16.bf16 "
               "{%0,%1,%2,%3,%4,%5,%6,%7,%8,%9,%10,%11,%12,%13,%14,%15,%16,%17,%18,%19,%20,%21,%22,%23,%24,%25,%26,%27}, "
               "{%28,%29,%30,%31}, %32, p, 1, 1, 0;\n}\n"
               : ACC8(d, 0), ACC8(d, 8), ACC8(d, 16), ACC4(d, 24)
               : "r"(a0), "r"(a1), "r"(a2), "r"(a3), "l"(db), "r"(sc));
}
__device__ __forceinline__ void wgmma_rs_n112_tb(float (&d)[56], uint32_t a0, uint32_t a1, uint32_t a2, uint32_t a3, uint64_t db, int sc) {
  asm volatile("{\n.reg .pred p;\nsetp.ne.b32 p, %61, 0;\n"
               "wgmma.mma_async.sync.aligned.m64n112k16.f32.bf16.bf16 "
               "{%0,%1,%2,%3,%4,%5,%6,%7,%8,%9,%10,%11,%12,%13,%14,%15,%16,%17,%18,%19,%20,%21,%22,%23,%24,%25,%26,%27,%28,%29,%30,%31,%32,%33,%34,%35,%36,%37,%38,%39,%40,%41,%42,%43,%44,%45,%46,%47,%48,%49,%50,%51,%52,%53,%54,%55}, "
               "{%56,%57,%58,%59}, %60, p, 1, 1, 1;\n}\n"
               : ACC8(d, 0), ACC8(d, 8), ACC8(d, 16), ACC8(d, 24), ACC8(d, 32), ACC8(d, 40), ACC8(d, 48)
               : "r"(a0), "r"(a1), "r"(a2), "r"(a3), "l"(db), "r"(sc));
}

__device__ __forceinline__ void wgmma_rs_n8(float (&d)[4], uint32_t a0, uint32_t a1, uint32_t a2, uint32_t a3, uint64_t db, int sc) {
  asm volatile("{\n.reg .pred p;\nsetp.ne.b32 p, %9, 0;\n"
               "wgmma.mma_async.sync.aligned.m64n8k16.f32.bf16.bf16 {%0,%1,%2,%3}, {%4,%5,%6,%7}, %8, p, 1, 1, 0;\n}\n"
               : ACC4(d, 0)
               : "r"(a0), "r"(a1), "r"(a2), "r"(a3), "l"(db), "r"(sc));
}
__device__ __forceinline__ uint32_t mul_lo(uint32_t v, uint32_t r) {
  __nv_bfloat162 a = *reinterpret_cast<__nv_bfloat162*>(&v), b = *reinterpret_cast<__nv_bfloat162*>(&r);
  __nv_bfloat162 c = __hmul2(__low2bfloat162(a), b);
  return *reinterpret_cast<uint32_t*>(&c);
}
__device__ __forceinline__ uint32_t mul_hi(uint32_t v, uint32_t r) {
  __nv_bfloat162 a = *reinterpret_cast<__nv_bfloat162*>(&v), b = *reinterpret_cast<__nv_bfloat162*>(&r);
  __nv_bfloat162 c = __hmul2(__high2bfloat162(a), b);
  return *reinterpret_cast<uint32_t*>(&c);
}
__device__ __forceinline__ uint32_t mul_ew(uint32_t v, uint32_t r) {
  __nv_bfloat162 a = *reinterpret_cast<__nv_bfloat162*>(&v), b = *reinterpret_cast<__nv_bfloat162*>(&r);
  __nv_bfloat162 c = __hmul2(a, b);
  return *reinterpret_cast<uint32_t*>(&c);
}
__device__ __forceinline__ uint32_t pack_bf16(float lo, float hi) {
  uint32_t r;
  asm("cvt.rn.bf16x2.f32 %0, %1, %2;" : "=r"(r) : "f"(hi), "f"(lo));
  return r;
}
__device__ __forceinline__ float bf2f(bf16 v) { return __bfloat162float(v); }
__device__ __forceinline__ float bflo(uint32_t w) { return __uint_as_float(w << 16); }
__device__ __forceinline__ float bfhi(uint32_t w) { return __uint_as_float(w & 0xffff0000u); }

__device__ __forceinline__ void st_img(uint32_t* p, uint32_t v) {
  asm volatile("st.relaxed.gpu.global.u32 [%0], %1;" ::"l"(p), "r"(v) : "memory");
}
__device__ __forceinline__ void fence_proxy_async_global() { asm volatile("fence.proxy.async.global;" ::: "memory"); }
__device__ __forceinline__ uint32_t ld_back(const uint32_t* p) {
  uint32_t v;
  asm volatile("ld.relaxed.gpu.global.u32 %0, [%1];" : "=r"(v) : "l"(p) : "memory");
  return v;
}
__host__ __device__ constexpr int Fq(int q, int t, int e) {
  if (t == 12) return 24 + e;
  const int u = (t + 3 * q) % 12;
  const int sw = (q >= 2 && u >= 6) ? 1 : 0;
  return 2 * u + (e ^ sw);
}
constexpr int M_ONE = 26, M_NONE = 27;
struct Mono { int f1, f2; };
__host__ __device__ constexpr Mono g0_mono(int s, int q, int e) {
  if (s < 30) { const int d = s / 6 + 1, a = (s % 6) >> 1; return {Fq(q, a, s & 1), Fq(q, a + d, e)}; }
  if (s < 33) return {Fq(q, s - 30, e), Fq(q, s - 24, e)};
  if (s < 35) return {Fq(q, s - 33, e), Fq(q, s - 33, e)};
  if (s == 35) return {Fq(q, e, 0), Fq(q, e, 1)};
  if (s == 36) return {Fq(q, 2, 0), Fq(q, 2, e)};
  if (s == 37) return e ? Mono{Fq(q, 2, 1), Fq(q, 2, 1)} : Mono{M_NONE, M_NONE};
  if (s < 44) return {24 + ((s - 38) & 1), Fq(q, (s - 38) >> 1, e)};
  if (s < 47) return {Fq(q, s - 44, e), M_ONE};
  if (q == 0) return {24, 24 + e};
  if (q == 1) return e ? Mono{25, 25} : Mono{M_NONE, M_NONE};
  if (q == 2) return {24 + e, M_ONE};
  return e ? Mono{M_NONE, M_NONE} : Mono{M_ONE, M_ONE};
}
constexpr int QM_RS = 40;
constexpr int O_ZERO = 31 * QM_RS + 39, O_CONST = 30 * QM_RS + 39;
struct StaticTabs {
  uint32_t otab[48 * 8];
  uint32_t x1tab[48 * 8];
  uint16_t ltab[88 * 4];
  uint16_t loff[32 * 8];
};
constexpr StaticTabs make_tabs() {
  StaticTabs T{};
  for (int s = 0; s < 48; s++)
    for (int q = 0; q < 4; q++)
      for (int e = 0; e < 2; e++) {
        const Mono m = g0_mono(s, q, e);
        const bool none = m.f1 == M_NONE, cs = m.f1 == M_ONE, lin = m.f2 == M_ONE;
        const uint32_t o1 = none ? O_ZERO : cs ? O_CONST : m.f1 * QM_RS + (lin ? 26 : m.f2);
        const uint32_t o2 = (none || cs || lin || m.f1 == m.f2) ? O_ZERO : m.f2 * QM_RS + m.f1;
        T.otab[s * 8 + q * 2 + e] = o1 | (o2 << 16);
        const bool qd = m.f1 < NF && m.f2 < NF;
        const uint32_t y1 = qd ? m.f1 * NF + m.f2 : 0xffffu;
        const uint32_t y2 = (qd && m.f1 != m.f2) ? m.f2 * NF + m.f1 : 0xffffu;
        T.x1tab[s * 8 + q * 2 + e] = y1 | (y2 << 16);
      }
  for (int s = 0; s < 88; s++)
    for (int q = 0; q < 4; q++) {
      uint16_t v = 0;
      if (s < 85) {
        const bool ex = s >= 78;
        const int a = s / 13, k = s - 78;
        const int tt = ex ? ((k < 3) ? k : (k < 6 ? k + 3 : 12)) : s % 13;
        const int in = ex ? 24 + (q >> 1) : 8 * (a >> 1) + 2 * q + (a & 1);
        const bool valid = !(ex && tt == 12 && (q & 1));
        const int f0 = Fq(q, tt, 0);
        v = (uint16_t)((f0 >> 1) | ((f0 & 1) << 4) | ((valid ? 1 : 0) << 5) | (in << 6));
      }
      T.ltab[s * 4 + q] = v;
    }
  for (int ln = 0; ln < 32; ln++)
    for (int k = 0; k < 8; k++) {
      const int m = ln >> 3, r = ln & 7;
      const int tt = (k < 6) ? 2 * k + (m >> 1) : 12;
      T.loff[ln * 8 + k] = (uint16_t)(2 * Fq(r >> 1, tt, r & 1));
    }
  return T;
}
static_assert(sizeof(StaticTabs) == 4288, "tabs");
__device__ __align__(128) const StaticTabs g_tabs = make_tabs();

constexpr int SETUP_WARPS = 7;
constexpr int WL_BYTES = NF * NF * NF * 2;
static inline uint2 make_role(int cta) {
  int kind = 5, grp = 0, j = 0, off = 0, bytes = 0;
  const int c = cta, SL = NF * NF * 2;
  if (c < 56) { kind = 1 + c / 28; grp = (c % 28) / 7; j = c % 7; off = kind * WL_BYTES + grp * 8 * SL; bytes = (grp < 3 ? 8 : 2) * SL; }
  else if (c < 80) { kind = 0; grp = (c - 56) / 8; j = (c - 56) % 8; off = 3 * WL_BYTES + grp * 8 * SL; bytes = 8 * SL; }
  else if (c < 83) { kind = 0; grp = 3; j = c - 80; off = 3 * WL_BYTES + 24 * SL; bytes = 2 * SL; }
  else if (c < 95) { kind = 3; grp = (c - 83) / 4; j = (c - 83) % 4; off = grp * 8 * SL; bytes = 8 * SL; }
  const int delta = off & 127;
  uint2 r;
  r.x = (uint32_t)(off - delta) | ((uint32_t)kind << 24);
  r.y = (uint32_t)(bytes + delta) | ((uint32_t)delta << 16) | ((uint32_t)grp << 24) | ((uint32_t)j << 28);
  return r;
}

__device__ __forceinline__ uint32_t layer_row(int li, int grp, int r, int lane, const unsigned char* raw, const StaticTabs* T,
                                              uint32_t bar, uint32_t tbar, const bf16* __restrict__ wout, uint32_t* img32) {
  const int ks = li ? r : 13 * grp + (r >> 2), ng = li ? grp : (r & 3);
  if (ks >= 43 || (!li && grp < 3 && r >= 52)) return 0;
  const uint32_t* w32 = reinterpret_cast<const uint32_t*>(raw);
  const int n8 = lane >> 2, q = lane & 3;
  const int o = (ng < 3) ? ng * 8 + n8 : 24 + (n8 >> 2);
  const bool vo = (ng < 3) || !(n8 & 1);
  const int ob = li ? (o - 8 * grp) * 338 : o * 13 - 8 * grp * 338;
  const int si = li ? 13 : 338;
  uint32_t bias = 0;
  if (vo && ks == 42 && li == 0 && q == 0) bias = (uint32_t)__ldg(reinterpret_cast<const unsigned short*>(wout) + 2 * NF + o);
  uint32_t* dst = img32 + G0_BYTES / 4 + li * (L_BYTES / 4) + (ks * 4 + ng) * 64 + lane;
  mbar_wait(tbar, 0);
  const uint32_t e0 = T->ltab[8 * ks + q], e1 = T->ltab[8 * ks + 4 + q];
  const bool v0 = vo && (e0 & 32), v1 = vo && (e1 & 32);
  const int s0 = v0 ? ob + (e0 >> 6) * si + (e0 & 15) : 0, s1 = v1 ? ob + (e1 >> 6) * si + (e1 & 15) : 0;
  TL(33);
  mbar_wait(bar, 0);
  TL(36);
  uint32_t w0 = w32[s0], w1 = w32[s1];
  w0 = (e0 & 16) ? __funnelshift_l(w0, w0, 16) : w0;
  w1 = (e1 & 16) ? __funnelshift_l(w1, w1, 16) : w1;
  w0 = v0 ? w0 : 0u;
  w1 = v1 ? w1 : bias;
  st_img(dst, w0); st_img(dst + 32, w1);
  const uint32_t chk = (ld_back(dst) ^ w0) | (ld_back(dst + 32) ^ w1);
  WRITER_FENCE();
  return chk;
}
__device__ __forceinline__ float x1_val(const unsigned short* wh, uint32_t e) {
  const uint32_t a = e & 0xffff, b = e >> 16;
  const uint32_t x = wh[a == 0xffff ? 0 : a], y = wh[b == 0xffff ? 0 : b];
  return (a == 0xffff ? 0.f : __uint_as_float(x << 16)) + (b == 0xffff ? 0.f : __uint_as_float(y << 16));
}
__device__ __forceinline__ uint32_t x1_row(int ng, int ks, int lane, const unsigned char* raw, const StaticTabs* T, uint32_t bar, uint32_t tbar, uint32_t* img32) {
  if (ks >= 24) return 0;
  const int n8 = lane >> 2, q = lane & 3;
  const unsigned short* wh = reinterpret_cast<const unsigned short*>(raw) + n8 * (NF * NF);
  uint32_t* dst = img32 + ks * (G0_SLAB / 4) + ng * 64 + lane;
  mbar_wait(tbar, 0);
  const uint2 ea = *reinterpret_cast<const uint2*>(&T->x1tab[16 * ks + 2 * q]), eb = *reinterpret_cast<const uint2*>(&T->x1tab[16 * ks + 8 + 2 * q]);
  mbar_wait(bar, 0);
  const uint32_t w0 = pack_bf16(x1_val(wh, ea.x), x1_val(wh, ea.y)), w1 = pack_bf16(x1_val(wh, eb.x), x1_val(wh, eb.y));
  st_img(dst, w0); st_img(dst + 32, w1);
  const uint32_t chk = (ld_back(dst) ^ w0) | (ld_back(dst + 32) ^ w1);
  WRITER_FENCE();
  return chk;
}

constexpr int NHELP = 4;
constexpr int H_MS = 32 * QM_RS + 4;
constexpr int H_W5 = 0, H_W4 = 35328, H_W0 = 70656, H_TAB = 73472, H_B = 77824, H_M = 82944, H_XE = H_M + 8 * H_MS * 4, H_BAR = H_XE + 1536;
__device__ __forceinline__ int wf_off(int b, int h) { return (b >> 3) * 512 + (h >> 3) * 128 + (b & 7) * 16 + (h & 7) * 2; }
__device__ __forceinline__ void helper_role(int hk, const Params& P, unsigned char* smem, uint32_t sb) {
  const int t = threadIdx.x, warp = __shfl_sync(0xffffffffu, t >> 5, 0), lane = t & 31;
  const uint32_t d5bar = sb + H_BAR, d4bar = sb + H_BAR + 8, tbar = sb + H_BAR + 16;
  const unsigned char* wsb = reinterpret_cast<const unsigned char*>(P.ws);
  unsigned char* WB = smem + H_B;
  float* M = reinterpret_cast<float*>(smem + H_M);
  constexpr uint32_t W5B = WL_BYTES + ((5 * WL_BYTES) & 127), W4B = WL_BYTES + ((4 * WL_BYTES) & 127);
  if (warp < 3 && elect_one()) {
    mbar_init(sb + H_BAR + 8 * warp, 1);
    asm volatile("fence.mbarrier_init.release.cluster;" ::: "memory");
    if (warp == 0) {
      mbar_expect_tx(d5bar, W5B);
#pragma unroll
      for (int c = 0; c < 5; c++)
        bulk_g2s(sb + H_W5 + c * 8192, wsb + ((5 * WL_BYTES) & ~127) + c * 8192, c < 4 ? 8192u : W5B - 4 * 8192, d5bar);
    }
  }
  reinterpret_cast<uint32_t*>(WB)[t] = 0;
  __syncthreads();
  if (warp >= 5 && warp < 12 && elect_one()) {
    if (warp < 10) {
      const int c = warp - 5;
      if (c == 0) mbar_expect_tx(d4bar, W4B + (hk == 3 ? 2768 : 0));
      bulk_g2s(sb + H_W4 + c * 8192, wsb + ((4 * WL_BYTES) & ~127) + c * 8192, c < 4 ? 8192u : W4B - 4 * 8192, d4bar);
    } else if (warp == 10) {
      mbar_expect_tx(tbar, sizeof(StaticTabs));
      bulk_g2s(sb + H_TAB, P.tabs, sizeof(StaticTabs), tbar);
    } else if (hk == 3) {
      bulk_g2s(sb + H_W0, wsb + ((24 * NF * NF * 2) & ~127), 2768, d4bar);
    }
  }
  const unsigned short* wo16 = reinterpret_cast<const unsigned short*>(P.wout);
  uint32_t c5[13];
#pragma unroll
  for (int k = 0; k < 13; k++) c5[k] = __ldg(reinterpret_cast<const uint32_t*>(P.wout + 5 * NF) + k);
  unsigned short wv = 0;
  const int io0 = (hk < 3) ? 8 * hk : 24;
  if (t >= 352 && t < 352 + NF) wv = __ldg(wo16 + 4 * NF + t - 352);
  else if (t >= 384 && t < 392 && io0 + t - 384 < NF) wv = __ldg(wo16 + 3 * NF + io0 + t - 384);
  const StaticTabs* T = reinterpret_cast<const StaticTabs*>(smem + H_TAB);
  const int n8 = lane >> 2, q = lane & 3, g = n8;
  const int fil = (hk < 3) ? n8 : (n8 >> 2);
  const bool fx1 = (hk == 3) && !(n8 & 1);
  uint32_t* dst = reinterpret_cast<uint32_t*>(P.img) + (warp >> 1) * (G0_SLAB / 4) + (warp & 1) * 32 + (3 + hk) * 64 + lane;
  if (t >= 352 && t < 352 + NF) *reinterpret_cast<unsigned short*>(WB + wf_off(26, t - 352)) = wv;
  if (t >= 384 && t < 392) { M[(t - 384) * H_MS + O_ZERO] = 0.f; M[(t - 384) * H_MS + O_CONST] = __uint_as_float((uint32_t)wv << 16); }
  mbar_wait(d5bar, 0);
  if (t < 338) {
    const uint32_t* w5 = reinterpret_cast<const uint32_t*>(smem + H_W5 + ((5 * WL_BYTES) & 127)) + t;
    float s0 = 0.f, s1 = 0.f, s2 = 0.f, s3 = 0.f;
#pragma unroll
    for (int k = 0; k < 13; k++) {
      const uint32_t wa = w5[(2 * k) * 338], wb = w5[(2 * k + 1) * 338];
      const float ca = bflo(c5[k]), cb = bfhi(c5[k]);
      s0 = fmaf(ca, bflo(wa), s0); s1 = fmaf(ca, bfhi(wa), s1);
      s2 = fmaf(cb, bflo(wb), s2); s3 = fmaf(cb, bfhi(wb), s3);
    }
    const int h = (t * 79) >> 10, tp = t - 13 * h;
    *reinterpret_cast<bf16*>(WB + wf_off(2 * tp, h)) = __float2bfloat16(s0 + s2);
    *reinterpret_cast<bf16*>(WB + wf_off(2 * tp + 1, h)) = __float2bfloat16(s1 + s3);
  }
  fence_proxy_async();
  mbar_wait(tbar, 0);
  uint2 fot[3];
#pragma unroll
  for (int r = 0; r < 3; r++) fot[r] = *reinterpret_cast<const uint2*>(&T->otab[(warp + 16 * r) * 8 + q * 2]);
  mbar_wait(d4bar, 0);
  const int wgi = warp >> 2, il = 2 * wgi + ((warp >> 1) & 1), mt = warp & 1;
  const bool mma_wg = (hk < 3) || (wgi == 0);
  uint32_t a[2][4];
  if (mma_wg) {
    const unsigned short* A = reinterpret_cast<const unsigned short*>(smem + H_W4 + ((4 * WL_BYTES) & 127)) + (io0 + il) * NF + mt * 16 + g;
#pragma unroll
    for (int kk = 0; kk < 2; kk++) {
#pragma unroll
      for (int jj = 0; jj < 4; jj++) {
        const int k = kk * 16 + 2 * q + (jj >> 1) * 8, mo = (jj & 1) * 8;
        const int kc = (k < NF) ? k : 0;
        const uint32_t lo = A[kc * (NF * NF) + mo], hi = A[(kc + 1) * (NF * NF) + mo];
        a[kk][jj] = (k < NF) ? (lo | (hi << 16)) : 0u;
      }
    }
  }
  if (hk == 3) {
    const int u0 = (warp >= 4) ? t - 128 : -1;
    if (u0 >= 0) {
      const int sl = u0 >> 3, xl = (u0 >> 2) & 1, xq = u0 & 3;
      const uint2 xt = *reinterpret_cast<const uint2*>(&T->x1tab[sl * 8 + xq * 2]);
      const unsigned short* wh = reinterpret_cast<const unsigned short*>(smem + H_W0 + ((24 * NF * NF * 2) & 127)) + xl * (NF * NF);
      reinterpret_cast<uint32_t*>(smem + H_XE)[u0] = pack_bf16(x1_val(wh, xt.x), x1_val(wh, xt.y));
    }
  }
  __syncthreads();
  if (mma_wg) {
    float c[16];
    wg_fence();
    wgmma_rs_n32(c, a[0][0], a[0][1], a[0][2], a[0][3], make_desc(H_B, 128, 512, 0), 0);
    wgmma_rs_n32(c, a[1][0], a[1][1], a[1][2], a[1][3], make_desc(H_B + 256, 128, 512, 0), 1);
    wg_commit();
    wg_wait<0>();
    reg_fence(c);
    float* Mi = M + il * H_MS;
#pragma unroll
    for (int n = 0; n < 4; n++) {
      *reinterpret_cast<float2*>(&Mi[(mt * 16 + g) * QM_RS + n * 8 + 2 * q]) = make_float2(c[4 * n], c[4 * n + 1]);
      *reinterpret_cast<float2*>(&Mi[(mt * 16 + g + 8) * QM_RS + n * 8 + 2 * q]) = make_float2(c[4 * n + 2], c[4 * n + 3]);
    }
  }
  __syncthreads();
  uint32_t val[3], chk = 0;
#pragma unroll
  for (int r = 0; r < 3; r++) {
    const float* Mf = M + fil * H_MS;
    const float v0 = Mf[fot[r].x & 0xffff] + Mf[fot[r].x >> 16], v1 = Mf[fot[r].y & 0xffff] + Mf[fot[r].y >> 16];
    const uint32_t xe = reinterpret_cast<const uint32_t*>(smem + H_XE)[(warp + 16 * r) * 8 + (n8 >> 2) * 4 + q];
    val[r] = fx1 ? xe : pack_bf16(v0, v1);
    st_img(dst + r * 8 * (G0_SLAB / 4), val[r]);
  }
#pragma unroll
  for (int r = 0; r < 3; r++) chk |= ld_back(dst + r * 8 * (G0_SLAB / 4)) ^ val[r];
  WRITER_FENCE();
  if (__any_sync(0xffffffffu, chk != 0)) __trap();
  __syncthreads();
  if (t == 0) asm volatile("red.relaxed.gpu.global.add.u32 [%0], 1;" ::"l"(P.ctr + 32) : "memory");
}

template <int S>
__device__ __forceinline__ uint32_t l_prod(const uint32_t (&vp)[4], const uint32_t (&X)[13]) {
  if constexpr (S < 78) {
    constexpr int a = S / 13, t = S % 13;
    return (a & 1) ? mul_hi(vp[a >> 1], X[t]) : mul_lo(vp[a >> 1], X[t]);
  } else if constexpr (S < 85) {
    constexpr int k = S - 78;
    constexpr int t = (k < 3) ? k : (k < 6 ? k + 3 : 12);
    return mul_lo(vp[3], X[t]);
  } else {
    return 0x00003F80u;
  }
}
template <int S>
__device__ __forceinline__ uint32_t g0_prod(const uint32_t (&X)[13], uint32_t selU, uint32_t selV) {
  if constexpr (S < 30) {
    constexpr int d = S / 6 + 1, a = (S % 6) >> 1;
    return (S & 1) ? mul_hi(X[a], X[a + d]) : mul_lo(X[a], X[a + d]);
  } else if constexpr (S < 33) {
    return mul_ew(X[S - 30], X[S - 24]);
  } else if constexpr (S < 35) {
    return mul_ew(X[S - 33], X[S - 33]);
  } else if constexpr (S == 35) {
    return mul_ew(__byte_perm(X[0], X[1], 0x5410), __byte_perm(X[0], X[1], 0x7632));
  } else if constexpr (S == 36) {
    return mul_lo(X[2], X[2]);
  } else if constexpr (S == 37) {
    return mul_hi(X[2], X[2]);
  } else if constexpr (S < 44) {
    constexpr int a = (S - 38) >> 1;
    return ((S - 38) & 1) ? mul_hi(X[12], X[a]) : mul_lo(X[12], X[a]);
  } else if constexpr (S < 47) {
    return X[S - 44];
  } else {
    return mul_ew(__byte_perm(X[12], 0x3F803F80u, selU), __byte_perm(X[12], 0x3F803F80u, selV));
  }
}

constexpr int NBK = 4;

template <int KS, int KE>
__device__ __forceinline__ void l_fill(uint32_t (*A)[4], const uint32_t (&vp)[2][4], const uint32_t (&X)[2][13]) {
  A[0][0] = l_prod<2 * KS>(vp[0], X[0]);
  A[0][1] = l_prod<2 * KS>(vp[1], X[1]);
  A[0][2] = l_prod<2 * KS + 1>(vp[0], X[0]);
  A[0][3] = l_prod<2 * KS + 1>(vp[1], X[1]);
  if constexpr (KS + 1 < KE) l_fill<KS + 1, KE>(A + 1, vp, X);
}
template <int KS, int OFF>
__device__ __forceinline__ void layer_rec(float (&d)[16], const uint32_t (&vp)[2][4], const uint32_t (&X)[2][13], uint64_t dk) {
  constexpr int KE = (KS + NBK < L_KS) ? KS + NBK : L_KS;
  uint32_t A[NBK][4];
  l_fill<KS, KE>(A, vp, X);
  wg_fence();
#pragma unroll
  for (int k = 0; k < KE - KS; k++)
    wgmma_rs_n32(d, A[k][0], A[k][1], A[k][2], A[k][3], dk + (uint64_t)((OFF + (KS + k) * L_SLAB) >> 4), (KS + k) > 0);
  wg_commit();
  if constexpr (KE < L_KS) {
    wg_wait<1>();
    layer_rec<KE, OFF>(d, vp, X, dk);
  }
}
template <int OFF, int NK>
__device__ __forceinline__ void layer_first(float (&d)[16], const uint32_t (&vp)[2][4], const uint32_t (&X)[2][13], uint64_t dk) {
  uint32_t A[NK][4];
  l_fill<0, NK>(A, vp, X);
  wg_fence();
#pragma unroll
  for (int k = 0; k < NK; k++) wgmma_rs_n32(d, A[k][0], A[k][1], A[k][2], A[k][3], dk + (uint64_t)((OFF + k * L_SLAB) >> 4), k > 0);
  wg_commit();
}
template <int KS, int KE>
__device__ __forceinline__ void g0_fill(uint32_t (*A)[4], const uint32_t (&X)[2][13], uint32_t selU, uint32_t selV) {
  A[0][0] = g0_prod<2 * KS>(X[0], selU, selV);
  A[0][1] = g0_prod<2 * KS>(X[1], selU, selV);
  A[0][2] = g0_prod<2 * KS + 1>(X[0], selU, selV);
  A[0][3] = g0_prod<2 * KS + 1>(X[1], selU, selV);
  if constexpr (KS + 1 < KE) g0_fill<KS + 1, KE>(A + 1, X, selU, selV);
}
template <int B0>
__device__ __forceinline__ void g0_rec(float (&d)[28], const uint32_t (&X)[2][13], uint32_t selU, uint32_t selV, uint64_t dk, uint32_t bar2, bool first) {
  constexpr int KS = B0 * NBK;
  if constexpr (KS == 8) { if (first) mbar_wait(bar2, 0); }
  if constexpr (KS == 16) { if (first) mbar_wait(bar2 + 8, 0); }
  constexpr int KE = (KS + NBK < G0_KS) ? KS + NBK : G0_KS;
  uint32_t A[NBK][4];
  g0_fill<KS, KE>(A, X, selU, selV);
  wg_fence();
#pragma unroll
  for (int k = 0; k < KE - KS; k++)
    wgmma_rs_n56(d, A[k][0], A[k][1], A[k][2], A[k][3], dk + (uint64_t)((OFF_G0 + (KS + k) * G0_SLAB) >> 4), (KS + k) > 0);
  wg_commit();
  if constexpr (KE < G0_KS) {
    wg_wait<1>();
    g0_rec<B0 + 1>(d, X, selU, selV, dk, bar2, first);
  }
}

__device__ __forceinline__ void ldsm_x4_t(uint32_t addr, uint32_t& r0, uint32_t& r1, uint32_t& r2, uint32_t& r3) {
  asm volatile("ldmatrix.sync.aligned.m8n8.x4.trans.shared.b16 {%0,%1,%2,%3}, [%4];"
               : "=r"(r0), "=r"(r1), "=r"(r2), "=r"(r3) : "r"(addr) : "memory");
}
__device__ __forceinline__ void ldsm_x2_t(uint32_t addr, uint32_t& r0, uint32_t& r1) {
  asm volatile("ldmatrix.sync.aligned.m8n8.x2.trans.shared.b16 {%0,%1}, [%2];" : "=r"(r0), "=r"(r1) : "r"(addr) : "memory");
}
__device__ __forceinline__ float tanh_fast(float x) { float y; asm("tanh.approx.f32 %0, %1;" : "=f"(y) : "f"(x)); return y; }

__device__ __forceinline__ uint32_t gelu2_pair(float lo, float hi, uint32_t bias) {
  uint32_t x = pack_bf16(lo, hi), t, u;
  asm("add.rn.bf16x2 %0, %0, %1;" : "+r"(x) : "r"(bias));
  asm("mul.rn.bf16x2 %0, %1, %1;" : "=r"(t) : "r"(x));
  asm("fma.rn.bf16x2 %0, %0, %1, %2;" : "+r"(t) : "r"(0x3D123D12u), "r"(0x3F4C3F4Cu));
  asm("mul.rn.bf16x2 %0, %1, %2;" : "=r"(u) : "r"(x), "r"(t));
  asm("tanh.approx.bf16x2 %0, %0;" : "+r"(u));
  asm("fma.rn.bf16x2 %0, %1, %0, %1;" : "+r"(u) : "r"(x));
  return u;
}

__device__ __forceinline__ void ldsm_x4(uint32_t addr, uint32_t (&r)[4]) {
  asm volatile("ldmatrix.sync.aligned.m8n8.x4.shared.b16 {%0,%1,%2,%3}, [%4];"
               : "=r"(r[0]), "=r"(r[1]), "=r"(r[2]), "=r"(r[3]) : "r"(addr) : "memory");
}
__device__ __forceinline__ uint32_t lds_u16(uint32_t addr) {
  unsigned short v;
  asm volatile("ld.shared.u16 %0, [%1];" : "=h"(v) : "r"(addr) : "memory");
  return v;
}
__device__ __forceinline__ uint32_t lds_u32(uint32_t addr) {
  uint32_t v;
  asm volatile("ld.shared.u32 %0, [%1];" : "=r"(v) : "r"(addr) : "memory");
  return v;
}

__global__ void __launch_bounds__(512, 1)
main_kernel(const __grid_constant__ Params P, const __grid_constant__ TmaMaps tms) {
  extern __shared__ __align__(1024) unsigned char smem[];
  const uint32_t sb = smem_u32(smem);
  const int tid = threadIdx.x, warp = __shfl_sync(0xffffffffu, tid >> 5, 0), lane = tid & 31;
  if (blockIdx.x < NHELP) {
    helper_role(blockIdx.x, P, smem, sb);
    return;
  }
  const int cta = blockIdx.x - NHELP, nq = cta & 3, grp = cta >> 2;
  const uint2 role = P.role[cta];
  const uint32_t bar0 = sb + OFF_BAR;
  auto BAR = [&](int i) { return bar0 + 8 * i; };
  const int wg = warp >> 2, w4 = warp & 3, g = lane >> 2, q = lane & 3;
  const uint64_t dk = P.dk;
  const long long tl_c0 = TL_START();
  TL_INIT();
  TL_PUT0(tl_c0);

  if (tid < 256) {
    const unsigned char* isrc = reinterpret_cast<const unsigned char*>(P.idx + grp * 128 * NF);
#pragma unroll
    for (int k = 0; k < 4; k++) {
      const int c = tid + 256 * k;
      if (c < 832) cp_async16(sb + OFF_IDX + c * 16, isrc + c * 16);
    }
    asm volatile("cp.async.commit_group;" ::: "memory");
#pragma unroll
    for (int k = 0; k < 8; k++) {
      const int c = tid + 256 * k;
      if (c < 2000) cp_async16(sb + OFF_TAB + ((c ^ ((c >> 3) & 1)) << 4), reinterpret_cast<const unsigned char*>(P.table) + c * 16);
    }
    asm volatile("cp.async.commit_group;" ::: "memory");
  }
  if (elect_one()) {
    mbar_init(BAR(warp), (warp == BAR_W1FREE || warp == BAR_W1DONE) ? 2 : (warp == BAR_IMG) ? 224 : 1);
    if (warp < NBAR - 16)
      mbar_init(BAR(16 + warp), (16 + warp == BAR_X0) ? 256 : (16 + warp == BAR_SETUP) ? SETUP_WARPS : (16 + warp == BAR_TABS) ? 224 : (16 + warp >= BAR_G0B) ? 224 : 1);
    asm volatile("fence.mbarrier_init.release.cluster;" ::: "memory");
  }
  __syncthreads();
  TL(26);

  if (warp == 15) {
    if (elect_one()) {
      mbar_expect_tx(BAR(BAR_STAB), sizeof(StaticTabs));
      bulk_g2s(sb + OFF_STAB, P.tabs, sizeof(StaticTabs), BAR(BAR_STAB));
      if ((sb & 0x3FFFF) != SMEM_BASE) __trap();
      const CUtensorMap* tm0 = &tms.m[nq];
      asm volatile("prefetch.tensormap [%0];" ::"l"(tm0) : "memory");
#pragma unroll
      for (int st = 0; st < W1_STAGES; st++) {
        if (st == 1 && (role.x >> 24) < 5) mbar_wait(BAR(BAR_Q), 0);
        mbar_expect_tx(BAR(BAR_W1FULL + st), W1_STAGE_BYTES);
        tma_2d(sb + w1_off(st), tm0, 0, st * 64, BAR(BAR_W1FULL + st));
        tma_2d(sb + w1_off(st) + 8192, tm0, 64, st * 64, BAR(BAR_W1FULL + st));
      }
      TLP(22);
      mbar_wait(BAR(BAR_EPOCH), 0);
      TLP(23);
      const unsigned epoch_p = lds_u32(sb + OFF_EPOCH);
      auto wait_ctr = [&](const unsigned* ctr, unsigned target) {
        unsigned v;
        uint32_t it = 0;
#pragma unroll 1
        do {
          asm volatile("ld.relaxed.gpu.global.u32 %0, [%1];" : "=r"(v) : "l"(ctr) : "memory");
          if (++it > (1u << 22)) __trap();
        } while ((int)(v - target) < 0);
      };
      wait_ctr(P.ctr + 32, epoch_p << 4);
      mbar_wait(BAR(BAR_X0), 0);
      TLP(24);
      mbar_arrive(BAR(BAR_G0OK));
      wait_ctr(P.ctr, epoch_p << 7);
      mbar_wait(BAR(BAR_W1FREE), 0);
      mbar_expect_tx(BAR(BAR_IMG + 2), L_BYTES);
#pragma unroll
      for (int i = 0; i < 4; i++)
        bulk_g2s(sb + OFF_LB + i * (L_BYTES / 4), P.img + G0_BYTES + L_BYTES + i * (L_BYTES / 4), L_BYTES / 4, BAR(BAR_IMG + 2));
      mbar_wait(BAR(BAR_W1DONE), 0);
      mbar_expect_tx(BAR(BAR_IMG + 1), L_BYTES);
      mbar_expect_tx(BAR(BAR_IMG + 3), L_BYTES);
#pragma unroll
      for (int i = 0; i < 2; i++)
        bulk_g2s(sb + OFF_LA + i * (L_BYTES / 2), P.img + G0_BYTES + i * (L_BYTES / 2), L_BYTES / 2, BAR(BAR_IMG + 1));
#pragma unroll
      for (int i = 0; i < 2; i++)
        bulk_g2s(sb + OFF_LC + i * (L_BYTES / 2), P.img + G0_BYTES + 2 * L_BYTES + i * (L_BYTES / 2), L_BYTES / 2, BAR(BAR_IMG + 3));
      TLP(25);
    }
    __syncwarp();
    mbar_wait(BAR(BAR_X0), 0);
    mbar_wait(BAR(BAR_TABS), 0);
  } else if (wg < 2) {
    asm volatile("cp.async.wait_group 1;" ::: "memory");
    named_bar(1, 256);
#pragma unroll
    for (int k = 0; k < 7; k++) {
      const int p = tid + 256 * k;
      if (p < 64 * NF) {
        const uint2 v = reinterpret_cast<const uint2*>(smem + OFF_IDX)[p];
        const uint32_t o0 = v.x * 32 + ((v.x >> 2) & 1) * 16, o1 = v.y * 32 + ((v.y >> 2) & 1) * 16;
        reinterpret_cast<uint32_t*>(smem + OFF_XOFF)[p] = o0 | (o1 << 16);
      }
    }
    TL(1);
    asm volatile("cp.async.wait_all;" ::: "memory");
    mbar_arrive(BAR(BAR_X0));
    mbar_wait(BAR(BAR_X0), 0);
    TL(3);
    float acc[56];
    {
      const uint32_t xo = sb + OFF_XOFF + (wg * 64 + w4 * 16 + (lane & 15)) * 52;
      const uint32_t tb = sb + OFF_TAB, hx = (lane >> 4) << 4;
      const uint64_t db0 = P.dmn;
      uint32_t A[3][2][4];
#pragma unroll
      for (int pr = 0; pr < 2; pr++) {
        const uint32_t oa = lds_u32(xo + 4 * pr);
        ldsm_x4(tb + ((oa & 0xffff) ^ hx), A[pr][0]); ldsm_x4(tb + ((oa >> 16) ^ hx), A[pr][1]);
      }
#pragma unroll
      for (int pr = 0; pr < 13; pr++) {
        const int st = pr >> 1;
        uint32_t oa = 0;
        if (pr + 2 < 13) oa = lds_u32(xo + 4 * (pr + 2));
        if (!(pr & 1)) mbar_wait(BAR(BAR_W1FULL + st), 0);
        if (pr == 0) TL(28); if (pr == 6) TL(29);
        const uint64_t db = db0 + (uint64_t)((w1_off(st) + (pr & 1) * 4096) >> 4);
        wg_fence();
        wgmma_rs_n112_tb(acc, A[pr % 3][0][0], A[pr % 3][0][1], A[pr % 3][0][2], A[pr % 3][0][3], db, pr > 0);
        wgmma_rs_n112_tb(acc, A[pr % 3][1][0], A[pr % 3][1][1], A[pr % 3][1][2], A[pr % 3][1][3], db + (2048 >> 4), 1);
        wg_commit();
        wg_wait<1>();
        if (pr == 4 && (tid & 127) == 0) mbar_arrive(BAR(BAR_W1FREE));
        if (pr + 2 < 13) { ldsm_x4(tb + ((oa & 0xffff) ^ hx), A[(pr + 2) % 3][0]); ldsm_x4(tb + ((oa >> 16) ^ hx), A[(pr + 2) % 3][1]); }
      }
      wg_wait<0>();
      reg_fence(acc);
      if ((tid & 127) == 0) mbar_arrive(BAR(BAR_W1DONE));
    }
    TL(4);
    float dot[4];
    {
      mbar_wait(BAR(BAR_TABS), 0);
      uint32_t bb[16];
      const uint4* bp = reinterpret_cast<const uint4*>(smem + OFF_BW + q * 64);
#pragma unroll
      for (int i = 0; i < 4; i++) { const uint4 v = bp[i]; bb[4 * i] = v.x; bb[4 * i + 1] = v.y; bb[4 * i + 2] = v.z; bb[4 * i + 3] = v.w; }
      uint32_t H[14][2];
#pragma unroll
      for (int c = 0; c < 14; c++) {
        H[c][0] = gelu2_pair(acc[4 * c], acc[4 * c + 1], bb[c]);
        H[c][1] = gelu2_pair(acc[4 * c + 2], acc[4 * c + 3], bb[c]);
      }
      wg_fence();
#pragma unroll
      for (int j = 0; j < 7; j++)
        wgmma_rs_n8(dot, H[2 * j][0], H[2 * j][1], H[2 * j + 1][0], H[2 * j + 1][1], dk + (uint64_t)((OFF_W2 + j * 256) >> 4), j > 0);
      wg_commit();
      wg_wait<0>();
      reg_fence(dot);
    }
    __syncwarp();
    mbar_wait(BAR(BAR_EPOCH), 0);
    if (q == 0) {
      const unsigned epoch = lds_u32(sb + OFF_EPOCH);
#pragma unroll
      for (int r = 0; r < 2; r++) {
        const int row = wg * 64 + w4 * 16 + g + 8 * r;
        const unsigned long long pk = ((unsigned long long)epoch << 32) | (unsigned long long)__float_as_uint(dot[2 * r]);
        asm volatile("st.relaxed.gpu.global.u64 [%0], %1;" ::"l"(P.part + cta * 128 + row), "l"(pk) : "memory");
      }
    }
    __syncwarp();
  } else {
    const int t = tid - 256;
    const bool is_arr = (t == 192);
    unsigned ctr0 = 0;
    if (is_arr) asm volatile("ld.relaxed.gpu.global.u32 %0, [%1];" : "=r"(ctr0) : "l"(P.ctr) : "memory");
    {
      const int kind = role.x >> 24, w = warp - 8, rgrp = (role.y >> 24) & 15, rj = role.y >> 28;
      const unsigned char* wsb = reinterpret_cast<const unsigned char*>(P.ws);
      if (kind < 5 && elect_one()) {
        const uint32_t bytes = role.y & 0xffff;
        const uint32_t o = w * 8192;
        if (w == 0) mbar_expect_tx(BAR(BAR_Q), bytes);
        if (o < bytes) bulk_g2s(sb + OFF_G0 + o, wsb + (role.x & 0xffffff) + o, min(bytes - o, 8192u), BAR(BAR_Q));
      }
      TL(40);
      __syncwarp();
      const StaticTabs* T = reinterpret_cast<const StaticTabs*>(smem + OFF_STAB);
      uint32_t* img32 = reinterpret_cast<uint32_t*>(P.img);
      const unsigned char* raw = smem + OFF_G0 + ((role.y >> 16) & 127);
      uint32_t chk = 0;
      if (kind < 3) chk = layer_row(kind, rgrp, rj * SETUP_WARPS + w, lane, raw, T, BAR(BAR_Q), BAR(BAR_STAB), P.wout, img32);
      else if (kind == 3) chk = x1_row(rgrp, rj * SETUP_WARPS + w, lane, raw, T, BAR(BAR_Q), BAR(BAR_STAB), img32);
      if (__any_sync(0xffffffffu, chk != 0)) __trap();
      if (lane == 0) mbar_arrive(BAR(BAR_SETUP));
    }
    TL(1);
    if (is_arr) {
      asm volatile("" : "+r"(ctr0));
      *reinterpret_cast<volatile unsigned*>(smem + OFF_EPOCH) = (ctr0 >> 7) + 1;
      mbar_wait(BAR(BAR_SETUP), 0);
      TLA(30);
      if ((role.x >> 24) == 3) asm volatile("red.relaxed.gpu.global.add.u32 [%0], 1;" ::"l"(P.ctr + 32) : "memory");
      asm volatile("red.relaxed.gpu.global.add.u32 [%0], 1;" ::"l"(P.ctr) : "memory");
      mbar_arrive(BAR(BAR_EPOCH));
      TLA(31);
    }
    __syncwarp();
    {
      const int c0 = (nq >> 1) * 208 + (nq & 1) * 96, nw = (nq & 1) ? 112 : 96;
      if (t < 56) {
        const int n = 2 * t;
        const uint32_t v = (n < nw) ? __ldg(reinterpret_cast<const uint32_t*>(P.b1 + c0 + n)) : 0u;
        reinterpret_cast<uint32_t*>(smem + OFF_BW)[(t & 3) * 16 + (t >> 2)] = v;
      }
      if (t >= 64 && t < 64 + 112) {
        const int k = t - 64;
        const float w = (k < nw) ? 0.5f * bf2f(__ldg(P.w2 + c0 + k)) : 0.f;
        unsigned char* base = smem + OFF_W2 + (k >> 4) * 256 + ((k >> 3) & 1) * 128;
        *reinterpret_cast<bf16*>(base + (k & 7) * 2) = __float2bfloat16(w);
        if ((k & 7) == 0) {
#pragma unroll
          for (int r = 1; r < 8; r++) *reinterpret_cast<uint4*>(base + r * 16) = make_uint4(0, 0, 0, 0);
        }
      }
      fence_proxy_async();
    }
    if (t >= 128 && t < 192) {
      int u = t - 128, l = u >> 5, qq = (u >> 3) & 3, a = u & 7;
      float wtv = 0.f;
      if (a < 6) wtv = bf2f(__ldg(P.wout + l * NF + 8 * (a >> 1) + 2 * qq + (a & 1)));
      else if (a == 6 && !(qq & 1)) wtv = bf2f(__ldg(P.wout + l * NF + 24 + (qq >> 1)));
      reinterpret_cast<float*>(smem + OFF_WTAB)[u] = wtv;
    }
    mbar_arrive(BAR(BAR_TABS));
    TL(2);
    mbar_wait(BAR(BAR_X0), 0);
    mbar_wait(BAR(BAR_TABS), 0);
  }

  if (warp >= 8 && warp < 15) {
    mbar_wait(BAR(BAR_G0OK), 0);
    const int t2 = tid - 256;
#pragma unroll
    for (int part = 0; part < 3; part++) {
#pragma unroll
      for (int k = 0; k < 4; k++) {
        const int c = t2 + 224 * k;
        cp_async16(sb + OFF_G0 + part * (G0_BYTES / 3) + c * 16, P.img + part * (G0_BYTES / 3) + c * 16);
      }
      asm volatile("cp.async.commit_group;" ::: "memory");
    }
    asm volatile("cp.async.wait_group 2;" ::: "memory"); fence_proxy_async(); mbar_arrive(BAR(BAR_IMG + 0));
    asm volatile("cp.async.wait_group 1;" ::: "memory"); fence_proxy_async(); mbar_arrive(BAR(BAR_G0B));
    asm volatile("cp.async.wait_group 0;" ::: "memory"); fence_proxy_async(); mbar_arrive(BAR(BAR_G0B + 1));
  }
  TL(5);
  const uint32_t selU = (q == 0) ? 0x1010u : (q == 1) ? 0x3232u : (q == 2) ? 0x3210u : 0x7654u;
  const uint32_t selV = (q < 2) ? 0x3210u : 0x7654u;
  uint32_t bo_raw = __ldg(reinterpret_cast<const unsigned short*>(P.bout));
  mbar_wait(BAR(BAR_EPOCH), 0);
  mbar_wait(BAR(BAR_STAB), 0);
  const unsigned epoch = lds_u32(sb + OFF_EPOCH);

  uint32_t X[2][13];
  auto load_x = [&](int sl) {
    const uint4 o = *reinterpret_cast<const uint4*>(smem + OFF_LOFF + lane * 16);
    const uint32_t xo = sb + OFF_XOFF + sl * 52;
    const uint32_t tb = sb + OFF_TAB, hx = ((lane >> 3) & 1) << 4;
    const uint32_t a0 = lds_u16(xo + (o.x & 0xffff)), a1 = lds_u16(xo + (o.x >> 16));
    const uint32_t a2 = lds_u16(xo + (o.y & 0xffff)), a3 = lds_u16(xo + (o.y >> 16));
    const uint32_t a4 = lds_u16(xo + (o.z & 0xffff)), a5 = lds_u16(xo + (o.z >> 16));
    const uint32_t a6 = lds_u16(xo + (o.w & 0xffff));
    ldsm_x4_t(tb + (a0 ^ hx), X[0][0], X[1][0], X[0][1], X[1][1]);
    ldsm_x4_t(tb + (a1 ^ hx), X[0][2], X[1][2], X[0][3], X[1][3]);
    ldsm_x4_t(tb + (a2 ^ hx), X[0][4], X[1][4], X[0][5], X[1][5]);
    ldsm_x4_t(tb + (a3 ^ hx), X[0][6], X[1][6], X[0][7], X[1][7]);
    ldsm_x4_t(tb + (a4 ^ hx), X[0][8], X[1][8], X[0][9], X[1][9]);
    ldsm_x4_t(tb + (a5 ^ hx), X[0][10], X[1][10], X[0][11], X[1][11]);
    ldsm_x2_t(tb + (a6 ^ hx), X[0][12], X[1][12]);
  };
  load_x(nq * 32 + wg * 4 + w4);
#pragma unroll 1
  for (int it = 0; it < 2; it++) {
    const int sl = nq * 32 + (wg + 4 * it) * 4 + w4;
    float S = 0.f;
    uint32_t vx[2][4], vg[2][4];
    {
      float a0[28];
      if (it == 0) mbar_wait(BAR(BAR_IMG + 0), 0);
      if (it < 2) TL(6 + it * 8);
      g0_rec<0>(a0, X, selU, selV, dk, BAR(BAR_G0B), it == 0);
      wg_wait<0>();
      reg_fence(a0);
      const float4* wt = reinterpret_cast<const float4*>(smem + OFF_WTAB) + q * 2;
      float4 wa = wt[0], wb = wt[1];
#pragma unroll
      for (int r = 0; r < 2; r++) {
        S = fmaf(wa.x, a0[0 + 2 * r], S); S = fmaf(wa.y, a0[1 + 2 * r], S);
        S = fmaf(wa.z, a0[4 + 2 * r], S); S = fmaf(wa.w, a0[5 + 2 * r], S);
        S = fmaf(wb.x, a0[8 + 2 * r], S); S = fmaf(wb.y, a0[9 + 2 * r], S);
        S = fmaf(wb.z, a0[24 + 2 * r], S);
#pragma unroll
        for (int c = 0; c < 3; c++) {
          vx[r][c] = pack_bf16(a0[4 * c + 2 * r], a0[4 * c + 2 * r + 1]);
          vg[r][c] = pack_bf16(a0[12 + 4 * c + 2 * r], a0[12 + 4 * c + 2 * r + 1]);
        }
        vx[r][3] = pack_bf16(a0[24 + 2 * r], 0.f);
        vg[r][3] = pack_bf16(a0[24 + 2 * r + 1], 0.f);
      }
    }
    float g3[16], xa[16];
    if (it < 2) TL(7 + it * 8);
    if (it == 0) {
      mbar_wait(BAR(BAR_IMG + 2), 0);
      mbar_wait(BAR(BAR_IMG + 1), 0);
      mbar_wait(BAR(BAR_IMG + 3), 0);
    }
    if (it < 2) TL(8 + it * 8);
    layer_rec<0, OFF_LB>(xa, vx, X, dk);
    if (it < 2) TL(9 + it * 8);
    wg_wait<1>();
    layer_first<OFF_LA, 3>(g3, vg, X, dk);
    wg_wait<1>();
    reg_fence(xa);
    {
      const float4* wt = reinterpret_cast<const float4*>(smem + OFF_WTAB) + 8 + q * 2;
      float4 wa = wt[0], wb = wt[1];
#pragma unroll
      for (int r = 0; r < 2; r++) {
        S = fmaf(wa.x, xa[0 + 2 * r], S); S = fmaf(wa.y, xa[1 + 2 * r], S);
        S = fmaf(wa.z, xa[4 + 2 * r], S); S = fmaf(wa.w, xa[5 + 2 * r], S);
        S = fmaf(wb.x, xa[8 + 2 * r], S); S = fmaf(wb.y, xa[9 + 2 * r], S);
        S = fmaf(wb.z, xa[12 + 2 * r], S);
#pragma unroll
        for (int c = 0; c < 3; c++) vx[r][c] = pack_bf16(xa[4 * c + 2 * r], xa[4 * c + 2 * r + 1]);
        vx[r][3] = pack_bf16(xa[12 + 2 * r], 0.f);
      }
    }
    layer_rec<3, OFF_LA>(g3, vg, X, dk);
    if (it < 2) TL(10 + it * 8);
    wg_wait<1>();
    const unsigned long long* pp = P.part + (grp * 4 + (lane & 3)) * 128 + sl;
    unsigned long long pk;
    asm volatile("ld.relaxed.gpu.global.u64 %0, [%1];" : "=l"(pk) : "l"(pp) : "memory");
    float xc[16];
    layer_rec<0, OFF_LC>(xc, vx, X, dk);
    if (it == 0) load_x(sl + 16);
    wg_wait<0>();
    reg_fence(xc);
    reg_fence(g3);
    {
      float Se = 0.f;
#pragma unroll
      for (int r = 0; r < 2; r++) {
#pragma unroll
        for (int c = 0; c < 3; c++) {
          S = fmaf(g3[4 * c + 2 * r], xc[4 * c + 2 * r], S);
          S = fmaf(g3[4 * c + 2 * r + 1], xc[4 * c + 2 * r + 1], S);
        }
        Se = fmaf(g3[12 + 2 * r], xc[12 + 2 * r], Se);
      }
      if (!(q & 1)) S += Se;
    }
#pragma unroll
    for (int o = 16; o > 0; o >>= 1) S += __shfl_xor_sync(0xffffffffu, S, o);
    if (it < 2) TL(12 + it * 8);
    {
      uint32_t spin = 0;
      while (lane < 4 && (unsigned)(pk >> 32) != epoch) {
        asm volatile("ld.relaxed.gpu.global.u64 %0, [%1];" : "=l"(pk) : "l"(pp) : "memory");
        if (++spin > (1u << 24)) __trap();
      }
      __syncwarp();
      float dv = __uint_as_float((unsigned)pk);
      float d01 = dv + __shfl_xor_sync(0xffffffffu, dv, 1);
      float dsum = d01 + __shfl_xor_sync(0xffffffffu, d01, 2);
      asm volatile("" : "+r"(bo_raw));
      if (lane == 0) P.out[grp * 128 + sl] = __float2bfloat16(S + dsum + __uint_as_float(bo_raw << 16));
    }
    __syncwarp();
    if (it < 2) TL(13 + it * 8);
  }
  TL_DUMP();
}

__global__ void __launch_bounds__(128) fallback_kernel(const int* __restrict__ idx, const bf16* __restrict__ table, const bf16* __restrict__ ws,
                                                       const bf16* __restrict__ wout, const bf16* __restrict__ w1, const bf16* __restrict__ b1,
                                                       const bf16* __restrict__ w2, const bf16* __restrict__ bout, bf16* __restrict__ out) {
  __shared__ float x0[416], xa[416], xb[416], red[128];
  const int b = blockIdx.x, t = threadIdx.x;
  for (int i = t; i < 416; i += 128) { x0[i] = bf2f(table[idx[b * NF + i / 16] * 16 + (i & 15)]); xa[i] = x0[i]; }
  __syncthreads();
  float acc = 0.f;
  float* cur = xa;
  float* nxt = xb;
  for (int l = 0; l < 6; l++) {
    for (int o = t; o < 416; o += 128) {
      const int h = o >> 4, d = o & 15;
      const bf16* w = ws + (l * NF + h) * NF * NF;
      float s = 0.f;
      for (int i = 0; i < NF; i++) {
        float u = 0.f;
        for (int j = 0; j < NF; j++) u = fmaf(bf2f(w[i * NF + j]), x0[j * 16 + d], u);
        s = fmaf(u, cur[i * 16 + d], s);
      }
      nxt[o] = s;
      acc = fmaf(s, bf2f(wout[l * NF + h]), acc);
    }
    __syncthreads();
    float* tmp = cur; cur = nxt; nxt = tmp;
  }
  for (int n = t; n < 416; n += 128) {
    float h = 0.f;
    for (int k = 0; k < 416; k++) h = fmaf(x0[k], bf2f(w1[k * 416 + n]), h);
    h += bf2f(b1[n]);
    const float gl = 0.5f * h * (1.f + tanhf(0.7978845608028654f * (h + 0.044715f * h * h * h)));
    acc = fmaf(gl, bf2f(w2[n]), acc);
  }
  red[t] = acc;
  __syncthreads();
  for (int o = 64; o > 0; o >>= 1) { if (t < o) red[t] += red[t + o]; __syncthreads(); }
  if (t == 0) out[b] = __float2bfloat16(red[0] + bf2f(bout[0]));
}

typedef CUresult (*EncodeFn)(CUtensorMap*, CUtensorMapDataType, cuuint32_t, void*, const cuuint64_t*, const cuuint64_t*,
                             const cuuint32_t*, const cuuint32_t*, CUtensorMapInterleave, CUtensorMapSwizzle,
                             CUtensorMapL2promotion, CUtensorMapFloatOOBfill);

extern "C" void kernel_launch(void* const* d_in, const int* in_sizes, int n_in, void* d_out, int out_size) {
  const int* idx = (const int*)d_in[0];
  const bf16* table = (const bf16*)d_in[1];
  const bf16* ws = (const bf16*)d_in[2];
  const bf16* wout = (const bf16*)d_in[3];
  const bf16* w1 = (const bf16*)d_in[4];
  const bf16* b1 = (const bf16*)d_in[5];
  const bf16* w2 = (const bf16*)d_in[6];
  const bf16* bo = (const bf16*)d_in[7];
  bf16* out = (bf16*)d_out;

  static EncodeFn enc = nullptr;
  static Params P;
  static int n_sm = 0;
  if (!n_sm) {
    int dev = 0;
    cudaGetDevice(&dev);
    cudaDeviceGetAttribute(&n_sm, cudaDevAttrMultiProcessorCount, dev);
  }
  if (n_sm < NCTA + NHELP) {
    fallback_kernel<<<4096, 128, 0, cudaStreamPerThread>>>(idx, table, ws, wout, w1, b1, w2, bo, out);
    return;
  }
  if (!enc) {
    void* fn = nullptr;
    cudaDriverEntryPointQueryResult qr;
    cudaGetDriverEntryPoint("cuTensorMapEncodeTiled", &fn, cudaEnableDefault, &qr);
    enc = (EncodeFn)fn;
    cudaFuncSetAttribute(main_kernel, cudaFuncAttributeMaxDynamicSharedMemorySize, LAUNCH_SMEM);
    void* p;
    cudaGetSymbolAddress(&p, g_img); P.img = (unsigned char*)p;
    cudaGetSymbolAddress(&p, g_part); P.part = (unsigned long long*)p;
    cudaGetSymbolAddress(&p, g_ctr); P.ctr = (unsigned*)p;
    cudaGetSymbolAddress(&p, g_tabs); P.tabs = p;
    P.dk = make_desc(0, 128, 256, 0);
    P.dmn = make_desc(0, 8192, 1024, 1);
    for (int c = 0; c < NCTA; c++) P.role[c] = make_role(c);
  }
  P.idx = idx; P.table = table; P.ws = ws; P.wout = wout; P.b1 = b1; P.w2 = w2; P.bout = bo; P.out = out;
  TmaMaps tms;
  for (int h = 0; h < 4; h++) {
    const int c0 = (h >> 1) * 208 + (h & 1) * 96, nw = (h & 1) ? 112 : 96;
    cuuint64_t dims[2] = {(cuuint64_t)nw, 416};
    cuuint64_t strides[1] = {832};
    cuuint32_t box[2] = {64, 64};
    cuuint32_t es[2] = {1, 1};
    enc(&tms.m[h], CU_TENSOR_MAP_DATA_TYPE_BFLOAT16, 2, (void*)(w1 + c0), dims, strides, box, es,
        CU_TENSOR_MAP_INTERLEAVE_NONE, CU_TENSOR_MAP_SWIZZLE_128B, CU_TENSOR_MAP_L2_PROMOTION_L2_128B,
        CU_TENSOR_MAP_FLOAT_OOB_FILL_NONE);
  }
  main_kernel<<<NCTA + NHELP, 512, LAUNCH_SMEM, cudaStreamPerThread>>>(P, tms);
}
```

```cpp
#include <cuda_runtime.h>
#include <cuda_bf16.h>
#include <cuda.h>
#include <stdint.h>

typedef __nv_bfloat16 bf16;

constexpr int NF = 26;
constexpr int NCTA = 128;

constexpr int G0_KS = 24, G0_N = 56, G0_SLAB = G0_N * 32;
constexpr int L_KS = 43, L_SLAB = 1024;
constexpr int G0_BYTES = G0_KS * G0_SLAB;
constexpr int L_BYTES = L_KS * L_SLAB;
constexpr int IMG_BYTES = G0_BYTES + 3 * L_BYTES;

constexpr int W1_STAGES = 7;
constexpr int W1_STAGE_BYTES = 16384;
constexpr int OFF_LB = 0;
constexpr int OFF_LA = 44032;
constexpr int OFF_LC = 88064;
__host__ __device__ constexpr int w1_off(int st) { return st < 2 ? st * W1_STAGE_BYTES : OFF_LA + (st - 2) * W1_STAGE_BYTES; }
constexpr int OFF_G0 = 132096;
constexpr int OFF_IDX = 132096 + 16384;
constexpr int OFF_TAB = OFF_G0 + G0_BYTES;
constexpr int OFF_XOFF = OFF_TAB + 32000;
constexpr int OFF_BAR = OFF_XOFF + 6656;
constexpr int OFF_BW = OFF_BAR + 256;
constexpr int OFF_W2 = OFF_BW + 256;
constexpr int OFF_WTAB = OFF_W2 + 1792;
constexpr int OFF_EPOCH = OFF_WTAB + 256;
constexpr int OFF_STAB = (OFF_EPOCH + 16 + 127) / 128 * 128;
constexpr int OFF_LOFF = OFF_STAB + 3072 + 704;
constexpr int SMEM_BYTES = OFF_STAB + 4288;
static_assert(SMEM_BYTES <= 229376, "smem");
constexpr int LAUNCH_SMEM = SMEM_BYTES;

constexpr int BAR_W1FULL = 0  , BAR_W1FREE = 10  , BAR_W1DONE = 11  ,
              BAR_IMG = 14  , BAR_X0 = 18, BAR_SETUP = 19, BAR_EPOCH = 20, BAR_TABS = 21,
              BAR_Q = 22, BAR_STAB = 23, BAR_G0B = 24  , NBAR = 26;

struct TmaMaps { CUtensorMap m[4]; };
struct Params {
  const int* idx; const bf16* table; const bf16* ws; const bf16* wout; const bf16* b1; const bf16* w2; const bf16* bout;
  bf16* out;
  unsigned char* img; unsigned long long* part; unsigned* ctr; const void* tabs;
  uint64_t dk, dmn;
  uint2 role[NCTA];
};

__device__ __align__(1024) unsigned char g_img[IMG_BYTES];
__device__ unsigned long long g_part[NCTA * 128];
__device__ __align__(128) unsigned g_ctr[64];

#define GT(i) do {} while (0)
#define TL(i) do {} while (0)
#define TLP(i) do {} while (0)
#define TLA(i) do {} while (0)
#define TLW(w, i) do {} while (0)
#define TL_INIT() do {} while (0)
#define TL_START() 0
#define TL_PUT0(c) do {} while (0)
#define TL_DUMP() do {} while (0)
__device__ __forceinline__ uint32_t smem_u32(const void* p) { return (uint32_t)__cvta_generic_to_shared(p); }
__device__ __forceinline__ bool elect_one() {
  uint32_t pred;
  asm volatile("{\n.reg .pred p;\nelect.sync _|p, 0xffffffff;\nselp.u32 %0, 1, 0, p;\n}\n" : "=r"(pred));
  return pred != 0;
}
__device__ __forceinline__ void mbar_init(uint32_t bar, uint32_t cnt) {
  asm volatile("mbarrier.init.shared::cta.b64 [%0], %1;" ::"r"(bar), "r"(cnt) : "memory");
}
__device__ __forceinline__ void mbar_expect_tx(uint32_t bar, uint32_t bytes) {
  asm volatile("mbarrier.arrive.expect_tx.shared::cta.b64 _, [%0], %1;" ::"r"(bar), "r"(bytes) : "memory");
}
__device__ __forceinline__ void mbar_arrive(uint32_t bar) {
  asm volatile("mbarrier.arrive.shared::cta.b64 _, [%0];" ::"r"(bar) : "memory");
}
__device__ __forceinline__ bool mbar_try(uint32_t bar, uint32_t parity) {
  uint32_t ok;
  asm volatile("{\n.reg .pred p;\nmbarrier.try_wait.parity.shared::cta.b64 p, [%1], %2;\nselp.u32 %0, 1, 0, p;\n}\n"
               : "=r"(ok) : "r"(bar), "r"(parity) : "memory");
  return ok != 0;
}
__device__ __forceinline__ void mbar_wait(uint32_t bar, uint32_t parity) {
#pragma unroll 1
  for (uint32_t it = 0; it < (1u << 26); it++)
    if (mbar_try(bar, parity)) return;
  __trap();
}
__device__ __forceinline__ void bulk_g2s(uint32_t dst, const void* src, uint32_t bytes, uint32_t bar) {
  asm volatile("cp.async.bulk.shared::cluster.global.mbarrier::complete_tx::bytes [%0], [%1], %2, [%3];"
               ::"r"(dst), "l"(src), "r"(bytes), "r"(bar) : "memory");
}
__device__ __forceinline__ void tma_2d(uint32_t dst, const CUtensorMap* tm, int x, int y, uint32_t bar) {
  asm volatile("cp.async.bulk.tensor.2d.shared::cluster.global.mbarrier::complete_tx::bytes [%0], [%1, {%3, %4}], [%2];"
               ::"r"(dst), "l"(tm), "r"(bar), "r"(x), "r"(y) : "memory");
}
__device__ __forceinline__ void tma_5d(uint32_t dst, const CUtensorMap* tm, int x, int f, uint32_t bar) {
  asm volatile("cp.async.bulk.tensor.5d.shared::cluster.global.mbarrier::complete_tx::bytes [%0], [%1, {%3, %4, %4, %4, %5}], [%2];"
               ::"r"(dst), "l"(tm), "r"(bar), "r"(x), "r"(0), "r"(f) : "memory");
}
__device__ __forceinline__ void cp_async16(uint32_t dst, const void* src) {
  asm volatile("cp.async.cg.shared.global [%0], [%1], 16;" ::"r"(dst), "l"(src) : "memory");
}
__device__ __forceinline__ void fence_proxy_async() { asm volatile("fence.proxy.async.shared::cta;" ::: "memory"); }
template <int ID, int N> __device__ __forceinline__ void named_bar_t() { asm volatile("bar.sync %0, %1;" ::"n"(ID), "n"(N) : "memory"); }
#define named_bar(id, n) named_bar_t<id, n>()

__device__ __forceinline__ void wg_fence() { asm volatile("wgmma.fence.sync.aligned;" ::: "memory"); }
__device__ __forceinline__ void wg_commit() { asm volatile("wgmma.commit_group.sync.aligned;" ::: "memory"); }
template <int N> __device__ __forceinline__ void wg_wait() { asm volatile("wgmma.wait_group.sync.aligned %0;" ::"n"(N) : "memory"); }
template <int N> __device__ __forceinline__ void reg_fence(float (&d)[N]) {
#pragma unroll
  for (int i = 0; i < N; i++) asm volatile("" : "+f"(d[i])::"memory");
}
constexpr uint32_t SMEM_BASE = 1024;
__host__ __device__ constexpr uint64_t make_desc(uint32_t off, uint32_t lbo, uint32_t sbo, uint32_t swz) {
  return (uint64_t)(((SMEM_BASE + off) & 0x3FFFF) >> 4) | ((uint64_t)(lbo >> 4) << 16) | ((uint64_t)(sbo >> 4) << 32) | ((uint64_t)swz << 62);
}

#define ACC4(d, o) "+f"(d[o]), "+f"(d[o + 1]), "+f"(d[o + 2]), "+f"(d[o + 3])
#define ACC8(d, o) ACC4(d, o), ACC4(d, o + 4)

__device__ __forceinline__ void wgmma_rs_n32(float (&d)[16], uint32_t a0, uint32_t a1, uint32_t a2, uint32_t a3, uint64_t db, int sc) {
  asm volatile("{\n.reg .pred p;\nsetp.ne.b32 p, %21, 0;\n"
               "wgmma.mma_async.sync.aligned.m64n32k16.f32.bf16.bf16 "
               "{%0,%1,%2,%3,%4,%5,%6,%7,%8,%9,%10,%11,%12,%13,%14,%15}, {%16,%17,%18,%19}, %20, p, 1, 1, 0;\n}\n"
               : ACC8(d, 0), ACC8(d, 8)
               : "r"(a0), "r"(a1), "r"(a2), "r"(a3), "l"(db), "r"(sc));
}
__device__ __forceinline__ void wgmma_rs_n56(float (&d)[28], uint32_t a0, uint32_t a1, uint32_t a2, uint32_t a3, uint64_t db, int sc) {
  asm volatile("{\n.reg .pred p;\nsetp.ne.b32 p, %33, 0;\n"
               "wgmma.mma_async.sync.aligned.m64n56k16.f32.bf16.bf16 "
               "{%0,%1,%2,%3,%4,%5,%6,%7,%8,%9,%10,%11,%12,%13,%14,%15,%16,%17,%18,%19,%20,%21,%22,%23,%24,%25,%26,%27}, "
               "{%28,%29,%30,%31}, %32, p, 1, 1, 0;\n}\n"
               : ACC8(d, 0), ACC8(d, 8), ACC8(d, 16), ACC4(d, 24)
               : "r"(a0), "r"(a1), "r"(a2), "r"(a3), "l"(db), "r"(sc));
}
__device__ __forceinline__ void wgmma_rs_n112_tb(float (&d)[56], uint32_t a0, uint32_t a1, uint32_t a2, uint32_t a3, uint64_t db, int sc) {
  asm volatile("{\n.reg .pred p;\nsetp.ne.b32 p, %61, 0;\n"
               "wgmma.mma_async.sync.aligned.m64n112k16.f32.bf16.bf16 "
               "{%0,%1,%2,%3,%4,%5,%6,%7,%8,%9,%10,%11,%12,%13,%14,%15,%16,%17,%18,%19,%20,%21,%22,%23,%24,%25,%26,%27,%28,%29,%30,%31,%32,%33,%34,%35,%36,%37,%38,%39,%40,%41,%42,%43,%44,%45,%46,%47,%48,%49,%50,%51,%52,%53,%54,%55}, "
               "{%56,%57,%58,%59}, %60, p, 1, 1, 1;\n}\n"
               : ACC8(d, 0), ACC8(d, 8), ACC8(d, 16), ACC8(d, 24), ACC8(d, 32), ACC8(d, 40), ACC8(d, 48)
               : "r"(a0), "r"(a1), "r"(a2), "r"(a3), "l"(db), "r"(sc));
}

__device__ __forceinline__ void wgmma_rs_n8(float (&d)[4], uint32_t a0, uint32_t a1, uint32_t a2, uint32_t a3, uint64_t db, int sc) {
  asm volatile("{\n.reg .pred p;\nsetp.ne.b32 p, %9, 0;\n"
               "wgmma.mma_async.sync.aligned.m64n8k16.f32.bf16.bf16 {%0,%1,%2,%3}, {%4,%5,%6,%7}, %8, p, 1, 1, 0;\n}\n"
               : ACC4(d, 0)
               : "r"(a0), "r"(a1), "r"(a2), "r"(a3), "l"(db), "r"(sc));
}
__device__ __forceinline__ uint32_t mul_lo(uint32_t v, uint32_t r) {
  __nv_bfloat162 a = *reinterpret_cast<__nv_bfloat162*>(&v), b = *reinterpret_cast<__nv_bfloat162*>(&r);
  __nv_bfloat162 c = __hmul2(__low2bfloat162(a), b);
  return *reinterpret_cast<uint32_t*>(&c);
}
__device__ __forceinline__ uint32_t mul_hi(uint32_t v, uint32_t r) {
  __nv_bfloat162 a = *reinterpret_cast<__nv_bfloat162*>(&v), b = *reinterpret_cast<__nv_bfloat162*>(&r);
  __nv_bfloat162 c = __hmul2(__high2bfloat162(a), b);
  return *reinterpret_cast<uint32_t*>(&c);
}
__device__ __forceinline__ uint32_t mul_ew(uint32_t v, uint32_t r) {
  __nv_bfloat162 a = *reinterpret_cast<__nv_bfloat162*>(&v), b = *reinterpret_cast<__nv_bfloat162*>(&r);
  __nv_bfloat162 c = __hmul2(a, b);
  return *reinterpret_cast<uint32_t*>(&c);
}
__device__ __forceinline__ uint32_t pack_bf16(float lo, float hi) {
  uint32_t r;
  asm("cvt.rn.bf16x2.f32 %0, %1, %2;" : "=r"(r) : "f"(hi), "f"(lo));
  return r;
}
__device__ __forceinline__ float bf2f(bf16 v) { return __bfloat162float(v); }
__device__ __forceinline__ float bflo(uint32_t w) { return __uint_as_float(w << 16); }
__device__ __forceinline__ float bfhi(uint32_t w) { return __uint_as_float(w & 0xffff0000u); }

__device__ __forceinline__ void st_img(uint32_t* p, uint32_t v) {
  asm volatile("st.relaxed.gpu.global.u32 [%0], %1;" ::"l"(p), "r"(v) : "memory");
}
__device__ __forceinline__ void fence_proxy_async_global() { asm volatile("fence.proxy.async.global;" ::: "memory"); }
__device__ __forceinline__ uint32_t ld_back(const uint32_t* p) {
  uint32_t v;
  asm volatile("ld.relaxed.gpu.global.u32 %0, [%1];" : "=r"(v) : "l"(p) : "memory");
  return v;
}
__host__ __device__ constexpr int Fq(int q, int t, int e) {
  if (t == 12) return 24 + e;
  const int u = (t + 3 * q) % 12;
  const int sw = (q >= 2 && u >= 6) ? 1 : 0;
  return 2 * u + (e ^ sw);
}
constexpr int M_ONE = 26, M_NONE = 27;
struct Mono { int f1, f2; };
__host__ __device__ constexpr Mono g0_mono(int s, int q, int e) {
  if (s < 30) { const int d = s / 6 + 1, a = (s % 6) >> 1; return {Fq(q, a, s & 1), Fq(q, a + d, e)}; }
  if (s < 33) return {Fq(q, s - 30, e), Fq(q, s - 24, e)};
  if (s < 35) return {Fq(q, s - 33, e), Fq(q, s - 33, e)};
  if (s == 35) return {Fq(q, e, 0), Fq(q, e, 1)};
  if (s == 36) return {Fq(q, 2, 0), Fq(q, 2, e)};
  if (s == 37) return e ? Mono{Fq(q, 2, 1), Fq(q, 2, 1)} : Mono{M_NONE, M_NONE};
  if (s < 44) return {24 + ((s - 38) & 1), Fq(q, (s - 38) >> 1, e)};
  if (s < 47) return {Fq(q, s - 44, e), M_ONE};
  if (q == 0) return {24, 24 + e};
  if (q == 1) return e ? Mono{25, 25} : Mono{M_NONE, M_NONE};
  if (q == 2) return {24 + e, M_ONE};
  return e ? Mono{M_NONE, M_NONE} : Mono{M_ONE, M_ONE};
}
constexpr int QM_RS = 40;
constexpr int O_ZERO = 31 * QM_RS + 39, O_CONST = 30 * QM_RS + 39;
struct StaticTabs {
  uint32_t otab[48 * 8];
  uint32_t x1tab[48 * 8];
  uint16_t ltab[88 * 4];
  uint16_t loff[32 * 8];
};
constexpr StaticTabs make_tabs() {
  StaticTabs T{};
  for (int s = 0; s < 48; s++)
    for (int q = 0; q < 4; q++)
      for (int e = 0; e < 2; e++) {
        const Mono m = g0_mono(s, q, e);
        const bool none = m.f1 == M_NONE, cs = m.f1 == M_ONE, lin = m.f2 == M_ONE;
        const uint32_t o1 = none ? O_ZERO : cs ? O_CONST : m.f1 * QM_RS + (lin ? 26 : m.f2);
        const uint32_t o2 = (none || cs || lin || m.f1 == m.f2) ? O_ZERO : m.f2 * QM_RS + m.f1;
        T.otab[s * 8 + q * 2 + e] = o1 | (o2 << 16);
        const bool qd = m.f1 < NF && m.f2 < NF;
        const uint32_t y1 = qd ? m.f1 * NF + m.f2 : 0xffffu;
        const uint32_t y2 = (qd && m.f1 != m.f2) ? m.f2 * NF + m.f1 : 0xffffu;
        T.x1tab[s * 8 + q * 2 + e] = y1 | (y2 << 16);
      }
  for (int s = 0; s < 88; s++)
    for (int q = 0; q < 4; q++) {
      uint16_t v = 0;
      if (s < 85) {
        const bool ex = s >= 78;
        const int a = s / 13, k = s - 78;
        const int tt = ex ? ((k < 3) ? k : (k < 6 ? k + 3 : 12)) : s % 13;
        const int in = ex ? 24 + (q >> 1) : 8 * (a >> 1) + 2 * q + (a & 1);
        const bool valid = !(ex && tt == 12 && (q & 1));
        const int f0 = Fq(q, tt, 0);
        v = (uint16_t)((f0 >> 1) | ((f0 & 1) << 4) | ((valid ? 1 : 0) << 5) | (in << 6));
      }
      T.ltab[s * 4 + q] = v;
    }
  for (int ln = 0; ln < 32; ln++)
    for (int k = 0; k < 8; k++) {
      const int m = ln >> 3, r = ln & 7;
      const int tt = (k < 6) ? 2 * k + (m >> 1) : 12;
      T.loff[ln * 8 + k] = (uint16_t)(2 * Fq(r >> 1, tt, r & 1));
    }
  return T;
}
static_assert(sizeof(StaticTabs) == 4288, "tabs");
__device__ __align__(128) const StaticTabs g_tabs = make_tabs();

constexpr int SETUP_WARPS = 7;
constexpr int WL_BYTES = NF * NF * NF * 2;
static inline uint2 make_role(int cta) {
  int kind = 5, grp = 0, j = 0, off = 0, bytes = 0;
  const int c = cta, SL = NF * NF * 2;
  if (c < 56) { kind = 1 + c / 28; grp = (c % 28) / 7; j = c % 7; off = kind * WL_BYTES + grp * 8 * SL; bytes = (grp < 3 ? 8 : 2) * SL; }
  else if (c < 80) { kind = 0; grp = (c - 56) / 8; j = (c - 56) % 8; off = 3 * WL_BYTES + grp * 8 * SL; bytes = 8 * SL; }
  else if (c < 83) { kind = 0; grp = 3; j = c - 80; off = 3 * WL_BYTES + 24 * SL; bytes = 2 * SL; }
  else if (c < 95) { kind = 3; grp = (c - 83) / 4; j = (c - 83) % 4; off = grp * 8 * SL; bytes = 8 * SL; }
  const int delta = off & 127;
  uint2 r;
  r.x = (uint32_t)(off - delta) | ((uint32_t)kind << 24);
  r.y = (uint32_t)(bytes + delta) | ((uint32_t)delta << 16) | ((uint32_t)grp << 24) | ((uint32_t)j << 28);
  return r;
}

__device__ __forceinline__ uint32_t layer_row(int li, int grp, int r, int lane, const unsigned char* raw, const StaticTabs* T,
                                              uint32_t bar, uint32_t tbar, const bf16* __restrict__ wout, uint32_t* img32) {
  const int ks = li ? r : 13 * grp + (r >> 2), ng = li ? grp : (r & 3);
  if (ks >= 43 || (!li && grp < 3 && r >= 52)) return 0;
  const uint32_t* w32 = reinterpret_cast<const uint32_t*>(raw);
  const int n8 = lane >> 2, q = lane & 3;
  const int o = (ng < 3) ? ng * 8 + n8 : 24 + (n8 >> 2);
  const bool vo = (ng < 3) || !(n8 & 1);
  const int ob = li ? (o - 8 * grp) * 338 : o * 13 - 8 * grp * 338;
  const int si = li ? 13 : 338;
  uint32_t bias = 0;
  if (vo && ks == 42 && li == 0 && q == 0) bias = (uint32_t)__ldg(reinterpret_cast<const unsigned short*>(wout) + 2 * NF + o);
  uint32_t* dst = img32 + G0_BYTES / 4 + li * (L_BYTES / 4) + (ks * 4 + ng) * 64 + lane;
  mbar_wait(tbar, 0);
  const uint32_t e0 = T->ltab[8 * ks + q], e1 = T->ltab[8 * ks + 4 + q];
  const bool v0 = vo && (e0 & 32), v1 = vo && (e1 & 32);
  const int s0 = v0 ? ob + (e0 >> 6) * si + (e0 & 15) : 0, s1 = v1 ? ob + (e1 >> 6) * si + (e1 & 15) : 0;
  TL(33);
  mbar_wait(bar, 0);
  TL(36);
  uint32_t w0 = w32[s0], w1 = w32[s1];
  w0 = (e0 & 16) ? __funnelshift_l(w0, w0, 16) : w0;
  w1 = (e1 & 16) ? __funnelshift_l(w1, w1, 16) : w1;
  w0 = v0 ? w0 : 0u;
  w1 = v1 ? w1 : bias;
  st_img(dst, w0); st_img(dst + 32, w1);
  const uint32_t chk = (ld_back(dst) ^ w0) | (ld_back(dst + 32) ^ w1);
  fence_proxy_async_global();
  return chk;
}
__device__ __forceinline__ float x1_val(const unsigned short* wh, uint32_t e) {
  const uint32_t a = e & 0xffff, b = e >> 16;
  const uint32_t x = wh[a == 0xffff ? 0 : a], y = wh[b == 0xffff ? 0 : b];
  return (a == 0xffff ? 0.f : __uint_as_float(x << 16)) + (b == 0xffff ? 0.f : __uint_as_float(y << 16));
}
__device__ __forceinline__ uint32_t x1_row(int ng, int ks, int lane, const unsigned char* raw, const StaticTabs* T, uint32_t bar, uint32_t tbar, uint32_t* img32) {
  if (ks >= 24) return 0;
  const int n8 = lane >> 2, q = lane & 3;
  const unsigned short* wh = reinterpret_cast<const unsigned short*>(raw) + n8 * (NF * NF);
  uint32_t* dst = img32 + ks * (G0_SLAB / 4) + ng * 64 + lane;
  mbar_wait(tbar, 0);
  const uint2 ea = *reinterpret_cast<const uint2*>(&T->x1tab[16 * ks + 2 * q]), eb = *reinterpret_cast<const uint2*>(&T->x1tab[16 * ks + 8 + 2 * q]);
  mbar_wait(bar, 0);
  const uint32_t w0 = pack_bf16(x1_val(wh, ea.x), x1_val(wh, ea.y)), w1 = pack_bf16(x1_val(wh, eb.x), x1_val(wh, eb.y));
  st_img(dst, w0); st_img(dst + 32, w1);
  const uint32_t chk = (ld_back(dst) ^ w0) | (ld_back(dst + 32) ^ w1);
  fence_proxy_async_global();
  return chk;
}

constexpr int NHELP = 4;
constexpr int H_MS = 32 * QM_RS + 4;
constexpr int H_W5 = 0, H_W4 = 35328, H_W0 = 70656, H_TAB = 73472, H_B = 77824, H_M = 82944, H_XE = H_M + 8 * H_MS * 4, H_BAR = H_XE + 1536;
__device__ __forceinline__ int wf_off(int b, int h) { return (b >> 3) * 512 + (h >> 3) * 128 + (b & 7) * 16 + (h & 7) * 2; }
__device__ __forceinline__ void helper_role(int hk, const Params& P, unsigned char* smem, uint32_t sb) {
  const int t = threadIdx.x, warp = __shfl_sync(0xffffffffu, t >> 5, 0), lane = t & 31;
  const uint32_t d5bar = sb + H_BAR, d4bar = sb + H_BAR + 8, tbar = sb + H_BAR + 16;
  const unsigned char* wsb = reinterpret_cast<const unsigned char*>(P.ws);
  unsigned char* WB = smem + H_B;
  float* M = reinterpret_cast<float*>(smem + H_M);
  constexpr uint32_t W5B = WL_BYTES + ((5 * WL_BYTES) & 127), W4B = WL_BYTES + ((4 * WL_BYTES) & 127);
  if (warp < 3 && elect_one()) {
    mbar_init(sb + H_BAR + 8 * warp, 1);
    asm volatile("fence.mbarrier_init.release.cluster;" ::: "memory");
    if (warp == 0) {
      mbar_expect_tx(d5bar, W5B);
#pragma unroll
      for (int c = 0; c < 5; c++)
        bulk_g2s(sb + H_W5 + c * 8192, wsb + ((5 * WL_BYTES) & ~127) + c * 8192, c < 4 ? 8192u : W5B - 4 * 8192, d5bar);
    }
  }
  reinterpret_cast<uint32_t*>(WB)[t] = 0;
  __syncthreads();
  if (warp >= 5 && warp < 12 && elect_one()) {
    if (warp < 10) {
      const int c = warp - 5;
      if (c == 0) mbar_expect_tx(d4bar, W4B + (hk == 3 ? 2768 : 0));
      bulk_g2s(sb + H_W4 + c * 8192, wsb + ((4 * WL_BYTES) & ~127) + c * 8192, c < 4 ? 8192u : W4B - 4 * 8192, d4bar);
    } else if (warp == 10) {
      mbar_expect_tx(tbar, sizeof(StaticTabs));
      bulk_g2s(sb + H_TAB, P.tabs, sizeof(StaticTabs), tbar);
    } else if (hk == 3) {
      bulk_g2s(sb + H_W0, wsb + ((24 * NF * NF * 2) & ~127), 2768, d4bar);
    }
  }
  const unsigned short* wo16 = reinterpret_cast<const unsigned short*>(P.wout);
  uint32_t c5[13];
#pragma unroll
  for (int k = 0; k < 13; k++) c5[k] = __ldg(reinterpret_cast<const uint32_t*>(P.wout + 5 * NF) + k);
  unsigned short wv = 0;
  const int io0 = (hk < 3) ? 8 * hk : 24;
  if (t >= 352 && t < 352 + NF) wv = __ldg(wo16 + 4 * NF + t - 352);
  else if (t >= 384 && t < 392 && io0 + t - 384 < NF) wv = __ldg(wo16 + 3 * NF + io0 + t - 384);
  const StaticTabs* T = reinterpret_cast<const StaticTabs*>(smem + H_TAB);
  const int n8 = lane >> 2, q = lane & 3, g = n8;
  const int fil = (hk < 3) ? n8 : (n8 >> 2);
  const bool fx1 = (hk == 3) && !(n8 & 1);
  uint32_t* dst = reinterpret_cast<uint32_t*>(P.img) + (warp >> 1) * (G0_SLAB / 4) + (warp & 1) * 32 + (3 + hk) * 64 + lane;
  if (t >= 352 && t < 352 + NF) *reinterpret_cast<unsigned short*>(WB + wf_off(26, t - 352)) = wv;
  if (t >= 384 && t < 392) { M[(t - 384) * H_MS + O_ZERO] = 0.f; M[(t - 384) * H_MS + O_CONST] = __uint_as_float((uint32_t)wv << 16); }
  mbar_wait(d5bar, 0);
  if (t < 338) {
    const uint32_t* w5 = reinterpret_cast<const uint32_t*>(smem + H_W5 + ((5 * WL_BYTES) & 127)) + t;
    float s0 = 0.f, s1 = 0.f, s2 = 0.f, s3 = 0.f;
#pragma unroll
    for (int k = 0; k < 13; k++) {
      const uint32_t wa = w5[(2 * k) * 338], wb = w5[(2 * k + 1) * 338];
      const float ca = bflo(c5[k]), cb = bfhi(c5[k]);
      s0 = fmaf(ca, bflo(wa), s0); s1 = fmaf(ca, bfhi(wa), s1);
      s2 = fmaf(cb, bflo(wb), s2); s3 = fmaf(cb, bfhi(wb), s3);
    }
    const int h = (t * 79) >> 10, tp = t - 13 * h;
    *reinterpret_cast<bf16*>(WB + wf_off(2 * tp, h)) = __float2bfloat16(s0 + s2);
    *reinterpret_cast<bf16*>(WB + wf_off(2 * tp + 1, h)) = __float2bfloat16(s1 + s3);
  }
  fence_proxy_async();
  mbar_wait(tbar, 0);
  uint2 fot[3];
#pragma unroll
  for (int r = 0; r < 3; r++) fot[r] = *reinterpret_cast<const uint2*>(&T->otab[(warp + 16 * r) * 8 + q * 2]);
  mbar_wait(d4bar, 0);
  const int wgi = warp >> 2, il = 2 * wgi + ((warp >> 1) & 1), mt = warp & 1;
  const bool mma_wg = (hk < 3) || (wgi == 0);
  uint32_t a[2][4];
  if (mma_wg) {
    const unsigned short* A = reinterpret_cast<const unsigned short*>(smem + H_W4 + ((4 * WL_BYTES) & 127)) + (io0 + il) * NF + mt * 16 + g;
#pragma unroll
    for (int kk = 0; kk < 2; kk++) {
#pragma unroll
      for (int jj = 0; jj < 4; jj++) {
        const int k = kk * 16 + 2 * q + (jj >> 1) * 8, mo = (jj & 1) * 8;
        const int kc = (k < NF) ? k : 0;
        const uint32_t lo = A[kc * (NF * NF) + mo], hi = A[(kc + 1) * (NF * NF) + mo];
        a[kk][jj] = (k < NF) ? (lo | (hi << 16)) : 0u;
      }
    }
  }
  if (hk == 3) {
    const int u0 = (warp >= 4) ? t - 128 : -1;
    if (u0 >= 0) {
      const int sl = u0 >> 3, xl = (u0 >> 2) & 1, xq = u0 & 3;
      const uint2 xt = *reinterpret_cast<const uint2*>(&T->x1tab[sl * 8 + xq * 2]);
      const unsigned short* wh = reinterpret_cast<const unsigned short*>(smem + H_W0 + ((24 * NF * NF * 2) & 127)) + xl * (NF * NF);
      reinterpret_cast<uint32_t*>(smem + H_XE)[u0] = pack_bf16(x1_val(wh, xt.x), x1_val(wh, xt.y));
    }
  }
  __syncthreads();
  if (mma_wg) {
    float c[16];
    wg_fence();
    wgmma_rs_n32(c, a[0][0], a[0][1], a[0][2], a[0][3], make_desc(H_B, 128, 512, 0), 0);
    wgmma_rs_n32(c, a[1][0], a[1][1], a[1][2], a[1][3], make_desc(H_B + 256, 128, 512, 0), 1);
    wg_commit();
    wg_wait<0>();
    reg_fence(c);
    float* Mi = M + il * H_MS;
#pragma unroll
    for (int n = 0; n < 4; n++) {
      *reinterpret_cast<float2*>(&Mi[(mt * 16 + g) * QM_RS + n * 8 + 2 * q]) = make_float2(c[4 * n], c[4 * n + 1]);
      *reinterpret_cast<float2*>(&Mi[(mt * 16 + g + 8) * QM_RS + n * 8 + 2 * q]) = make_float2(c[4 * n + 2], c[4 * n + 3]);
    }
  }
  __syncthreads();
  uint32_t val[3], chk = 0;
#pragma unroll
  for (int r = 0; r < 3; r++) {
    const float* Mf = M + fil * H_MS;
    const float v0 = Mf[fot[r].x & 0xffff] + Mf[fot[r].x >> 16], v1 = Mf[fot[r].y & 0xffff] + Mf[fot[r].y >> 16];
    const uint32_t xe = reinterpret_cast<const uint32_t*>(smem + H_XE)[(warp + 16 * r) * 8 + (n8 >> 2) * 4 + q];
    val[r] = fx1 ? xe : pack_bf16(v0, v1);
    st_img(dst + r * 8 * (G0_SLAB / 4), val[r]);
  }
#pragma unroll
  for (int r = 0; r < 3; r++) chk |= ld_back(dst + r * 8 * (G0_SLAB / 4)) ^ val[r];
  fence_proxy_async_global();
  if (__any_sync(0xffffffffu, chk != 0)) __trap();
  __syncthreads();
  if (t == 0) asm volatile("red.relaxed.gpu.global.add.u32 [%0], 1;" ::"l"(P.ctr + 32) : "memory");
}

template <int S>
__device__ __forceinline__ uint32_t l_prod(const uint32_t (&vp)[4], const uint32_t (&X)[13]) {
  if constexpr (S < 78) {
    constexpr int a = S / 13, t = S % 13;
    return (a & 1) ? mul_hi(vp[a >> 1], X[t]) : mul_lo(vp[a >> 1], X[t]);
  } else if constexpr (S < 85) {
    constexpr int k = S - 78;
    constexpr int t = (k < 3) ? k : (k < 6 ? k + 3 : 12);
    return mul_lo(vp[3], X[t]);
  } else {
    return 0x00003F80u;
  }
}
template <int S>
__device__ __forceinline__ uint32_t g0_prod(const uint32_t (&X)[13], uint32_t selU, uint32_t selV) {
  if constexpr (S < 30) {
    constexpr int d = S / 6 + 1, a = (S % 6) >> 1;
    return (S & 1) ? mul_hi(X[a], X[a + d]) : mul_lo(X[a], X[a + d]);
  } else if constexpr (S < 33) {
    return mul_ew(X[S - 30], X[S - 24]);
  } else if constexpr (S < 35) {
    return mul_ew(X[S - 33], X[S - 33]);
  } else if constexpr (S == 35) {
    return mul_ew(__byte_perm(X[0], X[1], 0x5410), __byte_perm(X[0], X[1], 0x7632));
  } else if constexpr (S == 36) {
    return mul_lo(X[2], X[2]);
  } else if constexpr (S == 37) {
    return mul_hi(X[2], X[2]);
  } else if constexpr (S < 44) {
    constexpr int a = (S - 38) >> 1;
    return ((S - 38) & 1) ? mul_hi(X[12], X[a]) : mul_lo(X[12], X[a]);
  } else if constexpr (S < 47) {
    return X[S - 44];
  } else {
    return mul_ew(__byte_perm(X[12], 0x3F803F80u, selU), __byte_perm(X[12], 0x3F803F80u, selV));
  }
}

constexpr int NBK = 4;

template <int KS, int KE>
__device__ __forceinline__ void l_fill(uint32_t (*A)[4], const uint32_t (&vp)[2][4], const uint32_t (&X)[2][13]) {
  A[0][0] = l_prod<2 * KS>(vp[0], X[0]);
  A[0][1] = l_prod<2 * KS>(vp[1], X[1]);
  A[0][2] = l_prod<2 * KS + 1>(vp[0], X[0]);
  A[0][3] = l_prod<2 * KS + 1>(vp[1], X[1]);
  if constexpr (KS + 1 < KE) l_fill<KS + 1, KE>(A + 1, vp, X);
}
template <int KS, int OFF>
__device__ __forceinline__ void layer_rec(float (&d)[16], const uint32_t (&vp)[2][4], const uint32_t (&X)[2][13], uint64_t dk) {
  constexpr int KE = (KS + NBK < L_KS) ? KS + NBK : L_KS;
  uint32_t A[NBK][4];
  l_fill<KS, KE>(A, vp, X);
  wg_fence();
#pragma unroll
  for (int k = 0; k < KE - KS; k++)
    wgmma_rs_n32(d, A[k][0], A[k][1], A[k][2], A[k][3], dk + (uint64_t)((OFF + (KS + k) * L_SLAB) >> 4), (KS + k) > 0);
  wg_commit();
  if constexpr (KE < L_KS) {
    wg_wait<1>();
    layer_rec<KE, OFF>(d, vp, X, dk);
  }
}
template <int OFF, int NK>
__device__ __forceinline__ void layer_first(float (&d)[16], const uint32_t (&vp)[2][4], const uint32_t (&X)[2][13], uint64_t dk) {
  uint32_t A[NK][4];
  l_fill<0, NK>(A, vp, X);
  wg_fence();
#pragma unroll
  for (int k = 0; k < NK; k++) wgmma_rs_n32(d, A[k][0], A[k][1], A[k][2], A[k][3], dk + (uint64_t)((OFF + k * L_SLAB) >> 4), k > 0);
  wg_commit();
}
template <int KS, int KE>
__device__ __forceinline__ void g0_fill(uint32_t (*A)[4], const uint32_t (&X)[2][13], uint32_t selU, uint32_t selV) {
  A[0][0] = g0_prod<2 * KS>(X[0], selU, selV);
  A[0][1] = g0_prod<2 * KS>(X[1], selU, selV);
  A[0][2] = g0_prod<2 * KS + 1>(X[0], selU, selV);
  A[0][3] = g0_prod<2 * KS + 1>(X[1], selU, selV);
  if constexpr (KS + 1 < KE) g0_fill<KS + 1, KE>(A + 1, X, selU, selV);
}
template <int B0>
__device__ __forceinline__ void g0_rec(float (&d)[28], const uint32_t (&X)[2][13], uint32_t selU, uint32_t selV, uint64_t dk, uint32_t bar2, bool first) {
  constexpr int KS = B0 * NBK;
  if constexpr (KS == 8) { if (first) mbar_wait(bar2, 0); }
  if constexpr (KS == 16) { if (first) mbar_wait(bar2 + 8, 0); }
  constexpr int KE = (KS + NBK < G0_KS) ? KS + NBK : G0_KS;
  uint32_t A[NBK][4];
  g0_fill<KS, KE>(A, X, selU, selV);
  wg_fence();
#pragma unroll
  for (int k = 0; k < KE - KS; k++)
    wgmma_rs_n56(d, A[k][0], A[k][1], A[k][2], A[k][3], dk + (uint64_t)((OFF_G0 + (KS + k) * G0_SLAB) >> 4), (KS + k) > 0);
  wg_commit();
  if constexpr (KE < G0_KS) {
    wg_wait<1>();
    g0_rec<B0 + 1>(d, X, selU, selV, dk, bar2, first);
  }
}

__device__ __forceinline__ void ldsm_x4_t(uint32_t addr, uint32_t& r0, uint32_t& r1, uint32_t& r2, uint32_t& r3) {
  asm volatile("ldmatrix.sync.aligned.m8n8.x4.trans.shared.b16 {%0,%1,%2,%3}, [%4];"
               : "=r"(r0), "=r"(r1), "=r"(r2), "=r"(r3) : "r"(addr) : "memory");
}
__device__ __forceinline__ void ldsm_x2_t(uint32_t addr, uint32_t& r0, uint32_t& r1) {
  asm volatile("ldmatrix.sync.aligned.m8n8.x2.trans.shared.b16 {%0,%1}, [%2];" : "=r"(r0), "=r"(r1) : "r"(addr) : "memory");
}
__device__ __forceinline__ float tanh_fast(float x) { float y; asm("tanh.approx.f32 %0, %1;" : "=f"(y) : "f"(x)); return y; }

__device__ __forceinline__ uint32_t gelu2_pair(float lo, float hi, uint32_t bias) {
  uint32_t x = pack_bf16(lo, hi), t, u;
  asm("add.rn.bf16x2 %0, %0, %1;" : "+r"(x) : "r"(bias));
  asm("mul.rn.bf16x2 %0, %1, %1;" : "=r"(t) : "r"(x));
  asm("fma.rn.bf16x2 %0, %0, %1, %2;" : "+r"(t) : "r"(0x3D123D12u), "r"(0x3F4C3F4Cu));
  asm("mul.rn.bf16x2 %0, %1, %2;" : "=r"(u) : "r"(x), "r"(t));
  asm("tanh.approx.bf16x2 %0, %0;" : "+r"(u));
  asm("fma.rn.bf16x2 %0, %1, %0, %1;" : "+r"(u) : "r"(x));
  return u;
}

__device__ __forceinline__ void ldsm_x4(uint32_t addr, uint32_t (&r)[4]) {
  asm volatile("ldmatrix.sync.aligned.m8n8.x4.shared.b16 {%0,%1,%2,%3}, [%4];"
               : "=r"(r[0]), "=r"(r[1]), "=r"(r[2]), "=r"(r[3]) : "r"(addr) : "memory");
}
__device__ __forceinline__ uint32_t lds_u16(uint32_t addr) {
  unsigned short v;
  asm volatile("ld.shared.u16 %0, [%1];" : "=h"(v) : "r"(addr) : "memory");
  return v;
}
__device__ __forceinline__ void lds_u64(uint32_t addr, uint32_t& a, uint32_t& b) {
  asm volatile("ld.shared.v2.u32 {%0, %1}, [%2];" : "=r"(a), "=r"(b) : "r"(addr) : "memory");
}
__device__ __forceinline__ uint32_t lds_u32(uint32_t addr) {
  uint32_t v;
  asm volatile("ld.shared.u32 %0, [%1];" : "=r"(v) : "r"(addr) : "memory");
  return v;
}

__global__ void __launch_bounds__(512, 1)
main_kernel(const __grid_constant__ Params P, const __grid_constant__ TmaMaps tms) {
  extern __shared__ __align__(1024) unsigned char smem[];
  const uint32_t sb = smem_u32(smem);
  const int tid = threadIdx.x, warp = __shfl_sync(0xffffffffu, tid >> 5, 0), lane = tid & 31;
  if (blockIdx.x < NHELP) {
    helper_role(blockIdx.x, P, smem, sb);
    return;
  }
  const int cta = blockIdx.x - NHELP, nq = cta & 3, grp = cta >> 2;
  const uint2 role = P.role[cta];
  const uint32_t bar0 = sb + OFF_BAR;
  auto BAR = [&](int i) { return bar0 + 8 * i; };
  const int wg = warp >> 2, w4 = warp & 3, g = lane >> 2, q = lane & 3;
  const uint64_t dk = P.dk;
  const long long tl_c0 = TL_START();
  TL_INIT();
  TL_PUT0(tl_c0);

  if (tid < 256) {
    const unsigned char* isrc = reinterpret_cast<const unsigned char*>(P.idx + grp * 128 * NF);
#pragma unroll
    for (int k = 0; k < 4; k++) {
      const int c = tid + 256 * k;
      if (c < 832) cp_async16(sb + OFF_IDX + c * 16, isrc + c * 16);
    }
    asm volatile("cp.async.commit_group;" ::: "memory");
#pragma unroll
    for (int k = 0; k < 8; k++) {
      const int c = tid + 256 * k;
      if (c < 2000) cp_async16(sb + OFF_TAB + ((c ^ ((c >> 3) & 1)) << 4), reinterpret_cast<const unsigned char*>(P.table) + c * 16);
    }
    asm volatile("cp.async.commit_group;" ::: "memory");
  }
  if (elect_one()) {
    mbar_init(BAR(warp), (warp == BAR_W1FREE || warp == BAR_W1DONE) ? 2 : 1);
    if (warp < NBAR - 16)
      mbar_init(BAR(16 + warp), (16 + warp == BAR_X0) ? 256 : (16 + warp == BAR_SETUP) ? SETUP_WARPS : (16 + warp == BAR_TABS) ? 224 : 1);
    asm volatile("fence.mbarrier_init.release.cluster;" ::: "memory");
  }
  __syncthreads();
  TL(26);

  if (warp == 15) {
    if (elect_one()) {
      mbar_expect_tx(BAR(BAR_STAB), sizeof(StaticTabs));
      bulk_g2s(sb + OFF_STAB, P.tabs, sizeof(StaticTabs), BAR(BAR_STAB));
      if ((sb & 0x3FFFF) != SMEM_BASE) __trap();
      const CUtensorMap* tm0 = &tms.m[nq];
      asm volatile("prefetch.tensormap [%0];" ::"l"(tm0) : "memory");
#pragma unroll
      for (int st = 0; st < W1_STAGES; st++) {
        if (st == 1 && (role.x >> 24) < 5) mbar_wait(BAR(BAR_Q), 0);
        mbar_expect_tx(BAR(BAR_W1FULL + st), W1_STAGE_BYTES);
        tma_5d(sb + w1_off(st), tm0, 0, st * 4, BAR(BAR_W1FULL + st));
        tma_5d(sb + w1_off(st) + 8192, tm0, 64, st * 4, BAR(BAR_W1FULL + st));
      }
      TLP(22);
      mbar_wait(BAR(BAR_EPOCH), 0);
      TLP(23);
      const unsigned epoch_p = lds_u32(sb + OFF_EPOCH);
      auto wait_ctr = [&](const unsigned* ctr, unsigned target) {
        unsigned v;
        uint32_t it = 0;
#pragma unroll 1
        do {
          asm volatile("ld.relaxed.gpu.global.u32 %0, [%1];" : "=r"(v) : "l"(ctr) : "memory");
          if (++it > (1u << 22)) __trap();
        } while ((int)(v - target) < 0);
      };
      wait_ctr(P.ctr + 32, epoch_p << 4);
      mbar_wait(BAR(BAR_X0), 0);
      TLP(24);
#pragma unroll
      for (int i = 0; i < 6; i++) {
        const uint32_t bar = i < 2 ? BAR(BAR_IMG + 0) : BAR(BAR_G0B + (i - 2) / 2);
        if (!(i & 1)) mbar_expect_tx(bar, G0_BYTES / 3);
        bulk_g2s(sb + OFF_G0 + i * (G0_BYTES / 6), P.img + i * (G0_BYTES / 6), G0_BYTES / 6, bar);
      }
      wait_ctr(P.ctr, epoch_p << 7);
      mbar_wait(BAR(BAR_W1FREE), 0);
      mbar_expect_tx(BAR(BAR_IMG + 2), L_BYTES);
#pragma unroll
      for (int i = 0; i < 4; i++)
        bulk_g2s(sb + OFF_LB + i * (L_BYTES / 4), P.img + G0_BYTES + L_BYTES + i * (L_BYTES / 4), L_BYTES / 4, BAR(BAR_IMG + 2));
      mbar_wait(BAR(BAR_W1DONE), 0);
      mbar_expect_tx(BAR(BAR_IMG + 1), L_BYTES);
      mbar_expect_tx(BAR(BAR_IMG + 3), L_BYTES);
#pragma unroll
      for (int i = 0; i < 2; i++)
        bulk_g2s(sb + OFF_LA + i * (L_BYTES / 2), P.img + G0_BYTES + i * (L_BYTES / 2), L_BYTES / 2, BAR(BAR_IMG + 1));
#pragma unroll
      for (int i = 0; i < 2; i++)
        bulk_g2s(sb + OFF_LC + i * (L_BYTES / 2), P.img + G0_BYTES + 2 * L_BYTES + i * (L_BYTES / 2), L_BYTES / 2, BAR(BAR_IMG + 3));
      TLP(25);
    }
    __syncwarp();
    mbar_wait(BAR(BAR_X0), 0);
    mbar_wait(BAR(BAR_TABS), 0);
  } else if (wg < 2) {
    asm volatile("cp.async.wait_group 1;" ::: "memory");
    named_bar(1, 256);
#pragma unroll
    for (int k = 0; k < 7; k++) {
      const int p = tid + 256 * k;
      if (p < 64 * NF) {
        const uint2 v = reinterpret_cast<const uint2*>(smem + OFF_IDX)[p];
        const uint32_t o0 = v.x * 32 + ((v.x >> 2) & 1) * 16, o1 = v.y * 32 + ((v.y >> 2) & 1) * 16;
        reinterpret_cast<uint32_t*>(smem + OFF_XOFF)[p] = o0 | (o1 << 16);
      }
    }
    TL(1);
    asm volatile("cp.async.wait_all;" ::: "memory");
    mbar_arrive(BAR(BAR_X0));
    mbar_wait(BAR(BAR_X0), 0);
    TL(3);
    float acc[56];
    {
      const uint32_t xo0 = sb + OFF_XOFF + (wg * 64 + w4 * 16 + g) * 52, xo1 = xo0 + 8 * 52;
      const uint32_t tb = sb + OFF_TAB + (q & 1) * 8, hx = (q >> 1) << 4;
      const uint64_t db0 = P.dmn;
      auto load_a = [&](int pr, uint32_t (&A)[2][4]) {
        const uint32_t o0 = lds_u32(xo0 + 4 * pr), o1 = lds_u32(xo1 + 4 * pr);
        lds_u64(tb + ((o0 & 0xffff) ^ hx), A[0][0], A[0][2]); lds_u64(tb + ((o1 & 0xffff) ^ hx), A[0][1], A[0][3]);
        lds_u64(tb + ((o0 >> 16) ^ hx), A[1][0], A[1][2]); lds_u64(tb + ((o1 >> 16) ^ hx), A[1][1], A[1][3]);
      };
      uint32_t A[3][2][4];
      load_a(0, A[0]);
      load_a(1, A[1]);
#pragma unroll
      for (int pr = 0; pr < 13; pr++) {
        const int st = pr >> 1;
        if (!(pr & 1)) mbar_wait(BAR(BAR_W1FULL + st), 0);
        if (pr == 0) TL(28); if (pr == 6) TL(29);
        const uint64_t db = db0 + (uint64_t)((w1_off(st) + (pr & 1) * 4096) >> 4);
        wg_fence();
        wgmma_rs_n112_tb(acc, A[pr % 3][0][0], A[pr % 3][0][1], A[pr % 3][0][2], A[pr % 3][0][3], db, pr > 0);
        wgmma_rs_n112_tb(acc, A[pr % 3][1][0], A[pr % 3][1][1], A[pr % 3][1][2], A[pr % 3][1][3], db + (2048 >> 4), 1);
        wg_commit();
        wg_wait<1>();
        if (pr == 4 && (tid & 127) == 0) mbar_arrive(BAR(BAR_W1FREE));
        if (pr + 2 < 13) load_a(pr + 2, A[(pr + 2) % 3]);
      }
      wg_wait<0>();
      reg_fence(acc);
      if ((tid & 127) == 0) mbar_arrive(BAR(BAR_W1DONE));
    }
    TL(4);
    float dot[4];
    {
      mbar_wait(BAR(BAR_TABS), 0);
      uint32_t bb[16];
      const uint4* bp = reinterpret_cast<const uint4*>(smem + OFF_BW + q * 64);
#pragma unroll
      for (int i = 0; i < 4; i++) { const uint4 v = bp[i]; bb[4 * i] = v.x; bb[4 * i + 1] = v.y; bb[4 * i + 2] = v.z; bb[4 * i + 3] = v.w; }
      uint32_t H[14][2];
#pragma unroll
      for (int c = 0; c < 14; c++) {
        H[c][0] = gelu2_pair(acc[4 * c], acc[4 * c + 1], bb[c]);
        H[c][1] = gelu2_pair(acc[4 * c + 2], acc[4 * c + 3], bb[c]);
      }
      wg_fence();
#pragma unroll
      for (int j = 0; j < 7; j++)
        wgmma_rs_n8(dot, H[2 * j][0], H[2 * j][1], H[2 * j + 1][0], H[2 * j + 1][1], dk + (uint64_t)((OFF_W2 + j * 256) >> 4), j > 0);
      wg_commit();
      wg_wait<0>();
      reg_fence(dot);
    }
    __syncwarp();
    mbar_wait(BAR(BAR_EPOCH), 0);
    if (q == 0) {
      const unsigned epoch = lds_u32(sb + OFF_EPOCH);
#pragma unroll
      for (int r = 0; r < 2; r++) {
        const int row = wg * 64 + w4 * 16 + g + 8 * r;
        const unsigned long long pk = ((unsigned long long)epoch << 32) | (unsigned long long)__float_as_uint(dot[2 * r]);
        asm volatile("st.relaxed.gpu.global.u64 [%0], %1;" ::"l"(P.part + cta * 128 + row), "l"(pk) : "memory");
      }
    }
    __syncwarp();
  } else {
    const int t = tid - 256;
    const bool is_arr = (t == 192);
    unsigned ctr0 = 0;
    if (is_arr) asm volatile("ld.relaxed.gpu.global.u32 %0, [%1];" : "=r"(ctr0) : "l"(P.ctr) : "memory");
    {
      const int kind = role.x >> 24, w = warp - 8, rgrp = (role.y >> 24) & 15, rj = role.y >> 28;
      const unsigned char* wsb = reinterpret_cast<const unsigned char*>(P.ws);
      if (kind < 5 && elect_one()) {
        const uint32_t bytes = role.y & 0xffff;
        const uint32_t o = w * 8192;
        if (w == 0) mbar_expect_tx(BAR(BAR_Q), bytes);
        if (o < bytes) bulk_g2s(sb + OFF_G0 + o, wsb + (role.x & 0xffffff) + o, min(bytes - o, 8192u), BAR(BAR_Q));
      }
      TL(40);
      __syncwarp();
      const StaticTabs* T = reinterpret_cast<const StaticTabs*>(smem + OFF_STAB);
      uint32_t* img32 = reinterpret_cast<uint32_t*>(P.img);
      const unsigned char* raw = smem + OFF_G0 + ((role.y >> 16) & 127);
      uint32_t chk = 0;
      if (kind < 3) chk = layer_row(kind, rgrp, rj * SETUP_WARPS + w, lane, raw, T, BAR(BAR_Q), BAR(BAR_STAB), P.wout, img32);
      else if (kind == 3) chk = x1_row(rgrp, rj * SETUP_WARPS + w, lane, raw, T, BAR(BAR_Q), BAR(BAR_STAB), img32);
      if (__any_sync(0xffffffffu, chk != 0)) __trap();
      if (lane == 0) mbar_arrive(BAR(BAR_SETUP));
    }
    TL(1);
    if (is_arr) {
      asm volatile("" : "+r"(ctr0));
      *reinterpret_cast<volatile unsigned*>(smem + OFF_EPOCH) = (ctr0 >> 7) + 1;
      mbar_wait(BAR(BAR_SETUP), 0);
      TLA(30);
      if ((role.x >> 24) == 3) asm volatile("red.relaxed.gpu.global.add.u32 [%0], 1;" ::"l"(P.ctr + 32) : "memory");
      asm volatile("red.relaxed.gpu.global.add.u32 [%0], 1;" ::"l"(P.ctr) : "memory");
      mbar_arrive(BAR(BAR_EPOCH));
      TLA(31);
    }
    __syncwarp();
    {
      const int c0 = (nq >> 1) * 208 + (nq & 1) * 96, nw = (nq & 1) ? 112 : 96;
      if (t < 56) {
        const int n = 2 * t;
        const uint32_t v = (n < nw) ? __ldg(reinterpret_cast<const uint32_t*>(P.b1 + c0 + n)) : 0u;
        reinterpret_cast<uint32_t*>(smem + OFF_BW)[(t & 3) * 16 + (t >> 2)] = v;
      }
      if (t >= 64 && t < 64 + 112) {
        const int k = t - 64;
        const float w = (k < nw) ? 0.5f * bf2f(__ldg(P.w2 + c0 + k)) : 0.f;
        unsigned char* base = smem + OFF_W2 + (k >> 4) * 256 + ((k >> 3) & 1) * 128;
        *reinterpret_cast<bf16*>(base + (k & 7) * 2) = __float2bfloat16(w);
        if ((k & 7) == 0) {
#pragma unroll
          for (int r = 1; r < 8; r++) *reinterpret_cast<uint4*>(base + r * 16) = make_uint4(0, 0, 0, 0);
        }
      }
      fence_proxy_async();
    }
    if (t >= 128 && t < 192) {
      int u = t - 128, l = u >> 5, qq = (u >> 3) & 3, a = u & 7;
      float wtv = 0.f;
      if (a < 6) wtv = bf2f(__ldg(P.wout + l * NF + 8 * (a >> 1) + 2 * qq + (a & 1)));
      else if (a == 6 && !(qq & 1)) wtv = bf2f(__ldg(P.wout + l * NF + 24 + (qq >> 1)));
      reinterpret_cast<float*>(smem + OFF_WTAB)[u] = wtv;
    }
    mbar_arrive(BAR(BAR_TABS));
    TL(2);
    mbar_wait(BAR(BAR_X0), 0);
    mbar_wait(BAR(BAR_TABS), 0);
  }

  TL(5);
  const uint32_t selU = (q == 0) ? 0x1010u : (q == 1) ? 0x3232u : (q == 2) ? 0x3210u : 0x7654u;
  const uint32_t selV = (q < 2) ? 0x3210u : 0x7654u;
  uint32_t bo_raw = __ldg(reinterpret_cast<const unsigned short*>(P.bout));
  mbar_wait(BAR(BAR_EPOCH), 0);
  mbar_wait(BAR(BAR_STAB), 0);
  const unsigned epoch = lds_u32(sb + OFF_EPOCH);

  uint32_t X[2][13];
  auto load_x = [&](int sl) {
    const uint4 o = *reinterpret_cast<const uint4*>(smem + OFF_LOFF + lane * 16);
    const uint32_t xo = sb + OFF_XOFF + sl * 52;
    const uint32_t tb = sb + OFF_TAB, hx = ((lane >> 3) & 1) << 4;
    const uint32_t a0 = lds_u16(xo + (o.x & 0xffff)), a1 = lds_u16(xo + (o.x >> 16));
    const uint32_t a2 = lds_u16(xo + (o.y & 0xffff)), a3 = lds_u16(xo + (o.y >> 16));
    const uint32_t a4 = lds_u16(xo + (o.z & 0xffff)), a5 = lds_u16(xo + (o.z >> 16));
    const uint32_t a6 = lds_u16(xo + (o.w & 0xffff));
    ldsm_x4_t(tb + (a0 ^ hx), X[0][0], X[1][0], X[0][1], X[1][1]);
    ldsm_x4_t(tb + (a1 ^ hx), X[0][2], X[1][2], X[0][3], X[1][3]);
    ldsm_x4_t(tb + (a2 ^ hx), X[0][4], X[1][4], X[0][5], X[1][5]);
    ldsm_x4_t(tb + (a3 ^ hx), X[0][6], X[1][6], X[0][7], X[1][7]);
    ldsm_x4_t(tb + (a4 ^ hx), X[0][8], X[1][8], X[0][9], X[1][9]);
    ldsm_x4_t(tb + (a5 ^ hx), X[0][10], X[1][10], X[0][11], X[1][11]);
    ldsm_x2_t(tb + (a6 ^ hx), X[0][12], X[1][12]);
  };
  load_x(nq * 32 + wg * 4 + w4);
#pragma unroll 1
  for (int it = 0; it < 2; it++) {
    const int sl = nq * 32 + (wg + 4 * it) * 4 + w4;
    float S = 0.f;
    uint32_t vx[2][4], vg[2][4];
    {
      float a0[28];
      if (it == 0) mbar_wait(BAR(BAR_IMG + 0), 0);
      if (it < 2) TL(6 + it * 8);
      g0_rec<0>(a0, X, selU, selV, dk, BAR(BAR_G0B), it == 0);
      wg_wait<0>();
      reg_fence(a0);
      const float4* wt = reinterpret_cast<const float4*>(smem + OFF_WTAB) + q * 2;
      float4 wa = wt[0], wb = wt[1];
#pragma unroll
      for (int r = 0; r < 2; r++) {
        S = fmaf(wa.x, a0[0 + 2 * r], S); S = fmaf(wa.y, a0[1 + 2 * r], S);
        S = fmaf(wa.z, a0[4 + 2 * r], S); S = fmaf(wa.w, a0[5 + 2 * r], S);
        S = fmaf(wb.x, a0[8 + 2 * r], S); S = fmaf(wb.y, a0[9 + 2 * r], S);
        S = fmaf(wb.z, a0[24 + 2 * r], S);
#pragma unroll
        for (int c = 0; c < 3; c++) {
          vx[r][c] = pack_bf16(a0[4 * c + 2 * r], a0[4 * c + 2 * r + 1]);
          vg[r][c] = pack_bf16(a0[12 + 4 * c + 2 * r], a0[12 + 4 * c + 2 * r + 1]);
        }
        vx[r][3] = pack_bf16(a0[24 + 2 * r], 0.f);
        vg[r][3] = pack_bf16(a0[24 + 2 * r + 1], 0.f);
      }
    }
    float g3[16], xa[16];
    if (it < 2) TL(7 + it * 8);
    if (it == 0) {
      mbar_wait(BAR(BAR_IMG + 2), 0);
      mbar_wait(BAR(BAR_IMG + 1), 0);
      mbar_wait(BAR(BAR_IMG + 3), 0);
    }
    if (it < 2) TL(8 + it * 8);
    layer_rec<0, OFF_LB>(xa, vx, X, dk);
    if (it < 2) TL(9 + it * 8);
    wg_wait<1>();
    layer_first<OFF_LA, 3>(g3, vg, X, dk);
    wg_wait<1>();
    reg_fence(xa);
    {
      const float4* wt = reinterpret_cast<const float4*>(smem + OFF_WTAB) + 8 + q * 2;
      float4 wa = wt[0], wb = wt[1];
#pragma unroll
      for (int r = 0; r < 2; r++) {
        S = fmaf(wa.x, xa[0 + 2 * r], S); S = fmaf(wa.y, xa[1 + 2 * r], S);
        S = fmaf(wa.z, xa[4 + 2 * r], S); S = fmaf(wa.w, xa[5 + 2 * r], S);
        S = fmaf(wb.x, xa[8 + 2 * r], S); S = fmaf(wb.y, xa[9 + 2 * r], S);
        S = fmaf(wb.z, xa[12 + 2 * r], S);
#pragma unroll
        for (int c = 0; c < 3; c++) vx[r][c] = pack_bf16(xa[4 * c + 2 * r], xa[4 * c + 2 * r + 1]);
        vx[r][3] = pack_bf16(xa[12 + 2 * r], 0.f);
      }
    }
    layer_rec<3, OFF_LA>(g3, vg, X, dk);
    if (it < 2) TL(10 + it * 8);
    wg_wait<1>();
    const unsigned long long* pp = P.part + (grp * 4 + (lane & 3)) * 128 + sl;
    unsigned long long pk;
    asm volatile("ld.relaxed.gpu.global.u64 %0, [%1];" : "=l"(pk) : "l"(pp) : "memory");
    float xc[16];
    layer_rec<0, OFF_LC>(xc, vx, X, dk);
    if (it == 0) load_x(sl + 16);
    wg_wait<0>();
    reg_fence(xc);
    reg_fence(g3);
    {
      float Se = 0.f;
#pragma unroll
      for (int r = 0; r < 2; r++) {
#pragma unroll
        for (int c = 0; c < 3; c++) {
          S = fmaf(g3[4 * c + 2 * r], xc[4 * c + 2 * r], S);
          S = fmaf(g3[4 * c + 2 * r + 1], xc[4 * c + 2 * r + 1], S);
        }
        Se = fmaf(g3[12 + 2 * r], xc[12 + 2 * r], Se);
      }
      if (!(q & 1)) S += Se;
    }
#pragma unroll
    for (int o = 16; o > 0; o >>= 1) S += __shfl_xor_sync(0xffffffffu, S, o);
    if (it < 2) TL(12 + it * 8);
    {
      uint32_t spin = 0;
      while (lane < 4 && (unsigned)(pk >> 32) != epoch) {
        asm volatile("ld.relaxed.gpu.global.u64 %0, [%1];" : "=l"(pk) : "l"(pp) : "memory");
        if (++spin > (1u << 24)) __trap();
      }
      __syncwarp();
      float dv = __uint_as_float((unsigned)pk);
      float d01 = dv + __shfl_xor_sync(0xffffffffu, dv, 1);
      float dsum = d01 + __shfl_xor_sync(0xffffffffu, d01, 2);
      asm volatile("" : "+r"(bo_raw));
      if (lane == 0) P.out[grp * 128 + sl] = __float2bfloat16(S + dsum + __uint_as_float(bo_raw << 16));
    }
    __syncwarp();
    if (it < 2) TL(13 + it * 8);
  }
  TL_DUMP();
}

__global__ void __launch_bounds__(128) fallback_kernel(const int* __restrict__ idx, const bf16* __restrict__ table, const bf16* __restrict__ ws,
                                                       const bf16* __restrict__ wout, const bf16* __restrict__ w1, const bf16* __restrict__ b1,
                                                       const bf16* __restrict__ w2, const bf16* __restrict__ bout, bf16* __restrict__ out) {
  __shared__ float x0[416], xa[416], xb[416], red[128];
  const int b = blockIdx.x, t = threadIdx.x;
  for (int i = t; i < 416; i += 128) { x0[i] = bf2f(table[idx[b * NF + i / 16] * 16 + (i & 15)]); xa[i] = x0[i]; }
  __syncthreads();
  float acc = 0.f;
  float* cur = xa;
  float* nxt = xb;
  for (int l = 0; l < 6; l++) {
    for (int o = t; o < 416; o += 128) {
      const int h = o >> 4, d = o & 15;
      const bf16* w = ws + (l * NF + h) * NF * NF;
      float s = 0.f;
      for (int i = 0; i < NF; i++) {
        float u = 0.f;
        for (int j = 0; j < NF; j++) u = fmaf(bf2f(w[i * NF + j]), x0[j * 16 + d], u);
        s = fmaf(u, cur[i * 16 + d], s);
      }
      nxt[o] = s;
      acc = fmaf(s, bf2f(wout[l * NF + h]), acc);
    }
    __syncthreads();
    float* tmp = cur; cur = nxt; nxt = tmp;
  }
  for (int n = t; n < 416; n += 128) {
    float h = 0.f;
    for (int k = 0; k < 416; k++) h = fmaf(x0[k], bf2f(w1[k * 416 + n]), h);
    h += bf2f(b1[n]);
    const float gl = 0.5f * h * (1.f + tanhf(0.7978845608028654f * (h + 0.044715f * h * h * h)));
    acc = fmaf(gl, bf2f(w2[n]), acc);
  }
  red[t] = acc;
  __syncthreads();
  for (int o = 64; o > 0; o >>= 1) { if (t < o) red[t] += red[t + o]; __syncthreads(); }
  if (t == 0) out[b] = __float2bfloat16(red[0] + bf2f(bout[0]));
}

typedef CUresult (*EncodeFn)(CUtensorMap*, CUtensorMapDataType, cuuint32_t, void*, const cuuint64_t*, const cuuint64_t*,
                             const cuuint32_t*, const cuuint32_t*, CUtensorMapInterleave, CUtensorMapSwizzle,
                             CUtensorMapL2promotion, CUtensorMapFloatOOBfill);

extern "C" void kernel_launch(void* const* d_in, const int* in_sizes, int n_in, void* d_out, int out_size) {
  const int* idx = (const int*)d_in[0];
  const bf16* table = (const bf16*)d_in[1];
  const bf16* ws = (const bf16*)d_in[2];
  const bf16* wout = (const bf16*)d_in[3];
  const bf16* w1 = (const bf16*)d_in[4];
  const bf16* b1 = (const bf16*)d_in[5];
  const bf16* w2 = (const bf16*)d_in[6];
  const bf16* bo = (const bf16*)d_in[7];
  bf16* out = (bf16*)d_out;

  static EncodeFn enc = nullptr;
  static Params P;
  static int n_sm = 0;
  if (!n_sm) {
    int dev = 0;
    cudaGetDevice(&dev);
    cudaDeviceGetAttribute(&n_sm, cudaDevAttrMultiProcessorCount, dev);
  }
  if (n_sm < NCTA + NHELP) {
    fallback_kernel<<<4096, 128, 0, cudaStreamPerThread>>>(idx, table, ws, wout, w1, b1, w2, bo, out);
    return;
  }
  if (!enc) {
    void* fn = nullptr;
    cudaDriverEntryPointQueryResult qr;
    cudaGetDriverEntryPoint("cuTensorMapEncodeTiled", &fn, cudaEnableDefault, &qr);
    enc = (EncodeFn)fn;
    cudaFuncSetAttribute(main_kernel, cudaFuncAttributeMaxDynamicSharedMemorySize, LAUNCH_SMEM);
    void* p;
    cudaGetSymbolAddress(&p, g_img); P.img = (unsigned char*)p;
    cudaGetSymbolAddress(&p, g_part); P.part = (unsigned long long*)p;
    cudaGetSymbolAddress(&p, g_ctr); P.ctr = (unsigned*)p;
    cudaGetSymbolAddress(&p, g_tabs); P.tabs = p;
    P.dk = make_desc(0, 128, 256, 0);
    P.dmn = make_desc(0, 8192, 1024, 1);
    for (int c = 0; c < NCTA; c++) P.role[c] = make_role(c);
  }
  P.idx = idx; P.table = table; P.ws = ws; P.wout = wout; P.b1 = b1; P.w2 = w2; P.bout = bo; P.out = out;
  TmaMaps tms;
  for (int h = 0; h < 4; h++) {
    const int c0 = (h >> 1) * 208 + (h & 1) * 96, nw = (h & 1) ? 112 : 96;
    cuuint64_t dims[5] = {(cuuint64_t)nw, 2, 4, 2, 26};
    cuuint64_t strides[4] = {832, 4 * 832, 2 * 832, 16 * 832};
    cuuint32_t box[5] = {64, 2, 4, 2, 4};
    cuuint32_t es[5] = {1, 1, 1, 1, 1};
    enc(&tms.m[h], CU_TENSOR_MAP_DATA_TYPE_BFLOAT16, 5, (void*)(w1 + c0), dims, strides, box, es,
        CU_TENSOR_MAP_INTERLEAVE_NONE, CU_TENSOR_MAP_SWIZZLE_128B, CU_TENSOR_MAP_L2_PROMOTION_L2_128B,
        CU_TENSOR_MAP_FLOAT_OOB_FILL_NONE);
  }
  main_kernel<<<NCTA + NHELP, 512, LAUNCH_SMEM, cudaStreamPerThread>>>(P, tms);
}
```

```cpp
#include <cuda_runtime.h>
#include <cuda_bf16.h>
#include <cuda.h>
#include <stdint.h>

typedef __nv_bfloat16 bf16;

constexpr int NF = 26;
constexpr int NCTA = 128;

constexpr int G0_KS = 24, G0_N = 56, G0_SLAB = G0_N * 32;
constexpr int L_KS = 43, L_SLAB = 1024;
constexpr int G0_BYTES = G0_KS * G0_SLAB;
constexpr int L_BYTES = L_KS * L_SLAB;
constexpr int IMG_BYTES = G0_BYTES + 3 * L_BYTES;

constexpr int W1_STAGES = 7;
constexpr int W1_STAGE_BYTES = 16384;
constexpr int OFF_LB = 0;
constexpr int OFF_LA = 44032;
constexpr int OFF_LC = 88064;
__host__ __device__ constexpr int w1_off(int st) { return st < 2 ? st * W1_STAGE_BYTES : OFF_LA + (st - 2) * W1_STAGE_BYTES; }
constexpr int OFF_G0 = 132096;
constexpr int OFF_IDX = 132096 + 16384;
constexpr int OFF_TAB = OFF_G0 + G0_BYTES;
constexpr int OFF_XOFF = OFF_TAB + 32000;
constexpr int OFF_BAR = OFF_XOFF + 6656;
constexpr int OFF_BW = OFF_BAR + 256;
constexpr int OFF_W2 = OFF_BW + 256;
constexpr int OFF_WTAB = OFF_W2 + 1792;
constexpr int OFF_EPOCH = OFF_WTAB + 256;
constexpr int OFF_STAB = (OFF_EPOCH + 16 + 127) / 128 * 128;
constexpr int OFF_LOFF = OFF_STAB + 3072 + 704;
constexpr int SMEM_BYTES = OFF_STAB + 4288;
static_assert(SMEM_BYTES <= 232448, "smem");

constexpr int BAR_W1FULL = 0  , BAR_W1FREE = 10  , BAR_W1DONE = 11  ,
              BAR_IMG = 14  , BAR_X0 = 18, BAR_SETUP = 19, BAR_EPOCH = 20, BAR_TABS = 21,
              BAR_Q = 22, BAR_STAB = 23, BAR_G0B = 24  , NBAR = 26;

struct TmaMaps { CUtensorMap m[4]; };
struct Params {
  const int* idx; const bf16* table; const bf16* ws; const bf16* wout; const bf16* b1; const bf16* w2; const bf16* bout;
  bf16* out;
  unsigned char* img; unsigned long long* part; unsigned* ctr; const void* tabs;
  uint64_t dk, dmn;
  uint2 role[NCTA];
};

__device__ __align__(1024) unsigned char g_img[IMG_BYTES];
__device__ unsigned long long g_part[NCTA * 128];
__device__ __align__(128) unsigned g_ctr[64];

__device__ __forceinline__ uint32_t smem_u32(const void* p) { return (uint32_t)__cvta_generic_to_shared(p); }
__device__ __forceinline__ bool elect_one() {
  uint32_t pred;
  asm volatile("{\n.reg .pred p;\nelect.sync _|p, 0xffffffff;\nselp.u32 %0, 1, 0, p;\n}\n" : "=r"(pred));
  return pred != 0;
}
__device__ __forceinline__ void mbar_init(uint32_t bar, uint32_t cnt) {
  asm volatile("mbarrier.init.shared::cta.b64 [%0], %1;" ::"r"(bar), "r"(cnt) : "memory");
}
__device__ __forceinline__ void mbar_expect_tx(uint32_t bar, uint32_t bytes) {
  asm volatile("mbarrier.arrive.expect_tx.shared::cta.b64 _, [%0], %1;" ::"r"(bar), "r"(bytes) : "memory");
}
__device__ __forceinline__ void mbar_arrive(uint32_t bar) {
  asm volatile("mbarrier.arrive.shared::cta.b64 _, [%0];" ::"r"(bar) : "memory");
}
__device__ __forceinline__ bool mbar_try(uint32_t bar, uint32_t parity) {
  uint32_t ok;
  asm volatile("{\n.reg .pred p;\nmbarrier.try_wait.parity.shared::cta.b64 p, [%1], %2;\nselp.u32 %0, 1, 0, p;\n}\n"
               : "=r"(ok) : "r"(bar), "r"(parity) : "memory");
  return ok != 0;
}
__device__ __forceinline__ void mbar_wait(uint32_t bar, uint32_t parity) {
#pragma unroll 1
  for (uint32_t it = 0; it < (1u << 26); it++)
    if (mbar_try(bar, parity)) return;
  __trap();
}
__device__ __forceinline__ void bulk_g2s(uint32_t dst, const void* src, uint32_t bytes, uint32_t bar) {
  asm volatile("cp.async.bulk.shared::cluster.global.mbarrier::complete_tx::bytes [%0], [%1], %2, [%3];"
               ::"r"(dst), "l"(src), "r"(bytes), "r"(bar) : "memory");
}
__device__ __forceinline__ void tma_2d(uint32_t dst, const CUtensorMap* tm, int x, int y, uint32_t bar) {
  asm volatile("cp.async.bulk.tensor.2d.shared::cluster.global.mbarrier::complete_tx::bytes [%0], [%1, {%3, %4}], [%2];"
               ::"r"(dst), "l"(tm), "r"(bar), "r"(x), "r"(y) : "memory");
}
__device__ __forceinline__ void cp_async16(uint32_t dst, const void* src) {
  asm volatile("cp.async.cg.shared.global [%0], [%1], 16;" ::"r"(dst), "l"(src) : "memory");
}
__device__ __forceinline__ void fence_proxy_async() { asm volatile("fence.proxy.async.shared::cta;" ::: "memory"); }
template <int ID, int N> __device__ __forceinline__ void named_bar_t() { asm volatile("bar.sync %0, %1;" ::"n"(ID), "n"(N) : "memory"); }
#define named_bar(id, n) named_bar_t<id, n>()

__device__ __forceinline__ void wg_fence() { asm volatile("wgmma.fence.sync.aligned;" ::: "memory"); }
__device__ __forceinline__ void wg_commit() { asm volatile("wgmma.commit_group.sync.aligned;" ::: "memory"); }
template <int N> __device__ __forceinline__ void wg_wait() { asm volatile("wgmma.wait_group.sync.aligned %0;" ::"n"(N) : "memory"); }
template <int N> __device__ __forceinline__ void reg_fence(float (&d)[N]) {
#pragma unroll
  for (int i = 0; i < N; i++) asm volatile("" : "+f"(d[i])::"memory");
}
constexpr uint32_t SMEM_BASE = 1024;
__host__ __device__ constexpr uint64_t make_desc(uint32_t off, uint32_t lbo, uint32_t sbo, uint32_t swz) {
  return (uint64_t)(((SMEM_BASE + off) & 0x3FFFF) >> 4) | ((uint64_t)(lbo >> 4) << 16) | ((uint64_t)(sbo >> 4) << 32) | ((uint64_t)swz << 62);
}

#define ACC4(d, o) "+f"(d[o]), "+f"(d[o + 1]), "+f"(d[o + 2]), "+f"(d[o + 3])
#define ACC8(d, o) ACC4(d, o), ACC4(d, o + 4)

__device__ __forceinline__ void wgmma_rs_n32(float (&d)[16], uint32_t a0, uint32_t a1, uint32_t a2, uint32_t a3, uint64_t db, int sc) {
  asm volatile("{\n.reg .pred p;\nsetp.ne.b32 p, %21, 0;\n"
               "wgmma.mma_async.sync.aligned.m64n32k16.f32.bf16.bf16 "
               "{%0,%1,%2,%3,%4,%5,%6,%7,%8,%9,%10,%11,%12,%13,%14,%15}, {%16,%17,%18,%19}, %20, p, 1, 1, 0;\n}\n"
               : ACC8(d, 0), ACC8(d, 8)
               : "r"(a0), "r"(a1), "r"(a2), "r"(a3), "l"(db), "r"(sc));
}
__device__ __forceinline__ void wgmma_rs_n56(float (&d)[28], uint32_t a0, uint32_t a1, uint32_t a2, uint32_t a3, uint64_t db, int sc) {
  asm volatile("{\n.reg .pred p;\nsetp.ne.b32 p, %33, 0;\n"
               "wgmma.mma_async.sync.aligned.m64n56k16.f32.bf16.bf16 "
               "{%0,%1,%2,%3,%4,%5,%6,%7,%8,%9,%10,%11,%12,%13,%14,%15,%16,%17,%18,%19,%20,%21,%22,%23,%24,%25,%26,%27}, "
               "{%28,%29,%30,%31}, %32, p, 1, 1, 0;\n}\n"
               : ACC8(d, 0), ACC8(d, 8), ACC8(d, 16), ACC4(d, 24)
               : "r"(a0), "r"(a1), "r"(a2), "r"(a3), "l"(db), "r"(sc));
}
__device__ __forceinline__ void wgmma_rs_n112_tb(float (&d)[56], uint32_t a0, uint32_t a1, uint32_t a2, uint32_t a3, uint64_t db, int sc) {
  asm volatile("{\n.reg .pred p;\nsetp.ne.b32 p, %61, 0;\n"
               "wgmma.mma_async.sync.aligned.m64n112k16.f32.bf16.bf16 "
               "{%0,%1,%2,%3,%4,%5,%6,%7,%8,%9,%10,%11,%12,%13,%14,%15,%16,%17,%18,%19,%20,%21,%22,%23,%24,%25,%26,%27,%28,%29,%30,%31,%32,%33,%34,%35,%36,%37,%38,%39,%40,%41,%42,%43,%44,%45,%46,%47,%48,%49,%50,%51,%52,%53,%54,%55}, "
               "{%56,%57,%58,%59}, %60, p, 1, 1, 1;\n}\n"
               : ACC8(d, 0), ACC8(d, 8), ACC8(d, 16), ACC8(d, 24), ACC8(d, 32), ACC8(d, 40), ACC8(d, 48)
               : "r"(a0), "r"(a1), "r"(a2), "r"(a3), "l"(db), "r"(sc));
}

__device__ __forceinline__ void wgmma_rs_n8(float (&d)[4], uint32_t a0, uint32_t a1, uint32_t a2, uint32_t a3, uint64_t db, int sc) {
  asm volatile("{\n.reg .pred p;\nsetp.ne.b32 p, %9, 0;\n"
               "wgmma.mma_async.sync.aligned.m64n8k16.f32.bf16.bf16 {%0,%1,%2,%3}, {%4,%5,%6,%7}, %8, p, 1, 1, 0;\n}\n"
               : ACC4(d, 0)
               : "r"(a0), "r"(a1), "r"(a2), "r"(a3), "l"(db), "r"(sc));
}
__device__ __forceinline__ uint32_t mul_lo(uint32_t v, uint32_t r) {
  __nv_bfloat162 a = *reinterpret_cast<__nv_bfloat162*>(&v), b = *reinterpret_cast<__nv_bfloat162*>(&r);
  __nv_bfloat162 c = __hmul2(__low2bfloat162(a), b);
  return *reinterpret_cast<uint32_t*>(&c);
}
__device__ __forceinline__ uint32_t mul_hi(uint32_t v, uint32_t r) {
  __nv_bfloat162 a = *reinterpret_cast<__nv_bfloat162*>(&v), b = *reinterpret_cast<__nv_bfloat162*>(&r);
  __nv_bfloat162 c = __hmul2(__high2bfloat162(a), b);
  return *reinterpret_cast<uint32_t*>(&c);
}
__device__ __forceinline__ uint32_t mul_ew(uint32_t v, uint32_t r) {
  __nv_bfloat162 a = *reinterpret_cast<__nv_bfloat162*>(&v), b = *reinterpret_cast<__nv_bfloat162*>(&r);
  __nv_bfloat162 c = __hmul2(a, b);
  return *reinterpret_cast<uint32_t*>(&c);
}
__device__ __forceinline__ uint32_t pack_bf16(float lo, float hi) {
  uint32_t r;
  asm("cvt.rn.bf16x2.f32 %0, %1, %2;" : "=r"(r) : "f"(hi), "f"(lo));
  return r;
}
__device__ __forceinline__ float bf2f(bf16 v) { return __bfloat162float(v); }
__device__ __forceinline__ float bflo(uint32_t w) { return __uint_as_float(w << 16); }
__device__ __forceinline__ float bfhi(uint32_t w) { return __uint_as_float(w & 0xffff0000u); }

__device__ __forceinline__ void st_img(uint32_t* p, uint32_t v) {
  asm volatile("st.relaxed.gpu.global.u32 [%0], %1;" ::"l"(p), "r"(v) : "memory");
}
__device__ __forceinline__ void fence_proxy_async_global() { asm volatile("fence.proxy.async.global;" ::: "memory"); }
__device__ __forceinline__ uint32_t ld_back(const uint32_t* p) {
  uint32_t v;
  asm volatile("ld.relaxed.gpu.global.u32 %0, [%1];" : "=r"(v) : "l"(p) : "memory");
  return v;
}
__host__ __device__ constexpr int Fq(int q, int t, int e) {
  if (t == 12) return 24 + e;
  const int u = (t + 3 * q) % 12;
  const int sw = (q >= 2 && u >= 6) ? 1 : 0;
  return 2 * u + (e ^ sw);
}
constexpr int M_ONE = 26, M_NONE = 27;
struct Mono { int f1, f2; };
__host__ __device__ constexpr Mono g0_mono(int s, int q, int e) {
  if (s < 30) { const int d = s / 6 + 1, a = (s % 6) >> 1; return {Fq(q, a, s & 1), Fq(q, a + d, e)}; }
  if (s < 33) return {Fq(q, s - 30, e), Fq(q, s - 24, e)};
  if (s < 35) return {Fq(q, s - 33, e), Fq(q, s - 33, e)};
  if (s == 35) return {Fq(q, e, 0), Fq(q, e, 1)};
  if (s == 36) return {Fq(q, 2, 0), Fq(q, 2, e)};
  if (s == 37) return e ? Mono{Fq(q, 2, 1), Fq(q, 2, 1)} : Mono{M_NONE, M_NONE};
  if (s < 44) return {24 + ((s - 38) & 1), Fq(q, (s - 38) >> 1, e)};
  if (s < 47) return {Fq(q, s - 44, e), M_ONE};
  if (q == 0) return {24, 24 + e};
  if (q == 1) return e ? Mono{25, 25} : Mono{M_NONE, M_NONE};
  if (q == 2) return {24 + e, M_ONE};
  return e ? Mono{M_NONE, M_NONE} : Mono{M_ONE, M_ONE};
}
constexpr int QM_RS = 40;
constexpr int O_ZERO = 31 * QM_RS + 39, O_CONST = 30 * QM_RS + 39;
struct StaticTabs {
  uint32_t otab[48 * 8];
  uint32_t x1tab[48 * 8];
  uint16_t ltab[88 * 4];
  uint16_t loff[32 * 8];
};
constexpr StaticTabs make_tabs() {
  StaticTabs T{};
  for (int s = 0; s < 48; s++)
    for (int q = 0; q < 4; q++)
      for (int e = 0; e < 2; e++) {
        const Mono m = g0_mono(s, q, e);
        const bool none = m.f1 == M_NONE, cs = m.f1 == M_ONE, lin = m.f2 == M_ONE;
        const uint32_t o1 = none ? O_ZERO : cs ? O_CONST : m.f1 * QM_RS + (lin ? 26 : m.f2);
        const uint32_t o2 = (none || cs || lin || m.f1 == m.f2) ? O_ZERO : m.f2 * QM_RS + m.f1;
        T.otab[s * 8 + q * 2 + e] = o1 | (o2 << 16);
        const bool qd = m.f1 < NF && m.f2 < NF;
        const uint32_t y1 = qd ? m.f1 * NF + m.f2 : 0xffffu;
        const uint32_t y2 = (qd && m.f1 != m.f2) ? m.f2 * NF + m.f1 : 0xffffu;
        T.x1tab[s * 8 + q * 2 + e] = y1 | (y2 << 16);
      }
  for (int s = 0; s < 88; s++)
    for (int q = 0; q < 4; q++) {
      uint16_t v = 0;
      if (s < 85) {
        const bool ex = s >= 78;
        const int a = s / 13, k = s - 78;
        const int tt = ex ? ((k < 3) ? k : (k < 6 ? k + 3 : 12)) : s % 13;
        const int in = ex ? 24 + (q >> 1) : 8 * (a >> 1) + 2 * q + (a & 1);
        const bool valid = !(ex && tt == 12 && (q & 1));
        const int f0 = Fq(q, tt, 0);
        v = (uint16_t)((f0 >> 1) | ((f0 & 1) << 4) | ((valid ? 1 : 0) << 5) | (in << 6));
      }
      T.ltab[s * 4 + q] = v;
    }
  for (int ln = 0; ln < 32; ln++)
    for (int k = 0; k < 8; k++) {
      const int m = ln >> 3, r = ln & 7;
      const int tt = (k < 6) ? 2 * k + (m >> 1) : 12;
      T.loff[ln * 8 + k] = (uint16_t)(2 * Fq(r >> 1, tt, r & 1));
    }
  return T;
}
static_assert(sizeof(StaticTabs) == 4288, "tabs");
__device__ __align__(128) const StaticTabs g_tabs = make_tabs();

constexpr int SETUP_WARPS = 7;
constexpr int WL_BYTES = NF * NF * NF * 2;
static inline uint2 make_role(int cta) {
  int kind = 5, grp = 0, j = 0, off = 0, bytes = 0;
  const int c = cta, SL = NF * NF * 2;
  if (c < 56) { kind = 1 + c / 28; grp = (c % 28) / 7; j = c % 7; off = kind * WL_BYTES + grp * 8 * SL; bytes = (grp < 3 ? 8 : 2) * SL; }
  else if (c < 80) { kind = 0; grp = (c - 56) / 8; j = (c - 56) % 8; off = 3 * WL_BYTES + grp * 8 * SL; bytes = 8 * SL; }
  else if (c < 83) { kind = 0; grp = 3; j = c - 80; off = 3 * WL_BYTES + 24 * SL; bytes = 2 * SL; }
  else if (c < 95) { kind = 3; grp = (c - 83) / 4; j = (c - 83) % 4; off = grp * 8 * SL; bytes = 8 * SL; }
  const int delta = off & 127;
  uint2 r;
  r.x = (uint32_t)(off - delta) | ((uint32_t)kind << 24);
  r.y = (uint32_t)(bytes + delta) | ((uint32_t)delta << 16) | ((uint32_t)grp << 24) | ((uint32_t)j << 28);
  return r;
}

__device__ __forceinline__ uint32_t layer_row(int li, int grp, int r, int lane, const unsigned char* raw, const StaticTabs* T,
                                              uint32_t bar, uint32_t tbar, const bf16* __restrict__ wout, uint32_t* img32) {
  const int ks = li ? r : 13 * grp + (r >> 2), ng = li ? grp : (r & 3);
  if (ks >= 43 || (!li && grp < 3 && r >= 52)) return 0;
  const uint32_t* w32 = reinterpret_cast<const uint32_t*>(raw);
  const int n8 = lane >> 2, q = lane & 3;
  const int o = (ng < 3) ? ng * 8 + n8 : 24 + (n8 >> 2);
  const bool vo = (ng < 3) || !(n8 & 1);
  const int ob = li ? (o - 8 * grp) * 338 : o * 13 - 8 * grp * 338;
  const int si = li ? 13 : 338;
  uint32_t bias = 0;
  if (vo && ks == 42 && li == 0 && q == 0) bias = (uint32_t)__ldg(reinterpret_cast<const unsigned short*>(wout) + 2 * NF + o);
  uint32_t* dst = img32 + G0_BYTES / 4 + li * (L_BYTES / 4) + (ks * 4 + ng) * 64 + lane;
  mbar_wait(tbar, 0);
  const uint32_t e0 = T->ltab[8 * ks + q], e1 = T->ltab[8 * ks + 4 + q];
  const bool v0 = vo && (e0 & 32), v1 = vo && (e1 & 32);
  const int s0 = v0 ? ob + (e0 >> 6) * si + (e0 & 15) : 0, s1 = v1 ? ob + (e1 >> 6) * si + (e1 & 15) : 0;
  mbar_wait(bar, 0);
  uint32_t w0 = w32[s0], w1 = w32[s1];
  w0 = (e0 & 16) ? __funnelshift_l(w0, w0, 16) : w0;
  w1 = (e1 & 16) ? __funnelshift_l(w1, w1, 16) : w1;
  w0 = v0 ? w0 : 0u;
  w1 = v1 ? w1 : bias;
  st_img(dst, w0); st_img(dst + 32, w1);
  const uint32_t chk = (ld_back(dst) ^ w0) | (ld_back(dst + 32) ^ w1);
  fence_proxy_async_global();
  return chk;
}
__device__ __forceinline__ float x1_val(const unsigned short* wh, uint32_t e) {
  const uint32_t a = e & 0xffff, b = e >> 16;
  const uint32_t x = wh[a == 0xffff ? 0 : a], y = wh[b == 0xffff ? 0 : b];
  return (a == 0xffff ? 0.f : __uint_as_float(x << 16)) + (b == 0xffff ? 0.f : __uint_as_float(y << 16));
}
__device__ __forceinline__ uint32_t x1_row(int ng, int ks, int lane, const unsigned char* raw, const StaticTabs* T, uint32_t bar, uint32_t tbar, uint32_t* img32) {
  if (ks >= 24) return 0;
  const int n8 = lane >> 2, q = lane & 3;
  const unsigned short* wh = reinterpret_cast<const unsigned short*>(raw) + n8 * (NF * NF);
  uint32_t* dst = img32 + ks * (G0_SLAB / 4) + ng * 64 + lane;
  mbar_wait(tbar, 0);
  const uint2 ea = *reinterpret_cast<const uint2*>(&T->x1tab[16 * ks + 2 * q]), eb = *reinterpret_cast<const uint2*>(&T->x1tab[16 * ks + 8 + 2 * q]);
  mbar_wait(bar, 0);
  const uint32_t w0 = pack_bf16(x1_val(wh, ea.x), x1_val(wh, ea.y)), w1 = pack_bf16(x1_val(wh, eb.x), x1_val(wh, eb.y));
  st_img(dst, w0); st_img(dst + 32, w1);
  const uint32_t chk = (ld_back(dst) ^ w0) | (ld_back(dst + 32) ^ w1);
  fence_proxy_async_global();
  return chk;
}

constexpr int NHELP = 4;
constexpr int H_MS = 32 * QM_RS + 4;
constexpr int H_W5 = 0, H_W4 = 35328, H_W0 = 70656, H_TAB = 73472, H_B = 77824, H_M = 82944, H_XE = H_M + 8 * H_MS * 4, H_BAR = H_XE + 1536;
__device__ __forceinline__ int wf_off(int b, int h) { return (b >> 3) * 512 + (h >> 3) * 128 + (b & 7) * 16 + (h & 7) * 2; }
__device__ __forceinline__ void helper_role(int hk, const Params& P, unsigned char* smem, uint32_t sb) {
  const int t = threadIdx.x, warp = __shfl_sync(0xffffffffu, t >> 5, 0), lane = t & 31;
  const uint32_t d5bar = sb + H_BAR, d4bar = sb + H_BAR + 8, tbar = sb + H_BAR + 16;
  const unsigned char* wsb = reinterpret_cast<const unsigned char*>(P.ws);
  unsigned char* WB = smem + H_B;
  float* M = reinterpret_cast<float*>(smem + H_M);
  constexpr uint32_t W5B = WL_BYTES + ((5 * WL_BYTES) & 127), W4B = WL_BYTES + ((4 * WL_BYTES) & 127);
  if (warp < 3 && elect_one()) {
    mbar_init(sb + H_BAR + 8 * warp, 1);
    asm volatile("fence.mbarrier_init.release.cluster;" ::: "memory");
    if (warp == 0) {
      mbar_expect_tx(d5bar, W5B);
#pragma unroll
      for (int c = 0; c < 5; c++)
        bulk_g2s(sb + H_W5 + c * 8192, wsb + ((5 * WL_BYTES) & ~127) + c * 8192, c < 4 ? 8192u : W5B - 4 * 8192, d5bar);
    }
  }
  reinterpret_cast<uint32_t*>(WB)[t] = 0;
  __syncthreads();
  if (warp >= 5 && warp < 12 && elect_one()) {
    if (warp < 10) {
      const int c = warp - 5;
      if (c == 0) mbar_expect_tx(d4bar, W4B + (hk == 3 ? 2768 : 0));
      bulk_g2s(sb + H_W4 + c * 8192, wsb + ((4 * WL_BYTES) & ~127) + c * 8192, c < 4 ? 8192u : W4B - 4 * 8192, d4bar);
    } else if (warp == 10) {
      mbar_expect_tx(tbar, sizeof(StaticTabs));
      bulk_g2s(sb + H_TAB, P.tabs, sizeof(StaticTabs), tbar);
    } else if (hk == 3) {
      bulk_g2s(sb + H_W0, wsb + ((24 * NF * NF * 2) & ~127), 2768, d4bar);
    }
  }
  const unsigned short* wo16 = reinterpret_cast<const unsigned short*>(P.wout);
  uint32_t c5[13];
#pragma unroll
  for (int k = 0; k < 13; k++) c5[k] = __ldg(reinterpret_cast<const uint32_t*>(P.wout + 5 * NF) + k);
  unsigned short wv = 0;
  const int io0 = (hk < 3) ? 8 * hk : 24;
  if (t >= 352 && t < 352 + NF) wv = __ldg(wo16 + 4 * NF + t - 352);
  else if (t >= 384 && t < 392 && io0 + t - 384 < NF) wv = __ldg(wo16 + 3 * NF + io0 + t - 384);
  const StaticTabs* T = reinterpret_cast<const StaticTabs*>(smem + H_TAB);
  const int n8 = lane >> 2, q = lane & 3, g = n8;
  const int fil = (hk < 3) ? n8 : (n8 >> 2);
  const bool fx1 = (hk == 3) && !(n8 & 1);
  uint32_t* dst = reinterpret_cast<uint32_t*>(P.img) + (warp >> 1) * (G0_SLAB / 4) + (warp & 1) * 32 + (3 + hk) * 64 + lane;
  if (t >= 352 && t < 352 + NF) *reinterpret_cast<unsigned short*>(WB + wf_off(26, t - 352)) = wv;
  if (t >= 384 && t < 392) { M[(t - 384) * H_MS + O_ZERO] = 0.f; M[(t - 384) * H_MS + O_CONST] = __uint_as_float((uint32_t)wv << 16); }
  mbar_wait(d5bar, 0);
  if (t < 338) {
    const uint32_t* w5 = reinterpret_cast<const uint32_t*>(smem + H_W5 + ((5 * WL_BYTES) & 127)) + t;
    float s0 = 0.f, s1 = 0.f, s2 = 0.f, s3 = 0.f;
#pragma unroll
    for (int k = 0; k < 13; k++) {
      const uint32_t wa = w5[(2 * k) * 338], wb = w5[(2 * k + 1) * 338];
      const float ca = bflo(c5[k]), cb = bfhi(c5[k]);
      s0 = fmaf(ca, bflo(wa), s0); s1 = fmaf(ca, bfhi(wa), s1);
      s2 = fmaf(cb, bflo(wb), s2); s3 = fmaf(cb, bfhi(wb), s3);
    }
    const int h = (t * 79) >> 10, tp = t - 13 * h;
    *reinterpret_cast<bf16*>(WB + wf_off(2 * tp, h)) = __float2bfloat16(s0 + s2);
    *reinterpret_cast<bf16*>(WB + wf_off(2 * tp + 1, h)) = __float2bfloat16(s1 + s3);
  }
  fence_proxy_async();
  mbar_wait(tbar, 0);
  uint2 fot[3];
#pragma unroll
  for (int r = 0; r < 3; r++) fot[r] = *reinterpret_cast<const uint2*>(&T->otab[(warp + 16 * r) * 8 + q * 2]);
  mbar_wait(d4bar, 0);
  const int wgi = warp >> 2, il = 2 * wgi + ((warp >> 1) & 1), mt = warp & 1;
  const bool mma_wg = (hk < 3) || (wgi == 0);
  uint32_t a[2][4];
  if (mma_wg) {
    const unsigned short* A = reinterpret_cast<const unsigned short*>(smem + H_W4 + ((4 * WL_BYTES) & 127)) + (io0 + il) * NF + mt * 16 + g;
#pragma unroll
    for (int kk = 0; kk < 2; kk++) {
#pragma unroll
      for (int jj = 0; jj < 4; jj++) {
        const int k = kk * 16 + 2 * q + (jj >> 1) * 8, mo = (jj & 1) * 8;
        const int kc = (k < NF) ? k : 0;
        const uint32_t lo = A[kc * (NF * NF) + mo], hi = A[(kc + 1) * (NF * NF) + mo];
        a[kk][jj] = (k < NF) ? (lo | (hi << 16)) : 0u;
      }
    }
  }
  if (hk == 3) {
    const int u0 = (warp >= 4) ? t - 128 : -1;
    if (u0 >= 0) {
      const int sl = u0 >> 3, xl = (u0 >> 2) & 1, xq = u0 & 3;
      const uint2 xt = *reinterpret_cast<const uint2*>(&T->x1tab[sl * 8 + xq * 2]);
      const unsigned short* wh = reinterpret_cast<const unsigned short*>(smem + H_W0 + ((24 * NF * NF * 2) & 127)) + xl * (NF * NF);
      reinterpret_cast<uint32_t*>(smem + H_XE)[u0] = pack_bf16(x1_val(wh, xt.x), x1_val(wh, xt.y));
    }
  }
  __syncthreads();
  if (mma_wg) {
    float c[16];
    wg_fence();
    wgmma_rs_n32(c, a[0][0], a[0][1], a[0][2], a[0][3], make_desc(H_B, 128, 512, 0), 0);
    wgmma_rs_n32(c, a[1][0], a[1][1], a[1][2], a[1][3], make_desc(H_B + 256, 128, 512, 0), 1);
    wg_commit();
    wg_wait<0>();
    reg_fence(c);
    float* Mi = M + il * H_MS;
#pragma unroll
    for (int n = 0; n < 4; n++) {
      *reinterpret_cast<float2*>(&Mi[(mt * 16 + g) * QM_RS + n * 8 + 2 * q]) = make_float2(c[4 * n], c[4 * n + 1]);
      *reinterpret_cast<float2*>(&Mi[(mt * 16 + g + 8) * QM_RS + n * 8 + 2 * q]) = make_float2(c[4 * n + 2], c[4 * n + 3]);
    }
  }
  __syncthreads();
  uint32_t val[3], chk = 0;
#pragma unroll
  for (int r = 0; r < 3; r++) {
    const float* Mf = M + fil * H_MS;
    const float v0 = Mf[fot[r].x & 0xffff] + Mf[fot[r].x >> 16], v1 = Mf[fot[r].y & 0xffff] + Mf[fot[r].y >> 16];
    const uint32_t xe = reinterpret_cast<const uint32_t*>(smem + H_XE)[(warp + 16 * r) * 8 + (n8 >> 2) * 4 + q];
    val[r] = fx1 ? xe : pack_bf16(v0, v1);
    st_img(dst + r * 8 * (G0_SLAB / 4), val[r]);
  }
#pragma unroll
  for (int r = 0; r < 3; r++) chk |= ld_back(dst + r * 8 * (G0_SLAB / 4)) ^ val[r];
  fence_proxy_async_global();
  if (__any_sync(0xffffffffu, chk != 0)) __trap();
  __syncthreads();
  if (t == 0) asm volatile("red.relaxed.gpu.global.add.u32 [%0], 1;" ::"l"(P.ctr + 32) : "memory");
}

template <int S>
__device__ __forceinline__ uint32_t l_prod(const uint32_t (&vp)[4], const uint32_t (&X)[13]) {
  if constexpr (S < 78) {
    constexpr int a = S / 13, t = S % 13;
    return (a & 1) ? mul_hi(vp[a >> 1], X[t]) : mul_lo(vp[a >> 1], X[t]);
  } else if constexpr (S < 85) {
    constexpr int k = S - 78;
    constexpr int t = (k < 3) ? k : (k < 6 ? k + 3 : 12);
    return mul_lo(vp[3], X[t]);
  } else {
    return 0x00003F80u;
  }
}
template <int S>
__device__ __forceinline__ uint32_t g0_prod(const uint32_t (&X)[13], uint32_t selU, uint32_t selV) {
  if constexpr (S < 30) {
    constexpr int d = S / 6 + 1, a = (S % 6) >> 1;
    return (S & 1) ? mul_hi(X[a], X[a + d]) : mul_lo(X[a], X[a + d]);
  } else if constexpr (S < 33) {
    return mul_ew(X[S - 30], X[S - 24]);
  } else if constexpr (S < 35) {
    return mul_ew(X[S - 33], X[S - 33]);
  } else if constexpr (S == 35) {
    return mul_ew(__byte_perm(X[0], X[1], 0x5410), __byte_perm(X[0], X[1], 0x7632));
  } else if constexpr (S == 36) {
    return mul_lo(X[2], X[2]);
  } else if constexpr (S == 37) {
    return mul_hi(X[2], X[2]);
  } else if constexpr (S < 44) {
    constexpr int a = (S - 38) >> 1;
    return ((S - 38) & 1) ? mul_hi(X[12], X[a]) : mul_lo(X[12], X[a]);
  } else if constexpr (S < 47) {
    return X[S - 44];
  } else {
    return mul_ew(__byte_perm(X[12], 0x3F803F80u, selU), __byte_perm(X[12], 0x3F803F80u, selV));
  }
}

constexpr int NBK = 4;

template <int KS, int KE>
__device__ __forceinline__ void l_fill(uint32_t (*A)[4], const uint32_t (&vp)[2][4], const uint32_t (&X)[2][13]) {
  A[0][0] = l_prod<2 * KS>(vp[0], X[0]);
  A[0][1] = l_prod<2 * KS>(vp[1], X[1]);
  A[0][2] = l_prod<2 * KS + 1>(vp[0], X[0]);
  A[0][3] = l_prod<2 * KS + 1>(vp[1], X[1]);
  if constexpr (KS + 1 < KE) l_fill<KS + 1, KE>(A + 1, vp, X);
}
template <int KS, int OFF>
__device__ __forceinline__ void layer_rec(float (&d)[16], const uint32_t (&vp)[2][4], const uint32_t (&X)[2][13], uint64_t dk) {
  constexpr int KE = (KS + NBK < L_KS) ? KS + NBK : L_KS;
  uint32_t A[NBK][4];
  l_fill<KS, KE>(A, vp, X);
  wg_fence();
#pragma unroll
  for (int k = 0; k < KE - KS; k++)
    wgmma_rs_n32(d, A[k][0], A[k][1], A[k][2], A[k][3], dk + (uint64_t)((OFF + (KS + k) * L_SLAB) >> 4), (KS + k) > 0);
  wg_commit();
  if constexpr (KE < L_KS) {
    wg_wait<1>();
    layer_rec<KE, OFF>(d, vp, X, dk);
  }
}
template <int OFF, int NK>
__device__ __forceinline__ void layer_first(float (&d)[16], const uint32_t (&vp)[2][4], const uint32_t (&X)[2][13], uint64_t dk) {
  uint32_t A[NK][4];
  l_fill<0, NK>(A, vp, X);
  wg_fence();
#pragma unroll
  for (int k = 0; k < NK; k++) wgmma_rs_n32(d, A[k][0], A[k][1], A[k][2], A[k][3], dk + (uint64_t)((OFF + k * L_SLAB) >> 4), k > 0);
  wg_commit();
}
template <int KS, int KE>
__device__ __forceinline__ void g0_fill(uint32_t (*A)[4], const uint32_t (&X)[2][13], uint32_t selU, uint32_t selV) {
  A[0][0] = g0_prod<2 * KS>(X[0], selU, selV);
  A[0][1] = g0_prod<2 * KS>(X[1], selU, selV);
  A[0][2] = g0_prod<2 * KS + 1>(X[0], selU, selV);
  A[0][3] = g0_prod<2 * KS + 1>(X[1], selU, selV);
  if constexpr (KS + 1 < KE) g0_fill<KS + 1, KE>(A + 1, X, selU, selV);
}
template <int B0>
__device__ __forceinline__ void g0_rec(float (&d)[28], const uint32_t (&X)[2][13], uint32_t selU, uint32_t selV, uint64_t dk, uint32_t bar2, bool first) {
  constexpr int KS = B0 * NBK;
  if constexpr (KS == 8) { if (first) mbar_wait(bar2, 0); }
  if constexpr (KS == 16) { if (first) mbar_wait(bar2 + 8, 0); }
  constexpr int KE = (KS + NBK < G0_KS) ? KS + NBK : G0_KS;
  uint32_t A[NBK][4];
  g0_fill<KS, KE>(A, X, selU, selV);
  wg_fence();
#pragma unroll
  for (int k = 0; k < KE - KS; k++)
    wgmma_rs_n56(d, A[k][0], A[k][1], A[k][2], A[k][3], dk + (uint64_t)((OFF_G0 + (KS + k) * G0_SLAB) >> 4), (KS + k) > 0);
  wg_commit();
  if constexpr (KE < G0_KS) {
    wg_wait<1>();
    g0_rec<B0 + 1>(d, X, selU, selV, dk, bar2, first);
  }
}

__device__ __forceinline__ void ldsm_x4_t(uint32_t addr, uint32_t& r0, uint32_t& r1, uint32_t& r2, uint32_t& r3) {
  asm volatile("ldmatrix.sync.aligned.m8n8.x4.trans.shared.b16 {%0,%1,%2,%3}, [%4];"
               : "=r"(r0), "=r"(r1), "=r"(r2), "=r"(r3) : "r"(addr) : "memory");
}
__device__ __forceinline__ void ldsm_x2_t(uint32_t addr, uint32_t& r0, uint32_t& r1) {
  asm volatile("ldmatrix.sync.aligned.m8n8.x2.trans.shared.b16 {%0,%1}, [%2];" : "=r"(r0), "=r"(r1) : "r"(addr) : "memory");
}
__device__ __forceinline__ float tanh_fast(float x) { float y; asm("tanh.approx.f32 %0, %1;" : "=f"(y) : "f"(x)); return y; }

__device__ __forceinline__ uint32_t gelu2_pair(float lo, float hi, uint32_t bias) {
  uint32_t x = pack_bf16(lo, hi), t, u;
  asm("add.rn.bf16x2 %0, %0, %1;" : "+r"(x) : "r"(bias));
  asm("mul.rn.bf16x2 %0, %1, %1;" : "=r"(t) : "r"(x));
  asm("fma.rn.bf16x2 %0, %0, %1, %2;" : "+r"(t) : "r"(0x3D123D12u), "r"(0x3F4C3F4Cu));
  asm("mul.rn.bf16x2 %0, %1, %2;" : "=r"(u) : "r"(x), "r"(t));
  asm("tanh.approx.bf16x2 %0, %0;" : "+r"(u));
  asm("fma.rn.bf16x2 %0, %1, %0, %1;" : "+r"(u) : "r"(x));
  return u;
}

__device__ __forceinline__ void ldsm_x4(uint32_t addr, uint32_t (&r)[4]) {
  asm volatile("ldmatrix.sync.aligned.m8n8.x4.shared.b16 {%0,%1,%2,%3}, [%4];"
               : "=r"(r[0]), "=r"(r[1]), "=r"(r[2]), "=r"(r[3]) : "r"(addr) : "memory");
}
__device__ __forceinline__ uint32_t lds_u16(uint32_t addr) {
  unsigned short v;
  asm volatile("ld.shared.u16 %0, [%1];" : "=h"(v) : "r"(addr) : "memory");
  return v;
}
__device__ __forceinline__ uint32_t lds_u32(uint32_t addr) {
  uint32_t v;
  asm volatile("ld.shared.u32 %0, [%1];" : "=r"(v) : "r"(addr) : "memory");
  return v;
}

__global__ void __launch_bounds__(512, 1)
main_kernel(const __grid_constant__ Params P, const __grid_constant__ TmaMaps tms) {
  extern __shared__ __align__(1024) unsigned char smem[];
  const uint32_t sb = smem_u32(smem);
  const int tid = threadIdx.x, warp = __shfl_sync(0xffffffffu, tid >> 5, 0), lane = tid & 31;
  if (blockIdx.x < NHELP) {
    helper_role(blockIdx.x, P, smem, sb);
    return;
  }
  const int cta = blockIdx.x - NHELP, nq = cta & 3, grp = cta >> 2;
  const uint2 role = P.role[cta];
  const uint32_t bar0 = sb + OFF_BAR;
  auto BAR = [&](int i) { return bar0 + 8 * i; };
  const int wg = warp >> 2, w4 = warp & 3, g = lane >> 2, q = lane & 3;
  const uint64_t dk = P.dk;

  if (tid < 256) {
    const unsigned char* isrc = reinterpret_cast<const unsigned char*>(P.idx + grp * 128 * NF);
#pragma unroll
    for (int k = 0; k < 4; k++) {
      const int c = tid + 256 * k;
      if (c < 832) cp_async16(sb + OFF_IDX + c * 16, isrc + c * 16);
    }
    asm volatile("cp.async.commit_group;" ::: "memory");
#pragma unroll
    for (int k = 0; k < 8; k++) {
      const int c = tid + 256 * k;
      if (c < 2000) cp_async16(sb + OFF_TAB + ((c ^ ((c >> 3) & 1)) << 4), reinterpret_cast<const unsigned char*>(P.table) + c * 16);
    }
    asm volatile("cp.async.commit_group;" ::: "memory");
  }
  if (elect_one()) {
    mbar_init(BAR(warp), (warp == BAR_W1FREE || warp == BAR_W1DONE) ? 2 : 1);
    if (warp < NBAR - 16)
      mbar_init(BAR(16 + warp), (16 + warp == BAR_X0) ? 256 : (16 + warp == BAR_SETUP) ? SETUP_WARPS : (16 + warp == BAR_TABS) ? 224 : 1);
    asm volatile("fence.mbarrier_init.release.cluster;" ::: "memory");
  }
  __syncthreads();

  if (warp == 15) {
    if (elect_one()) {
      mbar_expect_tx(BAR(BAR_STAB), sizeof(StaticTabs));
      bulk_g2s(sb + OFF_STAB, P.tabs, sizeof(StaticTabs), BAR(BAR_STAB));
      if ((sb & 0x3FFFF) != SMEM_BASE) __trap();
      const CUtensorMap* tm0 = &tms.m[nq];
      asm volatile("prefetch.tensormap [%0];" ::"l"(tm0) : "memory");
#pragma unroll
      for (int st = 0; st < W1_STAGES; st++) {
        if (st == 1 && (role.x >> 24) < 5) mbar_wait(BAR(BAR_Q), 0);
        mbar_expect_tx(BAR(BAR_W1FULL + st), W1_STAGE_BYTES);
        tma_2d(sb + w1_off(st), tm0, 0, st * 64, BAR(BAR_W1FULL + st));
        tma_2d(sb + w1_off(st) + 8192, tm0, 64, st * 64, BAR(BAR_W1FULL + st));
      }
      mbar_wait(BAR(BAR_EPOCH), 0);
      const unsigned epoch_p = lds_u32(sb + OFF_EPOCH);
      auto wait_ctr = [&](const unsigned* ctr, unsigned target) {
        unsigned v;
        uint32_t it = 0;
#pragma unroll 1
        do {
          asm volatile("ld.relaxed.gpu.global.u32 %0, [%1];" : "=r"(v) : "l"(ctr) : "memory");
          if (++it > (1u << 22)) __trap();
        } while ((int)(v - target) < 0);
      };
      wait_ctr(P.ctr + 32, epoch_p << 4);
      mbar_wait(BAR(BAR_X0), 0);
#pragma unroll
      for (int i = 0; i < 6; i++) {
        const uint32_t bar = i < 2 ? BAR(BAR_IMG + 0) : BAR(BAR_G0B + (i - 2) / 2);
        if (!(i & 1)) mbar_expect_tx(bar, G0_BYTES / 3);
        bulk_g2s(sb + OFF_G0 + i * (G0_BYTES / 6), P.img + i * (G0_BYTES / 6), G0_BYTES / 6, bar);
      }
      wait_ctr(P.ctr, epoch_p << 7);
      mbar_wait(BAR(BAR_W1FREE), 0);
      mbar_expect_tx(BAR(BAR_IMG + 2), L_BYTES);
#pragma unroll
      for (int i = 0; i < 4; i++)
        bulk_g2s(sb + OFF_LB + i * (L_BYTES / 4), P.img + G0_BYTES + L_BYTES + i * (L_BYTES / 4), L_BYTES / 4, BAR(BAR_IMG + 2));
      mbar_wait(BAR(BAR_W1DONE), 0);
      mbar_expect_tx(BAR(BAR_IMG + 1), L_BYTES);
      mbar_expect_tx(BAR(BAR_IMG + 3), L_BYTES);
#pragma unroll
      for (int i = 0; i < 2; i++)
        bulk_g2s(sb + OFF_LA + i * (L_BYTES / 2), P.img + G0_BYTES + i * (L_BYTES / 2), L_BYTES / 2, BAR(BAR_IMG + 1));
#pragma unroll
      for (int i = 0; i < 2; i++)
        bulk_g2s(sb + OFF_LC + i * (L_BYTES / 2), P.img + G0_BYTES + 2 * L_BYTES + i * (L_BYTES / 2), L_BYTES / 2, BAR(BAR_IMG + 3));
    }
    __syncwarp();
    mbar_wait(BAR(BAR_X0), 0);
    mbar_wait(BAR(BAR_TABS), 0);
  } else if (wg < 2) {
    asm volatile("cp.async.wait_group 1;" ::: "memory");
    named_bar(1, 256);
#pragma unroll
    for (int k = 0; k < 7; k++) {
      const int p = tid + 256 * k;
      if (p < 64 * NF) {
        const uint2 v = reinterpret_cast<const uint2*>(smem + OFF_IDX)[p];
        const uint32_t o0 = v.x * 32 + ((v.x >> 2) & 1) * 16, o1 = v.y * 32 + ((v.y >> 2) & 1) * 16;
        reinterpret_cast<uint32_t*>(smem + OFF_XOFF)[p] = o0 | (o1 << 16);
      }
    }
    asm volatile("cp.async.wait_all;" ::: "memory");
    mbar_arrive(BAR(BAR_X0));
    mbar_wait(BAR(BAR_X0), 0);
    float acc[56];
    {
      const uint32_t xo = sb + OFF_XOFF + (wg * 64 + w4 * 16 + (lane & 15)) * 52;
      const uint32_t tb = sb + OFF_TAB, hx = (lane >> 4) << 4;
      const uint64_t db0 = P.dmn;
      uint32_t A[3][2][4];
#pragma unroll
      for (int pr = 0; pr < 2; pr++) {
        const uint32_t oa = lds_u32(xo + 4 * pr);
        ldsm_x4(tb + ((oa & 0xffff) ^ hx), A[pr][0]); ldsm_x4(tb + ((oa >> 16) ^ hx), A[pr][1]);
      }
#pragma unroll
      for (int pr = 0; pr < 13; pr++) {
        const int st = pr >> 1;
        uint32_t oa = 0;
        if (pr + 2 < 13) oa = lds_u32(xo + 4 * (pr + 2));
        if (!(pr & 1)) mbar_wait(BAR(BAR_W1FULL + st), 0);
        const uint64_t db = db0 + (uint64_t)((w1_off(st) + (pr & 1) * 4096) >> 4);
        wg_fence();
        wgmma_rs_n112_tb(acc, A[pr % 3][0][0], A[pr % 3][0][1], A[pr % 3][0][2], A[pr % 3][0][3], db, pr > 0);
        wgmma_rs_n112_tb(acc, A[pr % 3][1][0], A[pr % 3][1][1], A[pr % 3][1][2], A[pr % 3][1][3], db + (2048 >> 4), 1);
        wg_commit();
        wg_wait<1>();
        if (pr == 4 && (tid & 127) == 0) mbar_arrive(BAR(BAR_W1FREE));
        if (pr + 2 < 13) { ldsm_x4(tb + ((oa & 0xffff) ^ hx), A[(pr + 2) % 3][0]); ldsm_x4(tb + ((oa >> 16) ^ hx), A[(pr + 2) % 3][1]); }
      }
      wg_wait<0>();
      reg_fence(acc);
      if ((tid & 127) == 0) mbar_arrive(BAR(BAR_W1DONE));
    }
    float dot[4];
    {
      mbar_wait(BAR(BAR_TABS), 0);
      uint32_t bb[16];
      const uint4* bp = reinterpret_cast<const uint4*>(smem + OFF_BW + q * 64);
#pragma unroll
      for (int i = 0; i < 4; i++) { const uint4 v = bp[i]; bb[4 * i] = v.x; bb[4 * i + 1] = v.y; bb[4 * i + 2] = v.z; bb[4 * i + 3] = v.w; }
      uint32_t H[14][2];
#pragma unroll
      for (int c = 0; c < 14; c++) {
        H[c][0] = gelu2_pair(acc[4 * c], acc[4 * c + 1], bb[c]);
        H[c][1] = gelu2_pair(acc[4 * c + 2], acc[4 * c + 3], bb[c]);
      }
      wg_fence();
#pragma unroll
      for (int j = 0; j < 7; j++)
        wgmma_rs_n8(dot, H[2 * j][0], H[2 * j][1], H[2 * j + 1][0], H[2 * j + 1][1], dk + (uint64_t)((OFF_W2 + j * 256) >> 4), j > 0);
      wg_commit();
      wg_wait<0>();
      reg_fence(dot);
    }
    __syncwarp();
    mbar_wait(BAR(BAR_EPOCH), 0);
    if (q == 0) {
      const unsigned epoch = lds_u32(sb + OFF_EPOCH);
#pragma unroll
      for (int r = 0; r < 2; r++) {
        const int row = wg * 64 + w4 * 16 + g + 8 * r;
        const unsigned long long pk = ((unsigned long long)epoch << 32) | (unsigned long long)__float_as_uint(dot[2 * r]);
        asm volatile("st.relaxed.gpu.global.u64 [%0], %1;" ::"l"(P.part + cta * 128 + row), "l"(pk) : "memory");
      }
    }
    __syncwarp();
  } else {
    const int t = tid - 256;
    const bool is_arr = (t == 192);
    unsigned ctr0 = 0;
    if (is_arr) asm volatile("ld.relaxed.gpu.global.u32 %0, [%1];" : "=r"(ctr0) : "l"(P.ctr) : "memory");
    {
      const int kind = role.x >> 24, w = warp - 8, rgrp = (role.y >> 24) & 15, rj = role.y >> 28;
      const unsigned char* wsb = reinterpret_cast<const unsigned char*>(P.ws);
      if (kind < 5 && elect_one()) {
        const uint32_t bytes = role.y & 0xffff;
        const uint32_t o = w * 8192;
        if (w == 0) mbar_expect_tx(BAR(BAR_Q), bytes);
        if (o < bytes) bulk_g2s(sb + OFF_G0 + o, wsb + (role.x & 0xffffff) + o, min(bytes - o, 8192u), BAR(BAR_Q));
      }
      __syncwarp();
      const StaticTabs* T = reinterpret_cast<const StaticTabs*>(smem + OFF_STAB);
      uint32_t* img32 = reinterpret_cast<uint32_t*>(P.img);
      const unsigned char* raw = smem + OFF_G0 + ((role.y >> 16) & 127);
      uint32_t chk = 0;
      if (kind < 3) chk = layer_row(kind, rgrp, rj * SETUP_WARPS + w, lane, raw, T, BAR(BAR_Q), BAR(BAR_STAB), P.wout, img32);
      else if (kind == 3) chk = x1_row(rgrp, rj * SETUP_WARPS + w, lane, raw, T, BAR(BAR_Q), BAR(BAR_STAB), img32);
      if (__any_sync(0xffffffffu, chk != 0)) __trap();
      if (lane == 0) mbar_arrive(BAR(BAR_SETUP));
    }
    if (is_arr) {
      asm volatile("" : "+r"(ctr0));
      *reinterpret_cast<volatile unsigned*>(smem + OFF_EPOCH) = (ctr0 >> 7) + 1;
      mbar_wait(BAR(BAR_SETUP), 0);
      if ((role.x >> 24) == 3) asm volatile("red.relaxed.gpu.global.add.u32 [%0], 1;" ::"l"(P.ctr + 32) : "memory");
      asm volatile("red.relaxed.gpu.global.add.u32 [%0], 1;" ::"l"(P.ctr) : "memory");
      mbar_arrive(BAR(BAR_EPOCH));
    }
    __syncwarp();
    {
      const int c0 = (nq >> 1) * 208 + (nq & 1) * 96, nw = (nq & 1) ? 112 : 96;
      if (t < 56) {
        const int n = 2 * t;
        const uint32_t v = (n < nw) ? __ldg(reinterpret_cast<const uint32_t*>(P.b1 + c0 + n)) : 0u;
        reinterpret_cast<uint32_t*>(smem + OFF_BW)[(t & 3) * 16 + (t >> 2)] = v;
      }
      if (t >= 64 && t < 64 + 112) {
        const int k = t - 64;
        const float w = (k < nw) ? 0.5f * bf2f(__ldg(P.w2 + c0 + k)) : 0.f;
        unsigned char* base = smem + OFF_W2 + (k >> 4) * 256 + ((k >> 3) & 1) * 128;
        *reinterpret_cast<bf16*>(base + (k & 7) * 2) = __float2bfloat16(w);
        if ((k & 7) == 0) {
#pragma unroll
          for (int r = 1; r < 8; r++) *reinterpret_cast<uint4*>(base + r * 16) = make_uint4(0, 0, 0, 0);
        }
      }
      fence_proxy_async();
    }
    if (t >= 128 && t < 192) {
      int u = t - 128, l = u >> 5, qq = (u >> 3) & 3, a = u & 7;
      float wtv = 0.f;
      if (a < 6) wtv = bf2f(__ldg(P.wout + l * NF + 8 * (a >> 1) + 2 * qq + (a & 1)));
      else if (a == 6 && !(qq & 1)) wtv = bf2f(__ldg(P.wout + l * NF + 24 + (qq >> 1)));
      reinterpret_cast<float*>(smem + OFF_WTAB)[u] = wtv;
    }
    mbar_arrive(BAR(BAR_TABS));
    mbar_wait(BAR(BAR_X0), 0);
    mbar_wait(BAR(BAR_TABS), 0);
  }

  const uint32_t selU = (q == 0) ? 0x1010u : (q == 1) ? 0x3232u : (q == 2) ? 0x3210u : 0x7654u;
  const uint32_t selV = (q < 2) ? 0x3210u : 0x7654u;
  uint32_t bo_raw = __ldg(reinterpret_cast<const unsigned short*>(P.bout));
  mbar_wait(BAR(BAR_EPOCH), 0);
  mbar_wait(BAR(BAR_STAB), 0);
  const unsigned epoch = lds_u32(sb + OFF_EPOCH);

  uint32_t X[2][13];
  auto load_x = [&](int sl) {
    const uint4 o = *reinterpret_cast<const uint4*>(smem + OFF_LOFF + lane * 16);
    const uint32_t xo = sb + OFF_XOFF + sl * 52;
    const uint32_t tb = sb + OFF_TAB, hx = ((lane >> 3) & 1) << 4;
    const uint32_t a0 = lds_u16(xo + (o.x & 0xffff)), a1 = lds_u16(xo + (o.x >> 16));
    const uint32_t a2 = lds_u16(xo + (o.y & 0xffff)), a3 = lds_u16(xo + (o.y >> 16));
    const uint32_t a4 = lds_u16(xo + (o.z & 0xffff)), a5 = lds_u16(xo + (o.z >> 16));
    const uint32_t a6 = lds_u16(xo + (o.w & 0xffff));
    ldsm_x4_t(tb + (a0 ^ hx), X[0][0], X[1][0], X[0][1], X[1][1]);
    ldsm_x4_t(tb + (a1 ^ hx), X[0][2], X[1][2], X[0][3], X[1][3]);
    ldsm_x4_t(tb + (a2 ^ hx), X[0][4], X[1][4], X[0][5], X[1][5]);
    ldsm_x4_t(tb + (a3 ^ hx), X[0][6], X[1][6], X[0][7], X[1][7]);
    ldsm_x4_t(tb + (a4 ^ hx), X[0][8], X[1][8], X[0][9], X[1][9]);
    ldsm_x4_t(tb + (a5 ^ hx), X[0][10], X[1][10], X[0][11], X[1][11]);
    ldsm_x2_t(tb + (a6 ^ hx), X[0][12], X[1][12]);
  };
  load_x(nq * 32 + wg * 4 + w4);
#pragma unroll 1
  for (int it = 0; it < 2; it++) {
    const int sl = nq * 32 + (wg + 4 * it) * 4 + w4;
    float S = 0.f;
    uint32_t vx[2][4], vg[2][4];
    {
      float a0[28];
      if (it == 0) mbar_wait(BAR(BAR_IMG + 0), 0);
      g0_rec<0>(a0, X, selU, selV, dk, BAR(BAR_G0B), it == 0);
      wg_wait<0>();
      reg_fence(a0);
      const float4* wt = reinterpret_cast<const float4*>(smem + OFF_WTAB) + q * 2;
      float4 wa = wt[0], wb = wt[1];
#pragma unroll
      for (int r = 0; r < 2; r++) {
        S = fmaf(wa.x, a0[0 + 2 * r], S); S = fmaf(wa.y, a0[1 + 2 * r], S);
        S = fmaf(wa.z, a0[4 + 2 * r], S); S = fmaf(wa.w, a0[5 + 2 * r], S);
        S = fmaf(wb.x, a0[8 + 2 * r], S); S = fmaf(wb.y, a0[9 + 2 * r], S);
        S = fmaf(wb.z, a0[24 + 2 * r], S);
#pragma unroll
        for (int c = 0; c < 3; c++) {
          vx[r][c] = pack_bf16(a0[4 * c + 2 * r], a0[4 * c + 2 * r + 1]);
          vg[r][c] = pack_bf16(a0[12 + 4 * c + 2 * r], a0[12 + 4 * c + 2 * r + 1]);
        }
        vx[r][3] = pack_bf16(a0[24 + 2 * r], 0.f);
        vg[r][3] = pack_bf16(a0[24 + 2 * r + 1], 0.f);
      }
    }
    float g3[16], xa[16];
    if (it == 0) {
      mbar_wait(BAR(BAR_IMG + 2), 0);
      mbar_wait(BAR(BAR_IMG + 1), 0);
      mbar_wait(BAR(BAR_IMG + 3), 0);
    }
    layer_rec<0, OFF_LB>(xa, vx, X, dk);
    wg_wait<1>();
    layer_first<OFF_LA, 3>(g3, vg, X, dk);
    wg_wait<1>();
    reg_fence(xa);
    {
      const float4* wt = reinterpret_cast<const float4*>(smem + OFF_WTAB) + 8 + q * 2;
      float4 wa = wt[0], wb = wt[1];
#pragma unroll
      for (int r = 0; r < 2; r++) {
        S = fmaf(wa.x, xa[0 + 2 * r], S); S = fmaf(wa.y, xa[1 + 2 * r], S);
        S = fmaf(wa.z, xa[4 + 2 * r], S); S = fmaf(wa.w, xa[5 + 2 * r], S);
        S = fmaf(wb.x, xa[8 + 2 * r], S); S = fmaf(wb.y, xa[9 + 2 * r], S);
        S = fmaf(wb.z, xa[12 + 2 * r], S);
#pragma unroll
        for (int c = 0; c < 3; c++) vx[r][c] = pack_bf16(xa[4 * c + 2 * r], xa[4 * c + 2 * r + 1]);
        vx[r][3] = pack_bf16(xa[12 + 2 * r], 0.f);
      }
    }
    layer_rec<3, OFF_LA>(g3, vg, X, dk);
    wg_wait<1>();
    const unsigned long long* pp = P.part + (grp * 4 + (lane & 3)) * 128 + sl;
    unsigned long long pk;
    asm volatile("ld.relaxed.gpu.global.u64 %0, [%1];" : "=l"(pk) : "l"(pp) : "memory");
    float xc[16];
    layer_rec<0, OFF_LC>(xc, vx, X, dk);
    if (it == 0) load_x(sl + 16);
    wg_wait<0>();
    reg_fence(xc);
    reg_fence(g3);
    {
      float Se = 0.f;
#pragma unroll
      for (int r = 0; r < 2; r++) {
#pragma unroll
        for (int c = 0; c < 3; c++) {
          S = fmaf(g3[4 * c + 2 * r], xc[4 * c + 2 * r], S);
          S = fmaf(g3[4 * c + 2 * r + 1], xc[4 * c + 2 * r + 1], S);
        }
        Se = fmaf(g3[12 + 2 * r], xc[12 + 2 * r], Se);
      }
      if (!(q & 1)) S += Se;
    }
#pragma unroll
    for (int o = 16; o > 0; o >>= 1) S += __shfl_xor_sync(0xffffffffu, S, o);
    {
      uint32_t spin = 0;
      while (lane < 4 && (unsigned)(pk >> 32) != epoch) {
        asm volatile("ld.relaxed.gpu.global.u64 %0, [%1];" : "=l"(pk) : "l"(pp) : "memory");
        if (++spin > (1u << 24)) __trap();
      }
      __syncwarp();
      float dv = __uint_as_float((unsigned)pk);
      float d01 = dv + __shfl_xor_sync(0xffffffffu, dv, 1);
      float dsum = d01 + __shfl_xor_sync(0xffffffffu, d01, 2);
      asm volatile("" : "+r"(bo_raw));
      if (lane == 0) P.out[grp * 128 + sl] = __float2bfloat16(S + dsum + __uint_as_float(bo_raw << 16));
    }
    __syncwarp();
  }
}

__global__ void __launch_bounds__(128) fallback_kernel(const int* __restrict__ idx, const bf16* __restrict__ table, const bf16* __restrict__ ws,
                                                       const bf16* __restrict__ wout, const bf16* __restrict__ w1, const bf16* __restrict__ b1,
                                                       const bf16* __restrict__ w2, const bf16* __restrict__ bout, bf16* __restrict__ out) {
  __shared__ float x0[416], xa[416], xb[416], red[128];
  const int b = blockIdx.x, t = threadIdx.x;
  for (int i = t; i < 416; i += 128) { x0[i] = bf2f(table[idx[b * NF + i / 16] * 16 + (i & 15)]); xa[i] = x0[i]; }
  __syncthreads();
  float acc = 0.f;
  float* cur = xa;
  float* nxt = xb;
  for (int l = 0; l < 6; l++) {
    for (int o = t; o < 416; o += 128) {
      const int h = o >> 4, d = o & 15;
      const bf16* w = ws + (l * NF + h) * NF * NF;
      float s = 0.f;
      for (int i = 0; i < NF; i++) {
        float u = 0.f;
        for (int j = 0; j < NF; j++) u = fmaf(bf2f(w[i * NF + j]), x0[j * 16 + d], u);
        s = fmaf(u, cur[i * 16 + d], s);
      }
      nxt[o] = s;
      acc = fmaf(s, bf2f(wout[l * NF + h]), acc);
    }
    __syncthreads();
    float* tmp = cur; cur = nxt; nxt = tmp;
  }
  for (int n = t; n < 416; n += 128) {
    float h = 0.f;
    for (int k = 0; k < 416; k++) h = fmaf(x0[k], bf2f(w1[k * 416 + n]), h);
    h += bf2f(b1[n]);
    const float gl = 0.5f * h * (1.f + tanhf(0.7978845608028654f * (h + 0.044715f * h * h * h)));
    acc = fmaf(gl, bf2f(w2[n]), acc);
  }
  red[t] = acc;
  __syncthreads();
  for (int o = 64; o > 0; o >>= 1) { if (t < o) red[t] += red[t + o]; __syncthreads(); }
  if (t == 0) out[b] = __float2bfloat16(red[0] + bf2f(bout[0]));
}

typedef CUresult (*EncodeFn)(CUtensorMap*, CUtensorMapDataType, cuuint32_t, void*, const cuuint64_t*, const cuuint64_t*,
                             const cuuint32_t*, const cuuint32_t*, CUtensorMapInterleave, CUtensorMapSwizzle,
                             CUtensorMapL2promotion, CUtensorMapFloatOOBfill);

extern "C" void kernel_launch(void* const* d_in, const int* in_sizes, int n_in, void* d_out, int out_size) {
  const int* idx = (const int*)d_in[0];
  const bf16* table = (const bf16*)d_in[1];
  const bf16* ws = (const bf16*)d_in[2];
  const bf16* wout = (const bf16*)d_in[3];
  const bf16* w1 = (const bf16*)d_in[4];
  const bf16* b1 = (const bf16*)d_in[5];
  const bf16* w2 = (const bf16*)d_in[6];
  const bf16* bo = (const bf16*)d_in[7];
  bf16* out = (bf16*)d_out;

  static EncodeFn enc = nullptr;
  static Params P;
  static int n_sm = 0;
  if (!n_sm) {
    int dev = 0;
    cudaGetDevice(&dev);
    cudaDeviceGetAttribute(&n_sm, cudaDevAttrMultiProcessorCount, dev);
  }
  if (n_sm < NCTA + NHELP) {
    fallback_kernel<<<4096, 128, 0, cudaStreamPerThread>>>(idx, table, ws, wout, w1, b1, w2, bo, out);
    return;
  }
  if (!enc) {
    void* fn = nullptr;
    cudaDriverEntryPointQueryResult qr;
    cudaGetDriverEntryPoint("cuTensorMapEncodeTiled", &fn, cudaEnableDefault, &qr);
    enc = (EncodeFn)fn;
    cudaFuncSetAttribute(main_kernel, cudaFuncAttributeMaxDynamicSharedMemorySize, SMEM_BYTES);
    void* p;
    cudaGetSymbolAddress(&p, g_img); P.img = (unsigned char*)p;
    cudaGetSymbolAddress(&p, g_part); P.part = (unsigned long long*)p;
    cudaGetSymbolAddress(&p, g_ctr); P.ctr = (unsigned*)p;
    cudaGetSymbolAddress(&p, g_tabs); P.tabs = p;
    P.dk = make_desc(0, 128, 256, 0);
    P.dmn = make_desc(0, 8192, 1024, 1);
    for (int c = 0; c < NCTA; c++) P.role[c] = make_role(c);
  }
  P.idx = idx; P.table = table; P.ws = ws; P.wout = wout; P.b1 = b1; P.w2 = w2; P.bout = bo; P.out = out;
  TmaMaps tms;
  for (int h = 0; h < 4; h++) {
    const int c0 = (h >> 1) * 208 + (h & 1) * 96, nw = (h & 1) ? 112 : 96;
    cuuint64_t dims[2] = {(cuuint64_t)nw, 416};
    cuuint64_t strides[1] = {832};
    cuuint32_t box[2] = {64, 64};
    cuuint32_t es[2] = {1, 1};
    enc(&tms.m[h], CU_TENSOR_MAP_DATA_TYPE_BFLOAT16, 2, (void*)(w1 + c0), dims, strides, box, es,
        CU_TENSOR_MAP_INTERLEAVE_NONE, CU_TENSOR_MAP_SWIZZLE_128B, CU_TENSOR_MAP_L2_PROMOTION_L2_128B,
        CU_TENSOR_MAP_FLOAT_OOB_FILL_NONE);
  }
  main_kernel<<<NCTA + NHELP, 512, SMEM_BYTES, cudaStreamPerThread>>>(P, tms);
}
```
